```python
import torch

def _softmax(x, axis=-1):
    return torch.softmax(x, dim=axis)

def _gelu(x):
    return torch.nn.functional.gelu(x, approximate='tanh')

def _silu(x):
    return torch.nn.functional.silu(x)

def _sigmoid(x):
    return torch.sigmoid(x)

def _layernorm(x, axis=-1, eps=1e-05):
    m = x.mean(dim=axis, keepdim=True)
    v = x.var(dim=axis, keepdim=True, unbiased=False)
    return (x - m) / torch.sqrt(v + eps)

def _scatter_add(tgt, idx, src, axis=0):
    return tgt.clone().index_add_(axis, idx, src)

def _segment_sum(src, seg, n):
    out = torch.zeros((n,) + src.shape[1:], dtype=src.dtype)
    return out.index_add_(0, seg, src)

def _pad(x, pw):
    flat = tuple((v for pair in reversed(pw) for v in pair))
    return torch.nn.functional.pad(x, flat)
kernel_name = 'adaLN_cond__ssm_conv_h3__glu_gated_bilinear__prompt'

def setup_inputs():

    _w = lambda a: (lambda t: t.to(torch.bfloat16) if t.is_floating_point() else t)(torch.as_tensor(a))

    def _A_setup():
        B, S, D = (1, 2048, 640)
        ks = 4
        return {'q': _w((lambda *s: torch.randn(*s, dtype=torch.bfloat16) * 0.05)(B, S, D)), 'k': _w((lambda *s: torch.randn(*s, dtype=torch.bfloat16) * 1.6)(B, S, D)), 'v': _w((lambda *s: torch.randn(*s, dtype=torch.bfloat16) * 1.6)(B, S, D)), 'shift_k': _w((lambda *s: torch.randn(*s, dtype=torch.bfloat16) * 1.6)(D, ks) * 0.5), 'ssm_k': _w((lambda *s: torch.randn(*s, dtype=torch.bfloat16) * 1.6)(D, S) * (1.0 / S ** 0.5)), 'ssm_D': _w((lambda *s: torch.randn(*s, dtype=torch.bfloat16) * 1.6)(D))}
    _A_in = _A_setup()

    def _B_setup():
        B, S, D, F = (1, 2048, 640, 1536)
        return {'x': _w((lambda *s: torch.randn(*s, dtype=torch.bfloat16) * 0.05)(B, S, D)), 'w_gate': _w((lambda *s: torch.randn(*s, dtype=torch.bfloat16) * 3.2)(D, F) * D ** (-0.5)), 'w_up': _w((lambda *s: torch.randn(*s, dtype=torch.bfloat16) * 3.2)(D, F) * D ** (-0.5)), 'w_down': _w((lambda *s: torch.randn(*s, dtype=torch.bfloat16) * 3.2)(F, D) * F ** (-0.5))}
    _B_in = _B_setup()
    return {'A_q': _A_in['q'], 'A_k': _A_in['k'], 'A_v': _A_in['v'], 'A_shift_k': _A_in['shift_k'], 'A_ssm_k': _A_in['ssm_k'], 'A_ssm_D': _A_in['ssm_D'], 'B_x': _B_in['x'], 'B_w_gate': _B_in['w_gate'], 'B_w_up': _B_in['w_up'], 'B_w_down': _B_in['w_down'], 'c': _w((lambda *s: torch.randn(*s, dtype=torch.bfloat16) * 0.2)(1, 640) * 8.0), 'w_mod': _w((lambda *s: torch.randn(*s, dtype=torch.bfloat16) * 0.2)(640, 6 * 640) * 640 ** (-0.5) * 8.0)}

def reference(A_q, A_k, A_v, A_shift_k, A_ssm_k, A_ssm_D, B_x, B_w_gate, B_w_up, B_w_down, c, w_mod):

    def _A_ref(q, k, v, shift_k, ssm_k, ssm_D):
        B, S, D = q.shape
        ks = shift_k.shape[-1]
        k_pad = _pad(k, ((0, 0), (ks - 1, 0), (0, 0)))
        k_shift = torch.zeros_like(k)
        for t in range(ks):
            k_shift = k_shift + k_pad[:, t:t + S, :] * shift_k[:, ks - 1 - t][None, None, :]
        kv = k_shift * v
        L = 2 * S
        kv_pad = _pad(kv, ((0, 0), (0, S), (0, 0)))
        kf_pad = _pad(ssm_k, ((0, 0), (0, S)))
        kv_f = (lambda x, axes=(-2, -1): torch.fft.rfft2(x.float(), dim=axes))(kv_pad[:, None, :, :], axes=(1, 2))
        kf_f = (lambda x, axes=(-2, -1): torch.fft.rfft2(x.float(), dim=axes))(kf_pad[:, None, :], axes=(1, 2))
        kf_f = (lambda x, *d: x.permute(*d))(kf_f, 1, 2, 0)
        y_f = kv_f * kf_f[None, :, :, :]
        y = (lambda x, s, axes=(-2, -1): torch.fft.irfft2(x, s=s, dim=axes).to(torch.bfloat16))(y_f, (1, L), axes=(1, 2))[:, 0, :S, :]
        y = y + kv * ssm_D[None, None, :]
        return q * y

    def _B_ref(x, w_gate, w_up, w_down):
        g = torch.einsum('bsd,df->bsf', x, w_gate)
        u = torch.einsum('bsd,df->bsf', x, w_up)
        h = g * u
        return torch.einsum('bsf,fd->bsd', h, w_down)
    x = A_q
    mod = (_silu(c) @ w_mod).reshape(c.shape[0], 6, 1, -1)
    sa, ca, ga, sb, cb, gb = (mod[:, 0].clone(), mod[:, 1].clone(), mod[:, 2].clone(), mod[:, 3].clone(), mod[:, 4].clone(), mod[:, 5].clone())
    h = _layernorm(x, axis=-1) * (1 + ca) + sa
    x = x + ga * _A_ref(h, A_k, A_v, A_shift_k, A_ssm_k, A_ssm_D)
    h = _layernorm(x, axis=-1) * (1 + cb) + sb
    x = x + gb * _B_ref(h, B_w_gate, B_w_up, B_w_down)
    return x
```

```cpp
#include <cuda_runtime.h>
#include <cuda.h>
#include <cuda_bf16.h>
#include <cstdint>

namespace {

constexpr int S_ = 2048, D_ = 640, F_ = 1536;

__device__ __align__(1024) __nv_bfloat16 g_kvT[D_ * S_];
__device__ __align__(1024) __nv_bfloat16 g_qT[D_ * S_];
__device__ __align__(1024) __nv_bfloat16 g_x1T[D_ * S_];
__device__ __align__(1024) __nv_bfloat16 g_h[S_ * F_];
__device__ __align__(1024) float2 g_st1[S_];
__device__ __align__(1024) uint32_t g_mod[6 * D_];
__device__ __align__(1024) float4 g_vv[F_];
__device__ __align__(1024) uint32_t g_sync[32 * 32 + 256 * 8];
#define TSTAMP(i) do { } while (0)

struct Params {
  CUtensorMap m_q, m_qT, m_wm, m_wg, m_wu, m_wgs, m_wus, m_x1T, m_w2, m_h, m_out;
  const __nv_bfloat16 *q, *k, *v, *shift, *ssm, *ssmD, *c;
};

constexpr uint32_t SLOT = 32768;
constexpr uint32_t O_WMOD = 65536;
constexpr uint32_t O_QSTG = 106496;
constexpr uint32_t O_KV = 131072;
constexpr uint32_t O_QIN = 153088;
constexpr uint32_t O_QROW = 173568;
constexpr uint32_t O_SSM = 196608;
constexpr uint32_t SEQ = 4112, KSEQ = 4368, KPAD = 272;
constexpr uint32_t O_CB = 217216;
constexpr uint32_t O_SB = O_CB + 1280;
constexpr uint32_t O_SILU = O_SB + 1280;
constexpr uint32_t O_VV = O_SILU + 1280;
constexpr uint32_t O_GB = O_VV + 3072;
constexpr uint32_t O_BAR = O_GB + 640;
constexpr uint32_t SMEM_BYTES = O_BAR + 1024;
enum { B_FULL = 0, B_EMPTY = 6, B_W2F = 12, B_W2E = 18, B_HF = 24, B_HE = 32, B_SSM = 40, B_KV = 45, B_Y = 50, B_QIN = 55, B_QF = 56,
       B_WM = 57, B_MODDONE = 59, B_P2DONE = 60, B_CB = 61, B_VV = 62, B_X1 = 63, B_STRIP = 64, B_STAGED = 65, B_RED = 67, B_RDY = 68, B_NUM = 69 };
__device__ __forceinline__ uint32_t w2entry(int e) { return e < 3 ? 65536 + e * 20480 : (e - 3) * 20480; }

__device__ __forceinline__ uint32_t smem_u32(const void* p) { return (uint32_t)__cvta_generic_to_shared(p); }
__device__ __forceinline__ void mbar_init(uint32_t bar, uint32_t cnt) { asm volatile("mbarrier.init.shared::cta.b64 [%0], %1;" ::"r"(bar), "r"(cnt) : "memory"); }
__device__ __forceinline__ void mbar_expect(uint32_t bar, uint32_t bytes) { asm volatile("mbarrier.arrive.expect_tx.shared::cta.b64 _, [%0], %1;" ::"r"(bar), "r"(bytes) : "memory"); }
__device__ __forceinline__ void mbar_arrive(uint32_t bar) { asm volatile("mbarrier.arrive.shared::cta.b64 _, [%0];" ::"r"(bar) : "memory"); }
__device__ __forceinline__ void mbar_wait(uint32_t bar, uint32_t parity) {
  asm volatile("{\n .reg .pred p;\n .reg .u32 c;\n mov.u32 c, 0;\n LOOP:\n mbarrier.try_wait.parity.shared::cta.b64 p, [%0], %1;\n @p bra DONE;\n add.u32 c, c, 1;\n setp.lt.u32 p, c, 200000;\n @p bra LOOP;\n DONE:\n }" ::"r"(bar), "r"(parity) : "memory");
}
__device__ __forceinline__ void mbar_wait_cluster(uint32_t bar, uint32_t parity) {
  asm volatile("{\n .reg .pred p;\n .reg .u32 c;\n mov.u32 c, 0;\n LOOP:\n mbarrier.try_wait.parity.acquire.cluster.shared::cta.b64 p, [%0], %1;\n @p bra DONE;\n add.u32 c, c, 1;\n setp.lt.u32 p, c, 200000;\n @p bra LOOP;\n DONE:\n }" ::"r"(bar), "r"(parity) : "memory");
}
__device__ __forceinline__ void poll_ge(const uint32_t* p, uint32_t target) {
  asm volatile("{\n .reg .pred p;\n .reg .u32 c, v;\n mov.u32 c, 0;\n LOOP:\n ld.acquire.gpu.global.u32 v, [%0];\n sub.u32 v, v, %1;\n setp.ge.s32 p, v, 0;\n @p bra DONE;\n add.u32 c, c, 1;\n setp.lt.u32 p, c, 400000;\n @p bra LOOP;\n DONE:\n fence.proxy.async;\n }" ::"l"(p), "r"(target) : "memory");
}
__device__ __forceinline__ uint32_t poll_tag(const uint32_t* p, uint32_t tag) {
  uint32_t v;
  asm volatile("{\n .reg .pred p;\n .reg .u32 c, t;\n mov.u32 c, 0;\n LOOP:\n ld.relaxed.gpu.global.u32 %0, [%1];\n shr.u32 t, %0, 16;\n setp.eq.u32 p, t, %2;\n @p bra DONE;\n add.u32 c, c, 1;\n setp.lt.u32 p, c, 400000;\n @p bra LOOP;\n DONE:\n }" : "=r"(v) : "l"(p), "r"(tag) : "memory");
  return v;
}
__device__ __forceinline__ uint2 poll_tag2(const uint32_t* p, uint32_t tag) {
  uint2 v;
  asm volatile("{\n .reg .pred p;\n .reg .u32 c, t, u;\n mov.u32 c, 0;\n LOOP:\n ld.relaxed.gpu.global.v2.u32 {%0,%1}, [%2];\n shr.u32 t, %0, 16;\n shr.u32 u, %1, 16;\n setp.eq.u32 p, t, %3;\n setp.eq.and.u32 p, u, %3, p;\n @p bra DONE;\n add.u32 c, c, 1;\n setp.lt.u32 p, c, 400000;\n @p bra LOOP;\n DONE:\n }" : "=r"(v.x), "=r"(v.y) : "l"(p), "r"(tag) : "memory");
  return v;
}
__device__ __forceinline__ void signal_add(uint32_t* p) { asm volatile("fence.acq_rel.gpu;\n red.relaxed.gpu.global.add.u32 [%0], 1;" ::"l"(p) : "memory"); }
__device__ __forceinline__ void tma2d(uint32_t dst, const CUtensorMap* m, int x, int y, uint32_t bar) {
  asm volatile("cp.async.bulk.tensor.2d.shared::cluster.global.mbarrier::complete_tx::bytes [%0], [%1, {%3, %4}], [%2];" ::"r"(dst), "l"(m), "r"(bar), "r"(x), "r"(y) : "memory");
}
__device__ __forceinline__ void tma2d_store(const CUtensorMap* m, uint32_t src, int x, int y) {
  asm volatile("cp.async.bulk.tensor.2d.global.shared::cta.bulk_group [%0, {%2, %3}], [%1];" ::"l"(m), "r"(src), "r"(x), "r"(y) : "memory");
}
__device__ __forceinline__ void bulk_ld(uint32_t dst, const void* src, uint32_t bytes, uint32_t bar) {
  asm volatile("cp.async.bulk.shared::cluster.global.mbarrier::complete_tx::bytes [%0], [%1], %2, [%3];" ::"r"(dst), "l"(src), "r"(bytes), "r"(bar) : "memory");
}
__device__ __forceinline__ void bulk_commit() { asm volatile("cp.async.bulk.commit_group;" ::: "memory"); }
__device__ __forceinline__ void bulk_wait0() { asm volatile("cp.async.bulk.wait_group 0;" ::: "memory"); }
__device__ __forceinline__ void bulk_wait0_read() { asm volatile("cp.async.bulk.wait_group.read 0;" ::: "memory"); }
__device__ __forceinline__ void fence_async() { asm volatile("fence.proxy.async;" ::: "memory"); }
__device__ __forceinline__ void fence_async_smem() { asm volatile("fence.proxy.async.shared::cta;" ::: "memory"); }
__device__ __forceinline__ void bar_sync(int id, int n) { asm volatile("bar.sync %0, %1;" ::"r"(id), "r"(n) : "memory"); }
__device__ __forceinline__ void bar_arrive(int id, int n) { asm volatile("bar.arrive %0, %1;" ::"r"(id), "r"(n) : "memory"); }
__device__ __forceinline__ void wg_fence() { asm volatile("wgmma.fence.sync.aligned;" ::: "memory"); }
__device__ __forceinline__ void wg_commit() { asm volatile("wgmma.commit_group.sync.aligned;" ::: "memory"); }
template <int N> __device__ __forceinline__ void wg_wait() { asm volatile("wgmma.wait_group.sync.aligned %0;" ::"n"(N) : "memory"); }
__device__ __forceinline__ void ldsm4(uint32_t a, uint32_t& r0, uint32_t& r1, uint32_t& r2, uint32_t& r3) {
  asm volatile("ldmatrix.sync.aligned.m8n8.x4.shared.b16 {%0,%1,%2,%3}, [%4];" : "=r"(r0), "=r"(r1), "=r"(r2), "=r"(r3) : "r"(a) : "memory");
}
__device__ __forceinline__ void ldsm4t(uint32_t a, uint32_t& r0, uint32_t& r1, uint32_t& r2, uint32_t& r3) {
  asm volatile("ldmatrix.sync.aligned.m8n8.x4.trans.shared.b16 {%0,%1,%2,%3}, [%4];" : "=r"(r0), "=r"(r1), "=r"(r2), "=r"(r3) : "r"(a) : "memory");
}
__device__ __forceinline__ void ldsm2t(uint32_t a, uint32_t& r0, uint32_t& r1) {
  asm volatile("ldmatrix.sync.aligned.m8n8.x2.trans.shared.b16 {%0,%1}, [%2];" : "=r"(r0), "=r"(r1) : "r"(a) : "memory");
}
__device__ __forceinline__ void stsm4(uint32_t a, uint32_t r0, uint32_t r1, uint32_t r2, uint32_t r3) {
  asm volatile("stmatrix.sync.aligned.m8n8.x4.shared.b16 [%0], {%1,%2,%3,%4};" ::"r"(a), "r"(r0), "r"(r1), "r"(r2), "r"(r3) : "memory");
}
__device__ __forceinline__ void mma16816(float* d, uint32_t a0, uint32_t a1, uint32_t a2, uint32_t a3, uint32_t b0, uint32_t b1) {
  asm volatile("mma.sync.aligned.m16n8k16.row.col.f32.bf16.bf16.f32 {%0,%1,%2,%3}, {%4,%5,%6,%7}, {%8,%9}, {%0,%1,%2,%3};"
               : "+f"(d[0]), "+f"(d[1]), "+f"(d[2]), "+f"(d[3]) : "r"(a0), "r"(a1), "r"(a2), "r"(a3), "r"(b0), "r"(b1));
}
__device__ __forceinline__ uint32_t lds32(uint32_t a) { uint32_t v; asm volatile("ld.shared.u32 %0, [%1];" : "=r"(v) : "r"(a) : "memory"); return v; }
__device__ __forceinline__ uint2 lds64(uint32_t a) { uint2 v; asm volatile("ld.shared.v2.u32 {%0,%1}, [%2];" : "=r"(v.x), "=r"(v.y) : "r"(a) : "memory"); return v; }
__device__ __forceinline__ uint4 lds128(uint32_t a) { uint4 v; asm volatile("ld.shared.v4.u32 {%0,%1,%2,%3}, [%4];" : "=r"(v.x), "=r"(v.y), "=r"(v.z), "=r"(v.w) : "r"(a) : "memory"); return v; }
__device__ __forceinline__ float4 lds128f(uint32_t a) { float4 v; asm volatile("ld.shared.v4.f32 {%0,%1,%2,%3}, [%4];" : "=f"(v.x), "=f"(v.y), "=f"(v.z), "=f"(v.w) : "r"(a) : "memory"); return v; }
__device__ __forceinline__ float2 lds64f(uint32_t a) { float2 v; asm volatile("ld.shared.v2.f32 {%0,%1}, [%2];" : "=f"(v.x), "=f"(v.y) : "r"(a) : "memory"); return v; }
__device__ __forceinline__ void sts32(uint32_t a, uint32_t v) { asm volatile("st.shared.u32 [%0], %1;" ::"r"(a), "r"(v) : "memory"); }
__device__ __forceinline__ void sts16(uint32_t a, uint16_t v) { asm volatile("st.shared.u16 [%0], %1;" ::"r"(a), "h"(v) : "memory"); }
__device__ __forceinline__ uint32_t prmt(uint32_t a, uint32_t b, uint32_t s) { uint32_t r; asm("prmt.b32 %0, %1, %2, %3;" : "=r"(r) : "r"(a), "r"(b), "r"(s)); return r; }
__device__ __forceinline__ uint32_t hfma2(uint32_t a, uint32_t b, uint32_t c) { uint32_t r; asm("fma.rn.bf16x2 %0, %1, %2, %3;" : "=r"(r) : "r"(a), "r"(b), "r"(c)); return r; }
__device__ __forceinline__ uint32_t hmul2(uint32_t a, uint32_t b) { uint32_t r; asm("mul.rn.bf16x2 %0, %1, %2;" : "=r"(r) : "r"(a), "r"(b)); return r; }
__device__ __forceinline__ uint32_t pack2(float lo, float hi) { uint32_t r; asm("cvt.rn.bf16x2.f32 %0, %1, %2;" : "=r"(r) : "f"(hi), "f"(lo)); return r; }
__device__ __forceinline__ float blo(uint32_t v) { return __uint_as_float(v << 16); }
__device__ __forceinline__ float bhi(uint32_t v) { return __uint_as_float(v & 0xffff0000u); }
__device__ __forceinline__ float rbf(float x) { return blo(pack2(x, 0.f)); }
__device__ __forceinline__ uint64_t mkdesc(uint32_t addr, uint32_t lbo, uint32_t sbo, uint32_t swz) {
  return (uint64_t)((addr & 0x3FFFF) >> 4) | ((uint64_t)(lbo >> 4) << 16) | ((uint64_t)(sbo >> 4) << 32) | ((uint64_t)swz << 62);
}
template <int N> __device__ __forceinline__ void regfence(float* d) {
#pragma unroll
  for (int i = 0; i < N; i++) asm volatile("" : "+f"(d[i])::"memory");
}

__device__ __forceinline__ void wgmma_rs_32_0(float* d, uint32_t a0, uint32_t a1, uint32_t a2, uint32_t a3, uint64_t db, int sd) {
  asm volatile("{ .reg .pred p; setp.ne.b32 p, %21, 0; wgmma.mma_async.sync.aligned.m64n32k16.f32.bf16.bf16 {%0,%1,%2,%3,%4,%5,%6,%7,%8,%9,%10,%11,%12,%13,%14,%15}, {%16,%17,%18,%19}, %20, p, 1, 1, 0; }"
   : "+f"(d[0]), "+f"(d[1]), "+f"(d[2]), "+f"(d[3]), "+f"(d[4]), "+f"(d[5]), "+f"(d[6]), "+f"(d[7]), "+f"(d[8]), "+f"(d[9]), "+f"(d[10]), "+f"(d[11]), "+f"(d[12]), "+f"(d[13]), "+f"(d[14]), "+f"(d[15]) : "r"(a0), "r"(a1), "r"(a2), "r"(a3), "l"(db), "r"(sd));
}
__device__ __forceinline__ void wgmma_rs_160_1(float* d, uint32_t a0, uint32_t a1, uint32_t a2, uint32_t a3, uint64_t db, int sd) {
  asm volatile("{ .reg .pred p; setp.ne.b32 p, %85, 0; wgmma.mma_async.sync.aligned.m64n160k16.f32.bf16.bf16 {%0,%1,%2,%3,%4,%5,%6,%7,%8,%9,%10,%11,%12,%13,%14,%15,%16,%17,%18,%19,%20,%21,%22,%23,%24,%25,%26,%27,%28,%29,%30,%31,%32,%33,%34,%35,%36,%37,%38,%39,%40,%41,%42,%43,%44,%45,%46,%47,%48,%49,%50,%51,%52,%53,%54,%55,%56,%57,%58,%59,%60,%61,%62,%63,%64,%65,%66,%67,%68,%69,%70,%71,%72,%73,%74,%75,%76,%77,%78,%79}, {%80,%81,%82,%83}, %84, p, 1, 1, 1; }"
   : "+f"(d[0]), "+f"(d[1]), "+f"(d[2]), "+f"(d[3]), "+f"(d[4]), "+f"(d[5]), "+f"(d[6]), "+f"(d[7]), "+f"(d[8]), "+f"(d[9]), "+f"(d[10]), "+f"(d[11]), "+f"(d[12]), "+f"(d[13]), "+f"(d[14]), "+f"(d[15]), "+f"(d[16]), "+f"(d[17]), "+f"(d[18]), "+f"(d[19]), "+f"(d[20]), "+f"(d[21]), "+f"(d[22]), "+f"(d[23]), "+f"(d[24]), "+f"(d[25]), "+f"(d[26]), "+f"(d[27]), "+f"(d[28]), "+f"(d[29]), "+f"(d[30]), "+f"(d[31]), "+f"(d[32]), "+f"(d[33]), "+f"(d[34]), "+f"(d[35]), "+f"(d[36]), "+f"(d[37]), "+f"(d[38]), "+f"(d[39]), "+f"(d[40]), "+f"(d[41]), "+f"(d[42]), "+f"(d[43]), "+f"(d[44]), "+f"(d[45]), "+f"(d[46]), "+f"(d[47]), "+f"(d[48]), "+f"(d[49]), "+f"(d[50]), "+f"(d[51]), "+f"(d[52]), "+f"(d[53]), "+f"(d[54]), "+f"(d[55]), "+f"(d[56]), "+f"(d[57]), "+f"(d[58]), "+f"(d[59]), "+f"(d[60]), "+f"(d[61]), "+f"(d[62]), "+f"(d[63]), "+f"(d[64]), "+f"(d[65]), "+f"(d[66]), "+f"(d[67]), "+f"(d[68]), "+f"(d[69]), "+f"(d[70]), "+f"(d[71]), "+f"(d[72]), "+f"(d[73]), "+f"(d[74]), "+f"(d[75]), "+f"(d[76]), "+f"(d[77]), "+f"(d[78]), "+f"(d[79]) : "r"(a0), "r"(a1), "r"(a2), "r"(a3), "l"(db), "r"(sd));
}
__device__ __forceinline__ void wgmma_rs_192_1(float* d, uint32_t a0, uint32_t a1, uint32_t a2, uint32_t a3, uint64_t db, int sd) {
  asm volatile("{ .reg .pred p; setp.ne.b32 p, %101, 0; wgmma.mma_async.sync.aligned.m64n192k16.f32.bf16.bf16 {%0,%1,%2,%3,%4,%5,%6,%7,%8,%9,%10,%11,%12,%13,%14,%15,%16,%17,%18,%19,%20,%21,%22,%23,%24,%25,%26,%27,%28,%29,%30,%31,%32,%33,%34,%35,%36,%37,%38,%39,%40,%41,%42,%43,%44,%45,%46,%47,%48,%49,%50,%51,%52,%53,%54,%55,%56,%57,%58,%59,%60,%61,%62,%63,%64,%65,%66,%67,%68,%69,%70,%71,%72,%73,%74,%75,%76,%77,%78,%79,%80,%81,%82,%83,%84,%85,%86,%87,%88,%89,%90,%91,%92,%93,%94,%95}, {%96,%97,%98,%99}, %100, p, 1, 1, 1; }"
   : "+f"(d[0]), "+f"(d[1]), "+f"(d[2]), "+f"(d[3]), "+f"(d[4]), "+f"(d[5]), "+f"(d[6]), "+f"(d[7]), "+f"(d[8]), "+f"(d[9]), "+f"(d[10]), "+f"(d[11]), "+f"(d[12]), "+f"(d[13]), "+f"(d[14]), "+f"(d[15]), "+f"(d[16]), "+f"(d[17]), "+f"(d[18]), "+f"(d[19]), "+f"(d[20]), "+f"(d[21]), "+f"(d[22]), "+f"(d[23]), "+f"(d[24]), "+f"(d[25]), "+f"(d[26]), "+f"(d[27]), "+f"(d[28]), "+f"(d[29]), "+f"(d[30]), "+f"(d[31]), "+f"(d[32]), "+f"(d[33]), "+f"(d[34]), "+f"(d[35]), "+f"(d[36]), "+f"(d[37]), "+f"(d[38]), "+f"(d[39]), "+f"(d[40]), "+f"(d[41]), "+f"(d[42]), "+f"(d[43]), "+f"(d[44]), "+f"(d[45]), "+f"(d[46]), "+f"(d[47]), "+f"(d[48]), "+f"(d[49]), "+f"(d[50]), "+f"(d[51]), "+f"(d[52]), "+f"(d[53]), "+f"(d[54]), "+f"(d[55]), "+f"(d[56]), "+f"(d[57]), "+f"(d[58]), "+f"(d[59]), "+f"(d[60]), "+f"(d[61]), "+f"(d[62]), "+f"(d[63]), "+f"(d[64]), "+f"(d[65]), "+f"(d[66]), "+f"(d[67]), "+f"(d[68]), "+f"(d[69]), "+f"(d[70]), "+f"(d[71]), "+f"(d[72]), "+f"(d[73]), "+f"(d[74]), "+f"(d[75]), "+f"(d[76]), "+f"(d[77]), "+f"(d[78]), "+f"(d[79]), "+f"(d[80]), "+f"(d[81]), "+f"(d[82]), "+f"(d[83]), "+f"(d[84]), "+f"(d[85]), "+f"(d[86]), "+f"(d[87]), "+f"(d[88]), "+f"(d[89]), "+f"(d[90]), "+f"(d[91]), "+f"(d[92]), "+f"(d[93]), "+f"(d[94]), "+f"(d[95]) : "r"(a0), "r"(a1), "r"(a2), "r"(a3), "l"(db), "r"(sd));
}
__device__ __forceinline__ void wgmma_ss_160_01(float* d, uint64_t da, uint64_t db, int sd) {
  asm volatile("{ .reg .pred p; setp.ne.b32 p, %82, 0; wgmma.mma_async.sync.aligned.m64n160k16.f32.bf16.bf16 {%0,%1,%2,%3,%4,%5,%6,%7,%8,%9,%10,%11,%12,%13,%14,%15,%16,%17,%18,%19,%20,%21,%22,%23,%24,%25,%26,%27,%28,%29,%30,%31,%32,%33,%34,%35,%36,%37,%38,%39,%40,%41,%42,%43,%44,%45,%46,%47,%48,%49,%50,%51,%52,%53,%54,%55,%56,%57,%58,%59,%60,%61,%62,%63,%64,%65,%66,%67,%68,%69,%70,%71,%72,%73,%74,%75,%76,%77,%78,%79}, %80, %81, p, 1, 1, 0, 1; }"
   : "+f"(d[0]), "+f"(d[1]), "+f"(d[2]), "+f"(d[3]), "+f"(d[4]), "+f"(d[5]), "+f"(d[6]), "+f"(d[7]), "+f"(d[8]), "+f"(d[9]), "+f"(d[10]), "+f"(d[11]), "+f"(d[12]), "+f"(d[13]), "+f"(d[14]), "+f"(d[15]), "+f"(d[16]), "+f"(d[17]), "+f"(d[18]), "+f"(d[19]), "+f"(d[20]), "+f"(d[21]), "+f"(d[22]), "+f"(d[23]), "+f"(d[24]), "+f"(d[25]), "+f"(d[26]), "+f"(d[27]), "+f"(d[28]), "+f"(d[29]), "+f"(d[30]), "+f"(d[31]), "+f"(d[32]), "+f"(d[33]), "+f"(d[34]), "+f"(d[35]), "+f"(d[36]), "+f"(d[37]), "+f"(d[38]), "+f"(d[39]), "+f"(d[40]), "+f"(d[41]), "+f"(d[42]), "+f"(d[43]), "+f"(d[44]), "+f"(d[45]), "+f"(d[46]), "+f"(d[47]), "+f"(d[48]), "+f"(d[49]), "+f"(d[50]), "+f"(d[51]), "+f"(d[52]), "+f"(d[53]), "+f"(d[54]), "+f"(d[55]), "+f"(d[56]), "+f"(d[57]), "+f"(d[58]), "+f"(d[59]), "+f"(d[60]), "+f"(d[61]), "+f"(d[62]), "+f"(d[63]), "+f"(d[64]), "+f"(d[65]), "+f"(d[66]), "+f"(d[67]), "+f"(d[68]), "+f"(d[69]), "+f"(d[70]), "+f"(d[71]), "+f"(d[72]), "+f"(d[73]), "+f"(d[74]), "+f"(d[75]), "+f"(d[76]), "+f"(d[77]), "+f"(d[78]), "+f"(d[79]) : "l"(da), "l"(db), "r"(sd));
}

__global__ void __cluster_dims__(2, 1, 1) __launch_bounds__(384, 1) fused_kernel(const __grid_constant__ Params p) {
  extern __shared__ __align__(1024) uint8_t smem_raw[];
  const uint32_t sb = smem_u32(smem_raw);
  const uint32_t bars = sb + O_BAR;
  const int tid = threadIdx.x, lane = tid & 31;
  const int warp = __shfl_sync(0xffffffffu, tid >> 5, 0);
  const int b = blockIdx.x;
  const int rb = b >> 3, cg = (b >> 1) & 3, kh = b & 1, fs = kh * 4 + cg;
  const int tb = b >> 2, cb = b & 3;
  auto BAR = [&](int i) { return bars + 8 * i; };

  uint32_t epoch = 0;
  if (warp >= 2) {
    const int run = lane & 7, ch = cb * 160 + (warp - 2) * 16 + (lane >> 3) * 4, t0 = tb * 64 + run * 8;
    uint2 kk[11], vv[8];
    const __nv_bfloat16* kp = p.k + (size_t)t0 * D_ + ch;
    const __nv_bfloat16* vp = p.v + (size_t)t0 * D_ + ch;
#pragma unroll
    for (int i = 0; i < 8; i++) asm volatile("ld.global.nc.L1::no_allocate.v2.u32 {%0,%1}, [%2];" : "=r"(kk[i + 3].x), "=r"(kk[i + 3].y) : "l"(kp + i * D_));
#pragma unroll
    for (int i = 0; i < 8; i++) asm volatile("ld.global.nc.L1::no_allocate.v2.u32 {%0,%1}, [%2];" : "=r"(vv[i].x), "=r"(vv[i].y) : "l"(vp + i * D_));
    const __nv_bfloat16* kh_ = t0 ? kp - 3 * D_ : kp;
#pragma unroll
    for (int i = 0; i < 3; i++) asm volatile("ld.global.nc.L1::no_allocate.v2.u32 {%0,%1}, [%2];" : "=r"(kk[i].x), "=r"(kk[i].y) : "l"(kh_ + i * D_));
    uint4 s0 = __ldg((const uint4*)(p.shift + ch * 4)), s1 = __ldg((const uint4*)(p.shift + ch * 4 + 8));
    if (warp < 4) asm volatile("ld.relaxed.gpu.global.u32 %0, [%1];" : "=r"(epoch) : "l"(g_sync) : "memory");
    __syncthreads();
    if (t0 == 0) { kk[0] = kk[1] = kk[2] = make_uint2(0, 0); }
    uint32_t wx[4], wy[4];
    wx[0] = prmt(s0.x, s0.z, 0x5410); wx[1] = prmt(s0.x, s0.z, 0x7632); wx[2] = prmt(s0.y, s0.w, 0x5410); wx[3] = prmt(s0.y, s0.w, 0x7632);
    wy[0] = prmt(s1.x, s1.z, 0x5410); wy[1] = prmt(s1.x, s1.z, 0x7632); wy[2] = prmt(s1.y, s1.w, 0x5410); wy[3] = prmt(s1.y, s1.w, 0x7632);
    uint32_t rx[8], ry[8];
#pragma unroll
    for (int i = 0; i < 8; i++) {
      uint32_t ax = hmul2(kk[i].x, wx[3]), ay = hmul2(kk[i].y, wy[3]);
      ax = hfma2(kk[i + 1].x, wx[2], ax); ay = hfma2(kk[i + 1].y, wy[2], ay);
      ax = hfma2(kk[i + 2].x, wx[1], ax); ay = hfma2(kk[i + 2].y, wy[1], ay);
      ax = hfma2(kk[i + 3].x, wx[0], ax); ay = hfma2(kk[i + 3].y, wy[0], ay);
      rx[i] = hmul2(ax, vv[i].x); ry[i] = hmul2(ay, vv[i].y);
    }
    __nv_bfloat16* op = g_kvT + (size_t)ch * S_ + t0;
    *(uint4*)(op) = make_uint4(prmt(rx[0], rx[1], 0x5410), prmt(rx[2], rx[3], 0x5410), prmt(rx[4], rx[5], 0x5410), prmt(rx[6], rx[7], 0x5410));
    *(uint4*)(op + S_) = make_uint4(prmt(rx[0], rx[1], 0x7632), prmt(rx[2], rx[3], 0x7632), prmt(rx[4], rx[5], 0x7632), prmt(rx[6], rx[7], 0x7632));
    *(uint4*)(op + 2 * S_) = make_uint4(prmt(ry[0], ry[1], 0x5410), prmt(ry[2], ry[3], 0x5410), prmt(ry[4], ry[5], 0x5410), prmt(ry[6], ry[7], 0x5410));
    *(uint4*)(op + 3 * S_) = make_uint4(prmt(ry[0], ry[1], 0x7632), prmt(ry[2], ry[3], 0x7632), prmt(ry[4], ry[5], 0x7632), prmt(ry[6], ry[7], 0x7632));
    bar_sync(1, 320);
    if (tid == 256) { TSTAMP(0); signal_add(g_sync + (1 + cb) * 32); TSTAMP(1); }
  } else {
    asm volatile("ld.relaxed.gpu.global.u32 %0, [%1];" : "=r"(epoch) : "l"(g_sync) : "memory");
    if (warp == 0) {
      for (int i = lane; i < B_NUM; i += 32) {
        uint32_t cnt = 1;
        if ((i >= B_EMPTY && i < B_EMPTY + 6) || (i >= B_W2E && i < B_W2E + 6) || i == B_P2DONE) cnt = 2;
        if ((i >= B_Y && i < B_Y + 5) || i == B_STAGED || i == B_STAGED + 1) cnt = 4;
        mbar_init(BAR(i), cnt);
      }
      __syncwarp();
      if (lane == 0) mbar_expect(BAR(B_RED), 40960);
      asm volatile("fence.mbarrier_init.release.cluster;" ::: "memory");
    } else {
#pragma unroll
      for (int i = 0; i < 10; i++) {
        uint32_t cv = __ldg((const uint32_t*)p.c + lane + 32 * i);
        float a = blo(cv), c2 = bhi(cv);
        sts32(sb + O_SILU + (lane + 32 * i) * 4, pack2(a / (1.f + __expf(-a)), c2 / (1.f + __expf(-c2))));
      }
      if (lane < 20) sts32(sb + O_SSM + (lane >> 2) * SEQ + (lane & 3) * 4, 0);
      if (lane < 17) {
#pragma unroll
        for (int j = 0; j < 5; j++) asm volatile("st.shared.v4.u32 [%0], {%1,%1,%1,%1};" ::"r"(sb + O_KV + j * KSEQ + lane * 16), "r"(0) : "memory");
      }
      fence_async_smem();
    }
    __syncthreads();
  }
  asm volatile("barrier.cluster.arrive.relaxed.aligned;" ::: "memory");
  const uint32_t e1 = epoch + 1, tag = e1 & 0xffff;

  if (warp < 4) {
    asm volatile("setmaxnreg.dec.sync.aligned.u32 40;");
    if (warp == 0) {
      if (lane == 0) {
#pragma unroll 1
        for (int j = 0; j < 5; j++) { mbar_expect(BAR(B_SSM + j), 4096); bulk_ld(sb + O_SSM + j * SEQ + 16, p.ssm + (size_t)(j * 128 + b) * S_, 4096, BAR(B_SSM + j)); }
        mbar_expect(BAR(B_QIN), 40960);
#pragma unroll 1
        for (int i = 0; i < 5; i++) tma2d(sb + O_QIN + i * 4096, &p.m_q, cb * 160 + i * 32, tb * 64, BAR(B_QIN));
#pragma unroll 1
        for (int i = 0; i < 16; i++) bulk_ld(sb + O_QROW + i * 1296, p.q + (size_t)(b * 16 + i) * D_, 1280, BAR(B_QIN));
        if (b < 120) {
#pragma unroll 1
          for (int h = 0; h < 2; h++) {
            mbar_expect(BAR(B_WM + h), 20480);
#pragma unroll 1
            for (int i = 0; i < 4; i++) tma2d(sb + O_WMOD + h * 20480 + i * 5120, &p.m_wm, h * 1920 + b * 16, i * 160, BAR(B_WM + h));
          }
        }
        auto loadW = [&](int s) {
          const uint32_t dst = sb + (s % 6) * SLOT, bar = BAR(B_FULL + s % 6);
          mbar_expect(bar, SLOT);
#pragma unroll
          for (int i = 0; i < 3; i++) { tma2d(dst + i * 4096, &p.m_wg, fs * 192 + i * 64, s * 32, bar); tma2d(dst + 12288 + i * 4096, &p.m_wu, fs * 192 + i * 64, s * 32, bar); }
        };
        auto loadA = [&](int s) {
          const uint32_t dst = sb + (s % 6) * SLOT + 24576, bar = BAR(B_FULL + s % 6);
          tma2d(dst, &p.m_x1T, rb * 128, s * 32, bar);
          tma2d(dst + 4096, &p.m_x1T, rb * 128 + 64, s * 32, bar);
        };
        loadW(0); loadW(1);
#pragma unroll 1
        for (int j = 0; j < 5; j++) {
          const int d = j * 128 + b;
          poll_ge(g_sync + (1 + d / 160) * 32, e1 * 32);
          if (j == 0) TSTAMP(2);
          mbar_expect(BAR(B_KV + j), 4096);
          bulk_ld(sb + O_KV + j * KSEQ + KPAD, g_kvT + (size_t)d * S_, 4096, BAR(B_KV + j));
        }
        poll_ge(g_sync + 5 * 32, e1 * 128);
        TSTAMP(3);
        mbar_expect(BAR(B_QF), 20480 + 16384);
#pragma unroll 1
        for (int j = 0; j < 5; j++) bulk_ld(sb + O_QIN + j * 4096, g_qT + (size_t)(j * 128 + b) * S_, 4096, BAR(B_QF));
        bulk_ld(sb + O_QROW, g_st1, 16384, BAR(B_QF));
        mbar_wait(BAR(B_MODDONE), 0);
        loadW(2); loadW(3);
        poll_ge(g_sync + 6 * 32, e1 * 128);
        TSTAMP(4);
#pragma unroll 1
        for (int s = 0; s < 4; s++) loadA(s);
        mbar_wait(BAR(B_P2DONE), 0);
#pragma unroll 1
        for (int s = 4; s < 20; s++) {
          if (s >= 6) mbar_wait(BAR(B_EMPTY + s % 6), (s / 6 - 1) & 1);
          loadW(s);
          if ((s & 3) == 0) poll_ge(g_sync + (6 + (s >> 2)) * 32, e1 * 128);
          loadA(s);
        }
        if (b == 0) asm volatile("st.relaxed.gpu.global.u32 [%0], %1;" ::"l"(g_sync), "r"(e1) : "memory");
#pragma unroll 1
        for (int s = 0; s < 12; s++) {
          if (s == 0) { mbar_wait(BAR(B_EMPTY + 2), 0); }
          else if (s == 1) { mbar_wait(BAR(B_EMPTY + 3), 0); }
          else if (s == 3) { mbar_wait(BAR(B_EMPTY + 0), 1); }
          else if (s == 4) { mbar_wait(BAR(B_EMPTY + 1), 1); }
          else if (s >= 6) { mbar_wait(BAR(B_W2E + s - 6), 0); }
          const int e = s % 6;
          const int k0 = kh * 768 + ((cg + s / 3) & 3) * 192 + (s % 3) * 64;
          mbar_expect(BAR(B_W2F + e), 20480);
#pragma unroll
          for (int i = 0; i < 5; i++) tma2d(sb + w2entry(e) + i * 4096, &p.m_w2, cg * 160 + i * 32, k0, BAR(B_W2F + e));
        }
        mbar_wait(BAR(B_W2E + 0), 1);
        mbar_wait(BAR(B_W2E + 1), 1);
      }
      __syncwarp();
      asm volatile("barrier.cluster.wait.aligned;" ::: "memory");
      if (lane == 0)
        asm volatile("{ .reg .b32 r; mapa.shared::cluster.u32 r, %0, %1; mbarrier.arrive.release.cluster.shared::cluster.b64 _, [r]; }" ::"r"(BAR(B_RDY)), "r"(kh ^ 1) : "memory");
    } else if (warp == 1) {
      const int r = lane >> 2, c = lane & 3;
      {
        mbar_wait(BAR(B_QIN), 0);
        float g0[4] = {0, 0, 0, 0}, g1[4] = {0, 0, 0, 0}, sm[4] = {0, 0, 0, 0};
        const uint32_t a = sb + O_QROW + (lane & 15) * 1296 + (lane >> 4) * 16;
#pragma unroll 4
        for (int i = 0; i < 40; i++) {
          uint32_t a0, a1, a2, a3;
          ldsm4(a + i * 32, a0, a1, a2, a3);
          mma16816(g0, a0, a1, a2, a3, a0, a2);
          mma16816(g1, a0, a1, a2, a3, a1, a3);
          mma16816(sm, a0, a1, a2, a3, 0x3f803f80u, 0x3f803f80u);
        }
        if (c == (r >> 1)) {
          float m0 = sm[0] * (1.f / D_), m1 = sm[2] * (1.f / D_);
          float v0 = ((r & 1) ? g0[1] : g0[0]) * (1.f / D_) - m0 * m0, v1 = ((r & 1) ? g1[3] : g1[2]) * (1.f / D_) - m1 * m1;
          float r0 = rsqrtf(fmaxf(v0, 0.f) + 1e-5f), r1 = rsqrtf(fmaxf(v1, 0.f) + 1e-5f);
          const int idx = (r >> 1) * 512 + b * 4 + (r & 1);
          g_st1[idx] = make_float2(r0, -m0 * r0);
          g_st1[idx + 2] = make_float2(r1, -m1 * r1);
        }
        bar_arrive(4, 96);
      }
      if (b < 120) {
#pragma unroll 1
        for (int h = 0; h < 2; h++) {
          mbar_wait(BAR(B_WM + h), 0);
          float d0[4] = {0, 0, 0, 0}, d1[4] = {0, 0, 0, 0}, d2[4] = {0, 0, 0, 0}, d3[4] = {0, 0, 0, 0};
          const uint32_t a = sb + O_WMOD + h * 20480 + (lane & 15) * 32 + (((lane >> 4) ^ ((lane >> 2) & 1)) * 16);
          const uint32_t sa = sb + O_SILU + c * 4;
#pragma unroll 2
          for (int i = 0; i < 20; i++) {
            uint32_t b0, b1, b2, b3, a0, a2;
            ldsm4t(a + i * 1024, b0, b1, b2, b3);
            a0 = lds32(sa + i * 64); a2 = lds32(sa + i * 64 + 16);
            mma16816(d0, a0, 0, a2, 0, b0, b1);
            mma16816(d1, a0, 0, a2, 0, b2, b3);
            ldsm4t(a + i * 1024 + 512, b0, b1, b2, b3);
            a0 = lds32(sa + i * 64 + 32); a2 = lds32(sa + i * 64 + 48);
            mma16816(d2, a0, 0, a2, 0, b0, b1);
            mma16816(d3, a0, 0, a2, 0, b2, b3);
          }
          if (r < 2) {
            uint32_t w = r ? pack2(d1[0] + d3[0], d1[1] + d3[1]) : pack2(d0[0] + d2[0], d0[1] + d2[1]);
            asm volatile("st.relaxed.gpu.global.v2.u32 [%0], {%1,%2};" ::"l"(g_mod + h * 1920 + b * 16 + lane * 2), "r"((w & 0xffff) | (tag << 16)), "r"((w >> 16) | (tag << 16)) : "memory");
          }
          if (lane == 0) TSTAMP(5 + h);
        }
      }
      __syncwarp();
      if (lane == 0) mbar_arrive(BAR(B_MODDONE));
#pragma unroll 1
      for (int i = 0; i < 10; i++) {
        uint2 w = poll_tag2(g_mod + 4 * D_ + (lane + 32 * i) * 2, tag);
        sts32(sb + O_CB + (lane + 32 * i) * 4, pack2(1.f + blo(w.x), 1.f + blo(w.y)));
      }
      __syncwarp();
      if (lane == 0) { mbar_arrive(BAR(B_CB)); TSTAMP(7); }
#pragma unroll 1
      for (int i = 0; i < 10; i++) {
        uint2 w = poll_tag2(g_mod + 3 * D_ + (lane + 32 * i) * 2, tag);
        sts32(sb + O_SB + (lane + 32 * i) * 4, prmt(w.x, w.y, 0x5410));
      }
#pragma unroll 1
      for (int i = 0; i < 5; i++) {
        uint32_t w = poll_tag(g_mod + 5 * D_ + cg * 160 + lane + 32 * i, tag);
        sts32(sb + O_GB + (lane + 32 * i) * 4, w << 16);
      }
      mbar_wait(BAR(B_P2DONE), 0);
      {
        float d0[4] = {0, 0, 0, 0}, d1[4] = {0, 0, 0, 0}, d2[4] = {0, 0, 0, 0};
        const CUtensorMap* m = (b & 64) ? &p.m_wus : &p.m_wgs;
        const int col0 = (b & 63) * 24;
#pragma unroll 1
        for (int h = 0; h < 2; h++) {
          __syncwarp();
          if (lane == 0) {
            fence_async_smem();
            mbar_expect(BAR(B_STRIP), 15360);
            tma2d(sb + O_SSM, m, col0, h * 320, BAR(B_STRIP));
            tma2d(sb + O_SSM + 7680, m, col0, h * 320 + 160, BAR(B_STRIP));
          }
          mbar_wait(BAR(B_STRIP), h);
          const uint32_t a = sb + O_SSM + (lane & 15) * 48 + (lane >> 4) * 16;
          const uint32_t sa = sb + ((r & 1) ? O_SB : O_CB) + h * 640 + c * 4;
#pragma unroll 2
          for (int i = 0; i < 20; i++) {
            uint32_t b0, b1, b2, b3, b4, b5, a0, a2;
            ldsm4t(a + i * 768, b0, b1, b2, b3);
            ldsm2t(sb + O_SSM + (lane & 15) * 48 + 32 + i * 768, b4, b5);
            a0 = lds32(sa + i * 32); a2 = lds32(sa + i * 32 + 16);
            mma16816(d0, a0, 0, a2, 0, b0, b1);
            mma16816(d1, a0, 0, a2, 0, b2, b3);
            mma16816(d2, a0, 0, a2, 0, b4, b5);
          }
        }
        if (r < 2) {
          float* o = (float*)g_vv + (col0 + 2 * c) * 4 + (b >> 6) * 2 + r;
          o[0] = d0[0]; o[4] = d0[1]; o[32] = d1[0]; o[36] = d1[1]; o[64] = d2[0]; o[68] = d2[1];
        }
        __syncwarp();
        if (lane == 0) {
          signal_add(g_sync + (11 + ((b & 63) >> 3)) * 32);
          fence_async_smem();
          poll_ge(g_sync + 10 * 32, e1 * 128);
          mbar_expect(BAR(B_X1), 20480);
#pragma unroll 1
          for (int i = 0; i < 5; i++) tma2d(sb + O_SSM + i * 4096, &p.m_x1T, rb * 128 + (kh ^ 1) * 64, cg * 160 + i * 32, BAR(B_X1));
          poll_ge(g_sync + (11 + fs) * 32, e1 * 16);
          mbar_expect(BAR(B_VV), 3072);
          bulk_ld(sb + O_VV, g_vv + fs * 192, 3072, BAR(B_VV));
          TSTAMP(8);
        }
      }
      __syncwarp();
      asm volatile("barrier.cluster.wait.aligned;" ::: "memory");
    } else {
      const int hw = warp - 2;
      mbar_wait(BAR(B_QIN), 0);
      if (tid == 64) TSTAMP(9);
      {
        const int t = hw * 32 + lane;
        const uint32_t src = sb + O_QIN + t * 64;
        const uint32_t dst = sb + O_QSTG + (lane & 7) * 128 + (((hw * 4 + (lane >> 3)) ^ (lane & 7)) * 16);
#pragma unroll 4
        for (int i = 0; i < 20; i++) {
          uint32_t r0, r1, r2, r3;
          ldsm4t(src + (i >> 2) * 4096 + (((i & 3) ^ ((t >> 1) & 3)) * 16), r0, r1, r2, r3);
          stsm4(dst + i * 1024, r0, r1, r2, r3);
        }
        fence_async_smem();
        bar_sync(4, 96);
        if (tid == 64) {
#pragma unroll 1
          for (int i = 0; i < 5; i++) tma2d_store(&p.m_qT, sb + O_QSTG + i * 4096, tb * 64, cb * 160 + i * 32);
          bulk_commit(); bulk_wait0();
          signal_add(g_sync + 5 * 32);
          TSTAMP(10);
        }
        __syncwarp();
      }
      float mv = 0.f;
      if (lane < 15) mv = blo(poll_tag(g_mod + (lane / 5) * D_ + (lane % 5) * 128 + b, tag));
      else if (lane < 20) mv = __bfloat162float(p.ssmD[(lane - 15) * 128 + b]);
      __syncwarp();
      if (tid == 64) TSTAMP(11);
      mbar_wait(BAR(B_QF), 0);
#pragma unroll 1
      for (int j = 0; j < 5; j++) {
        const float ga = __shfl_sync(0xffffffffu, mv, 10 + j);
        const float c1 = rbf(1.f + __shfl_sync(0xffffffffu, mv, 5 + j)) * ga, c0 = __shfl_sync(0xffffffffu, mv, j) * ga;
        const float dv = __shfl_sync(0xffffffffu, mv, 15 + j);
        mbar_wait(BAR(B_Y + j), 0);
#pragma unroll 1
        for (int i = 0; i < 4; i++) {
          const int ck = i * 64 + hw * 32 + lane;
          uint4 y = lds128(sb + O_SSM + j * SEQ + 16 + ck * 16), kv = lds128(sb + O_KV + j * KSEQ + KPAD + ck * 16), q = lds128(sb + O_QIN + j * 4096 + ck * 16);
          uint4 o;
          auto f = [&](uint32_t yy, uint32_t kk, uint32_t qq, int pi) {
            float4 st = lds128f(sb + O_QROW + pi * 4096 + ck * 16);
            float q0 = blo(qq), q1 = bhi(qq);
            float x0 = fmaf(fmaf(fmaf(q0, st.x, st.y), c1, c0), fmaf(blo(kk), dv, blo(yy)), q0);
            float x1 = fmaf(fmaf(fmaf(q1, st.z, st.w), c1, c0), fmaf(bhi(kk), dv, bhi(yy)), q1);
            return pack2(x0, x1);
          };
          o.x = f(y.x, kv.x, q.x, 0); o.y = f(y.y, kv.y, q.y, 1); o.z = f(y.z, kv.z, q.z, 2); o.w = f(y.w, kv.w, q.w, 3);
          *(uint4*)(g_x1T + (size_t)(j * 128 + b) * S_ + ck * 8) = o;
        }
        if (j == 4) { fence_async_smem(); __syncwarp(); if (lane == 0) mbar_arrive(BAR(B_P2DONE)); }
        bar_sync(4, 64);
        if (lane == 0 && hw == (j & 1)) { signal_add(g_sync + (6 + j) * 32); TSTAMP(12 + j); }
        __syncwarp();
      }
      if (lane == 0) {
        const uint32_t reg = sb + (5 - hw) * SLOT;
        const int row0 = rb * 128 + (hw ^ kh) * 64;
        uint32_t* flags = g_sync + 32 * 32 + (rb * 16 + kh * 8 + hw * 4) * 8;
        mbar_wait(BAR(B_STAGED + hw), 0);
#pragma unroll 1
        for (int i = 0; i < 3; i++) tma2d_store(&p.m_h, reg + i * 8192, fs * 192 + i * 64, row0);
        bulk_commit(); bulk_wait0();
        asm volatile("fence.acq_rel.gpu;\n st.relaxed.gpu.global.u32 [%0], %1;" ::"l"(flags + cg * 8), "r"(e1) : "memory");
        TSTAMP(17 + hw);
#pragma unroll 1
        for (int i = 0; i < 9; i++) {
          const int oc = (cg + 1 + i / 3) & 3;
          if (i % 3 == 0) poll_ge(flags + oc * 8, e1);
          if (i >= 4) mbar_wait(BAR(B_HE + hw * 4 + (i & 3)), ((i >> 2) - 1) & 1);
          mbar_expect(BAR(B_HF + hw * 4 + (i & 3)), 8192);
          tma2d(reg + (i & 3) * 8192, &p.m_h, kh * 768 + oc * 192 + (i % 3) * 64, row0, BAR(B_HF + hw * 4 + (i & 3)));
        }
      }
      __syncwarp();
      asm volatile("barrier.cluster.wait.aligned;" ::: "memory");
    }
  } else {
    asm volatile("setmaxnreg.inc.sync.aligned.u32 232;");
    const int isE = warp >= 8 ? 1 : 0;
    const int w = warp & 3, r = lane >> 2, c = lane & 3;
    if (isE) bar_arrive(2, 256);
    {
      const int nr = r & 3, low3 = w + 4 * (r >> 2);
      const int x0 = 16 * nr + low3 + 8 - 2 * c;
      const uint32_t offa = 16 + 4 * (x0 >> 1), offb = 16 + 4 * ((x0 - 1) >> 1);
      const uint32_t sel = (w & 1) ? 0x5432u : 0x7610u;
      const int cp = (c + nr) & 3;
      const bool carry = (c + nr) >= 4, b0 = nr & 1, b1 = nr & 2;
      const int ln1 = (lane & 16) | ((nr ^ 1) << 2) | ((cp - (nr ^ 1)) & 3);
      const int ln2 = (lane & 16) | ((nr ^ 2) << 2) | ((cp - (nr ^ 2)) & 3);
#pragma unroll 1
      for (int j = isE; j < 5; j += 2) {
        const uint32_t sa = sb + O_SSM + j * SEQ;
        uint32_t A[64];
        mbar_wait(BAR(B_SSM + j), 0);
        if (w & 1) {
#pragma unroll
          for (int g = 0; g < 16; g++) {
            uint32_t u0 = lds32(sa + offa + g * 256), u1 = lds32(sa + offa + g * 256 + 128), u2 = lds32(sa + offa + g * 256 - 16), u3 = lds32(sa + offa + g * 256 + 112);
            A[4 * g] = prmt(u0, u0, sel); A[4 * g + 1] = prmt(u1, u1, sel); A[4 * g + 2] = prmt(u2, u2, sel); A[4 * g + 3] = prmt(u3, u3, sel);
          }
        } else {
#pragma unroll
          for (int g = 0; g < 16; g++) {
            A[4 * g] = prmt(lds32(sa + offa + g * 256), lds32(sa + offb + g * 256), sel);
            A[4 * g + 1] = prmt(lds32(sa + offa + g * 256 + 128), lds32(sa + offb + g * 256 + 128), sel);
            A[4 * g + 2] = prmt(lds32(sa + offa + g * 256 - 16), lds32(sa + offb + g * 256 - 16), sel);
            A[4 * g + 3] = prmt(lds32(sa + offa + g * 256 + 112), lds32(sa + offb + g * 256 + 112), sel);
          }
        }
        float d[128];
        mbar_wait(BAR(B_KV + j), 0);
        bar_sync(2 + isE, 256);
        if (j == 0 && tid == 128) TSTAMP(19);
        const uint64_t db = mkdesc(sb + O_KV + j * KSEQ, 16, 128, 0);
        wg_fence();
        wgmma_rs_32_0(d + 112, A[0], A[1], A[2], A[3], db + 240, 0);
        wgmma_rs_32_0(d + 96, A[0], A[1], A[2], A[3], db + 208, 0);
        wgmma_rs_32_0(d + 80, A[0], A[1], A[2], A[3], db + 176, 0);
        wgmma_rs_32_0(d + 64, A[0], A[1], A[2], A[3], db + 144, 0);
        wgmma_rs_32_0(d + 112, A[4], A[5], A[6], A[7], db + 224, 1);
        wgmma_rs_32_0(d + 96, A[4], A[5], A[6], A[7], db + 192, 1);
        wgmma_rs_32_0(d + 80, A[4], A[5], A[6], A[7], db + 160, 1);
        wgmma_rs_32_0(d + 64, A[4], A[5], A[6], A[7], db + 128, 1);
        wgmma_rs_32_0(d + 112, A[8], A[9], A[10], A[11], db + 208, 1);
        wgmma_rs_32_0(d + 96, A[8], A[9], A[10], A[11], db + 176, 1);
        wgmma_rs_32_0(d + 80, A[8], A[9], A[10], A[11], db + 144, 1);
        wgmma_rs_32_0(d + 64, A[8], A[9], A[10], A[11], db + 112, 1);
        wgmma_rs_32_0(d + 112, A[12], A[13], A[14], A[15], db + 192, 1);
        wgmma_rs_32_0(d + 96, A[12], A[13], A[14], A[15], db + 160, 1);
        wgmma_rs_32_0(d + 80, A[12], A[13], A[14], A[15], db + 128, 1);
        wgmma_rs_32_0(d + 48, A[0], A[1], A[2], A[3], db + 112, 0);
        wgmma_rs_32_0(d + 112, A[16], A[17], A[18], A[19], db + 176, 1);
        wgmma_rs_32_0(d + 96, A[16], A[17], A[18], A[19], db + 144, 1);
        wgmma_rs_32_0(d + 80, A[16], A[17], A[18], A[19], db + 112, 1);
        wgmma_rs_32_0(d + 64, A[12], A[13], A[14], A[15], db + 96, 1);
        wgmma_rs_32_0(d + 112, A[20], A[21], A[22], A[23], db + 160, 1);
        wgmma_rs_32_0(d + 96, A[20], A[21], A[22], A[23], db + 128, 1);
        wgmma_rs_32_0(d + 80, A[20], A[21], A[22], A[23], db + 96, 1);
        wgmma_rs_32_0(d + 48, A[4], A[5], A[6], A[7], db + 96, 1);
        wgmma_rs_32_0(d + 112, A[24], A[25], A[26], A[27], db + 144, 1);
        wgmma_rs_32_0(d + 96, A[24], A[25], A[26], A[27], db + 112, 1);
        wgmma_rs_32_0(d + 80, A[24], A[25], A[26], A[27], db + 80, 1);
        wgmma_rs_32_0(d + 64, A[16], A[17], A[18], A[19], db + 80, 1);
        wgmma_rs_32_0(d + 112, A[28], A[29], A[30], A[31], db + 128, 1);
        wgmma_rs_32_0(d + 96, A[28], A[29], A[30], A[31], db + 96, 1);
        wgmma_rs_32_0(d + 48, A[8], A[9], A[10], A[11], db + 80, 1);
        wgmma_rs_32_0(d + 32, A[0], A[1], A[2], A[3], db + 80, 0);
        wgmma_rs_32_0(d + 112, A[32], A[33], A[34], A[35], db + 112, 1);
        wgmma_rs_32_0(d + 96, A[32], A[33], A[34], A[35], db + 80, 1);
        wgmma_rs_32_0(d + 80, A[28], A[29], A[30], A[31], db + 64, 1);
        wgmma_rs_32_0(d + 64, A[20], A[21], A[22], A[23], db + 64, 1);
        wgmma_rs_32_0(d + 112, A[36], A[37], A[38], A[39], db + 96, 1);
        wgmma_rs_32_0(d + 96, A[36], A[37], A[38], A[39], db + 64, 1);
        wgmma_rs_32_0(d + 48, A[12], A[13], A[14], A[15], db + 64, 1);
        wgmma_rs_32_0(d + 32, A[4], A[5], A[6], A[7], db + 64, 1);
        wgmma_rs_32_0(d + 112, A[40], A[41], A[42], A[43], db + 80, 1);
        wgmma_rs_32_0(d + 96, A[40], A[41], A[42], A[43], db + 48, 1);
        wgmma_rs_32_0(d + 80, A[32], A[33], A[34], A[35], db + 48, 1);
        wgmma_rs_32_0(d + 64, A[24], A[25], A[26], A[27], db + 48, 1);
        wgmma_rs_32_0(d + 112, A[44], A[45], A[46], A[47], db + 64, 1);
        wgmma_rs_32_0(d + 48, A[16], A[17], A[18], A[19], db + 48, 1);
        wgmma_rs_32_0(d + 32, A[8], A[9], A[10], A[11], db + 48, 1);
        wgmma_rs_32_0(d + 16, A[0], A[1], A[2], A[3], db + 48, 0);
        wgmma_rs_32_0(d + 112, A[48], A[49], A[50], A[51], db + 48, 1);
        wgmma_rs_32_0(d + 96, A[44], A[45], A[46], A[47], db + 32, 1);
        wgmma_rs_32_0(d + 80, A[36], A[37], A[38], A[39], db + 32, 1);
        wgmma_rs_32_0(d + 64, A[28], A[29], A[30], A[31], db + 32, 1);
        wgmma_rs_32_0(d + 112, A[52], A[53], A[54], A[55], db + 32, 1);
        wgmma_rs_32_0(d + 48, A[20], A[21], A[22], A[23], db + 32, 1);
        wgmma_rs_32_0(d + 32, A[12], A[13], A[14], A[15], db + 32, 1);
        wgmma_rs_32_0(d + 16, A[4], A[5], A[6], A[7], db + 32, 1);
        wgmma_rs_32_0(d + 112, A[56], A[57], A[58], A[59], db + 16, 1);
        wgmma_rs_32_0(d + 96, A[48], A[49], A[50], A[51], db + 16, 1);
        wgmma_rs_32_0(d + 80, A[40], A[41], A[42], A[43], db + 16, 1);
        wgmma_rs_32_0(d + 64, A[32], A[33], A[34], A[35], db + 16, 1);
        wgmma_rs_32_0(d + 48, A[24], A[25], A[26], A[27], db + 16, 1);
        wgmma_rs_32_0(d + 32, A[16], A[17], A[18], A[19], db + 16, 1);
        wgmma_rs_32_0(d + 16, A[8], A[9], A[10], A[11], db + 16, 1);
        wgmma_rs_32_0(d + 0, A[0], A[1], A[2], A[3], db + 16, 0);
        wgmma_rs_32_0(d + 112, A[60], A[61], A[62], A[63], db + 0, 1);
        wgmma_rs_32_0(d + 96, A[52], A[53], A[54], A[55], db + 0, 1);
        wgmma_rs_32_0(d + 80, A[44], A[45], A[46], A[47], db + 0, 1);
        wgmma_rs_32_0(d + 64, A[36], A[37], A[38], A[39], db + 0, 1);
        wgmma_rs_32_0(d + 48, A[28], A[29], A[30], A[31], db + 0, 1);
        wgmma_rs_32_0(d + 32, A[20], A[21], A[22], A[23], db + 0, 1);
        wgmma_rs_32_0(d + 16, A[12], A[13], A[14], A[15], db + 0, 1);
        wgmma_rs_32_0(d + 0, A[4], A[5], A[6], A[7], db + 0, 1);
        wg_commit();
        if (j < 4) bar_arrive(3 - isE, 256);
        wg_wait<0>();
        regfence<128>(d);
        float K[32];
        float pk = 0.f, ps = 0.f;
#pragma unroll
        for (int u = 0; u < 32; u++) {
          float e0 = d[4 * u], e1_ = d[4 * u + 1];
          if (u > 0) { e0 += d[4 * u - 2]; e1_ += d[4 * u - 1]; }
          float kx = b0 ? e1_ : e0, sx = b0 ? e0 : e1_;
          float kk = carry ? pk : kx, ss = carry ? ps : sx;
          pk = kx; ps = sx;
          K[u] = kk + __shfl_sync(0xffffffffu, ss, ln1);
        }
        const uint32_t ya = sa + 16 + 2 * (low3 + 16 * cp + 8 * (nr & 1) + 64 * (nr >> 1));
#pragma unroll
        for (int z = 0; z < 16; z++) {
          float kx = b1 ? K[2 * z + 1] : K[2 * z], sx = b1 ? K[2 * z] : K[2 * z + 1];
          float y = kx + __shfl_sync(0xffffffffu, sx, ln2);
          sts16(ya + z * 256, (uint16_t)pack2(y, 0.f));
        }
        __syncwarp();
        if (lane == 0) mbar_arrive(BAR(B_Y + j));
        if (lane == 0 && w == 0 && j >= 3) TSTAMP(17 + j);
      }
    }
    const int rh = isE ^ kh;
    uint32_t hA[48];
    {
      float ag[96], au[96];
      float s1a = 0.f, s2a = 0.f, s1b = 0.f, s2b = 0.f;
      const int kl = (lane & 7) + 8 * (lane >> 4);
      const uint32_t aoff = 24576 + rh * 4096 + kl * 128 + (((2 * w + ((lane >> 3) & 1)) ^ (lane & 7)) * 16);
      mbar_wait(BAR(B_CB), 0);
      int slot = 0, ph = 0;
#pragma unroll 1
      for (int s = 0; s < 20; s++) {
        const uint32_t st = sb + slot * SLOT;
        mbar_wait(BAR(B_FULL + slot), ph);
        if (s == 0 && lane == 0 && w == 0) TSTAMP(22 + isE);
#pragma unroll
        for (int kk = 0; kk < 2; kk++) {
          uint32_t a0, a1, a2, a3;
          ldsm4t(st + aoff + kk * 2048, a0, a1, a2, a3);
          const uint32_t c0 = lds32(sb + O_CB + s * 64 + kk * 32 + c * 4), c1 = lds32(sb + O_CB + s * 64 + kk * 32 + c * 4 + 16);
          float x;
          x = blo(a0); s1a += x; s2a = fmaf(x, x, s2a); x = bhi(a0); s1a += x; s2a = fmaf(x, x, s2a);
          x = blo(a1); s1b += x; s2b = fmaf(x, x, s2b); x = bhi(a1); s1b += x; s2b = fmaf(x, x, s2b);
          x = blo(a2); s1a += x; s2a = fmaf(x, x, s2a); x = bhi(a2); s1a += x; s2a = fmaf(x, x, s2a);
          x = blo(a3); s1b += x; s2b = fmaf(x, x, s2b); x = bhi(a3); s1b += x; s2b = fmaf(x, x, s2b);
          a0 = hmul2(a0, c0); a1 = hmul2(a1, c0); a2 = hmul2(a2, c1); a3 = hmul2(a3, c1);
          const uint64_t dg = mkdesc(st + kk * 2048, 4096, 1024, 1);
          wg_fence();
          wgmma_rs_192_1(ag, a0, a1, a2, a3, dg, (s | kk) ? 1 : 0);
          wgmma_rs_192_1(au, a0, a1, a2, a3, dg + (12288 >> 4), (s | kk) ? 1 : 0);
          wg_commit();
          wg_wait<1>();
          if (kk == 0 && s > 0 && lane == 0 && w == 0) mbar_arrive(BAR(B_EMPTY + (slot == 0 ? 5 : slot - 1)));
        }
        if (++slot == 6) { slot = 0; ph ^= 1; }
      }
      wg_wait<0>();
      regfence<96>(ag); regfence<96>(au);
      if (lane == 0 && w == 0) { mbar_arrive(BAR(B_EMPTY + 1)); TSTAMP(24 + isE); }
      s1a += __shfl_xor_sync(0xffffffffu, s1a, 1); s2a += __shfl_xor_sync(0xffffffffu, s2a, 1);
      s1b += __shfl_xor_sync(0xffffffffu, s1b, 1); s2b += __shfl_xor_sync(0xffffffffu, s2b, 1);
      s1a += __shfl_xor_sync(0xffffffffu, s1a, 2); s2a += __shfl_xor_sync(0xffffffffu, s2a, 2);
      s1b += __shfl_xor_sync(0xffffffffu, s1b, 2); s2b += __shfl_xor_sync(0xffffffffu, s2b, 2);
      const float ma = s1a * (1.f / D_), mb = s1b * (1.f / D_);
      const float ra = rsqrtf(fmaxf(s2a * (1.f / D_) - ma * ma, 0.f) + 1e-5f), rbb = rsqrtf(fmaxf(s2b * (1.f / D_) - mb * mb, 0.f) + 1e-5f);
      mbar_wait(BAR(B_VV), 0);
      mbar_wait(BAR(B_EMPTY + 5 - isE), 0);
      const uint32_t stg = sb + (5 - isE) * SLOT + (16 * w + (lane & 15)) * 128;
#pragma unroll
      for (int u = 0; u < 24; u++) {
        const float4 v0 = lds128f(sb + O_VV + (8 * u + 2 * c) * 16), v1 = lds128f(sb + O_VV + (8 * u + 2 * c + 1) * 16);
        const float h0 = fmaf(ra, fmaf(-ma, v0.x, ag[4 * u]), v0.y) * fmaf(ra, fmaf(-ma, v0.z, au[4 * u]), v0.w);
        const float h1 = fmaf(ra, fmaf(-ma, v1.x, ag[4 * u + 1]), v1.y) * fmaf(ra, fmaf(-ma, v1.z, au[4 * u + 1]), v1.w);
        const float h2 = fmaf(rbb, fmaf(-mb, v0.x, ag[4 * u + 2]), v0.y) * fmaf(rbb, fmaf(-mb, v0.z, au[4 * u + 2]), v0.w);
        const float h3 = fmaf(rbb, fmaf(-mb, v1.x, ag[4 * u + 3]), v1.y) * fmaf(rbb, fmaf(-mb, v1.z, au[4 * u + 3]), v1.w);
        hA[2 * u] = pack2(h0, h1); hA[2 * u + 1] = pack2(h2, h3);
        if (u & 1) {
          const int kq = u >> 1;
          stsm4(stg + (kq >> 2) * 8192 + (((2 * (kq & 3) + (lane >> 4)) ^ (lane & 7)) * 16), hA[4 * kq], hA[4 * kq + 1], hA[4 * kq + 2], hA[4 * kq + 3]);
        }
      }
      fence_async_smem();
      __syncwarp();
      if (lane == 0) mbar_arrive(BAR(B_STAGED + isE));
    }
    float o[80];
    {
#pragma unroll
      for (int s = 0; s < 3; s++) {
        mbar_wait(BAR(B_W2F + s), 0);
        const uint64_t dw = mkdesc(sb + w2entry(s), 4096, 512, 2);
        wg_fence();
#pragma unroll
        for (int kk = 0; kk < 4; kk++) wgmma_rs_160_1(o, hA[16 * s + 4 * kk], hA[16 * s + 4 * kk + 1], hA[16 * s + 4 * kk + 2], hA[16 * s + 4 * kk + 3], dw + kk * 64, (s | kk) ? 1 : 0);
        wg_commit();
        if (s > 0) { wg_wait<1>(); if (lane == 0 && w == 0) mbar_arrive(BAR(B_W2E + s - 1)); }
      }
      const uint32_t hreg = sb + (5 - isE) * SLOT;
#pragma unroll 1
      for (int i = 0; i < 9; i++) {
        const int e = i < 3 ? i + 3 : i - 3;
        mbar_wait(BAR(B_W2F + e), i >= 3);
        mbar_wait(BAR(B_HF + isE * 4 + (i & 3)), (i >> 2) & 1);
        if (i == 0 && lane == 0 && w == 0) TSTAMP(26 + isE);
        const uint64_t dw = mkdesc(sb + w2entry(e), 4096, 512, 2);
        const uint64_t dh = mkdesc(hreg + (i & 3) * 8192, 16, 1024, 1);
        wg_fence();
#pragma unroll
        for (int kk = 0; kk < 4; kk++) wgmma_ss_160_01(o, dh + kk * 2, dw + kk * 64, 1);
        wg_commit();
        wg_wait<1>();
        if (lane == 0 && w == 0) {
          mbar_arrive(BAR(B_W2E + (e == 0 ? 5 : e - 1)));
          if (i > 0) mbar_arrive(BAR(B_HE + isE * 4 + ((i - 1) & 3)));
        }
      }
      wg_wait<0>();
      regfence<80>(o);
      if (lane == 0 && w == 0) TSTAMP(28 + isE);
    }
    asm volatile("barrier.cluster.wait.aligned;" ::: "memory");
    const uint32_t red = sb + w2entry(0) + (tid & 127) * 16;
    if (isE) {
      mbar_wait(BAR(B_X1), 0);
      mbar_wait_cluster(BAR(B_RDY), 0);
      uint32_t rred, rbar;
      asm volatile("mapa.shared::cluster.u32 %0, %1, %2;" : "=r"(rred) : "r"(red), "r"(kh ^ 1));
      asm volatile("mapa.shared::cluster.u32 %0, %1, %2;" : "=r"(rbar) : "r"(BAR(B_RED)), "r"(kh ^ 1));
      const uint32_t xa = sb + O_SSM + ((lane & 7) + 8 * (lane >> 4)) * 128 + (((2 * w + ((lane >> 3) & 1)) ^ (lane & 7)) * 16);
#pragma unroll
      for (int u = 0; u < 10; u++) {
        uint32_t x0, x1, x2, x3;
        ldsm4t(xa + u * 2048, x0, x1, x2, x3);
        const float2 g0 = lds64f(sb + O_GB + (16 * u + 2 * c) * 4), g1 = lds64f(sb + O_GB + (16 * u + 8 + 2 * c) * 4);
        asm volatile("st.async.weak.shared::cluster.mbarrier::complete_tx::bytes.v4.f32 [%0], {%1,%2,%3,%4}, [%5];" ::"r"(rred + (2 * u) * 2048),
                     "f"(fmaf(g0.x, o[8 * u], blo(x0))), "f"(fmaf(g0.y, o[8 * u + 1], bhi(x0))), "f"(fmaf(g0.x, o[8 * u + 2], blo(x1))), "f"(fmaf(g0.y, o[8 * u + 3], bhi(x1))), "r"(rbar) : "memory");
        asm volatile("st.async.weak.shared::cluster.mbarrier::complete_tx::bytes.v4.f32 [%0], {%1,%2,%3,%4}, [%5];" ::"r"(rred + (2 * u + 1) * 2048),
                     "f"(fmaf(g1.x, o[8 * u + 4], blo(x2))), "f"(fmaf(g1.y, o[8 * u + 5], bhi(x2))), "f"(fmaf(g1.x, o[8 * u + 6], blo(x3))), "f"(fmaf(g1.y, o[8 * u + 7], bhi(x3))), "r"(rbar) : "memory");
      }
    } else {
      mbar_wait_cluster(BAR(B_RED), 0);
      if (tid == 128) TSTAMP(30);
      bar_sync(5, 128);
      const int row = 16 * w + (lane & 15);
      const uint32_t stg = sb + 5 * SLOT + row * 64;
#pragma unroll
      for (int u = 0; u < 10; u++) {
        const float4 p0 = lds128f(red + (2 * u) * 2048), p1 = lds128f(red + (2 * u + 1) * 2048);
        const float2 g0 = lds64f(sb + O_GB + (16 * u + 2 * c) * 4), g1 = lds64f(sb + O_GB + (16 * u + 8 + 2 * c) * 4);
        stsm4(stg + (u >> 1) * 4096 + (((2 * (u & 1) + (lane >> 4)) ^ ((row >> 1) & 3)) * 16),
              pack2(fmaf(g0.x, o[8 * u], p0.x), fmaf(g0.y, o[8 * u + 1], p0.y)), pack2(fmaf(g0.x, o[8 * u + 2], p0.z), fmaf(g0.y, o[8 * u + 3], p0.w)),
              pack2(fmaf(g1.x, o[8 * u + 4], p1.x), fmaf(g1.y, o[8 * u + 5], p1.y)), pack2(fmaf(g1.x, o[8 * u + 6], p1.z), fmaf(g1.y, o[8 * u + 7], p1.w)));
      }
      fence_async_smem();
      bar_sync(5, 128);
      if (tid == 128) {
#pragma unroll 1
        for (int i = 0; i < 5; i++) tma2d_store(&p.m_out, sb + 5 * SLOT + i * 4096, cg * 160 + i * 32, rb * 128 + kh * 64);
        bulk_commit(); bulk_wait0_read();
        TSTAMP(31);
      }
    }
  }
}

typedef CUresult (*EncodeFn)(CUtensorMap*, CUtensorMapDataType, cuuint32_t, void*, const cuuint64_t*, const cuuint64_t*, const cuuint32_t*,
                             const cuuint32_t*, CUtensorMapInterleave, CUtensorMapSwizzle, CUtensorMapL2promotion, CUtensorMapFloatOOBfill);

void make_map(EncodeFn enc, CUtensorMap* m, const void* ptr, uint64_t inner, uint64_t outer, uint32_t bi, uint32_t bo, CUtensorMapSwizzle sw) {
  cuuint64_t d[2] = {inner, outer};
  cuuint64_t s[1] = {inner * 2};
  cuuint32_t bx[2] = {bi, bo};
  cuuint32_t e[2] = {1, 1};
  enc(m, CU_TENSOR_MAP_DATA_TYPE_BFLOAT16, 2, const_cast<void*>(ptr), d, s, bx, e, CU_TENSOR_MAP_INTERLEAVE_NONE, sw, CU_TENSOR_MAP_L2_PROMOTION_L2_128B,
      CU_TENSOR_MAP_FLOAT_OOB_FILL_NONE);
}

}

extern "C" void kernel_launch(void* const* d_in, const int* in_sizes, int n_in, void* d_out, int out_size) {
  (void)in_sizes; (void)n_in; (void)out_size;
  void* f = nullptr;
  cudaDriverEntryPointQueryResult qr;
  cudaGetDriverEntryPoint("cuTensorMapEncodeTiled", &f, cudaEnableDefault, &qr);
  EncodeFn enc = (EncodeFn)f;
  void *qT, *x1T, *h;
  cudaGetSymbolAddress(&qT, g_qT);
  cudaGetSymbolAddress(&x1T, g_x1T);
  cudaGetSymbolAddress(&h, g_h);
  Params p;
  make_map(enc, &p.m_q, d_in[0], D_, S_, 32, 64, CU_TENSOR_MAP_SWIZZLE_64B);
  make_map(enc, &p.m_qT, qT, S_, D_, 64, 32, CU_TENSOR_MAP_SWIZZLE_128B);
  make_map(enc, &p.m_wm, d_in[11], 6 * D_, D_, 16, 160, CU_TENSOR_MAP_SWIZZLE_32B);
  make_map(enc, &p.m_wg, d_in[7], F_, D_, 64, 32, CU_TENSOR_MAP_SWIZZLE_128B);
  make_map(enc, &p.m_wu, d_in[8], F_, D_, 64, 32, CU_TENSOR_MAP_SWIZZLE_128B);
  make_map(enc, &p.m_wgs, d_in[7], F_, D_, 24, 160, CU_TENSOR_MAP_SWIZZLE_NONE);
  make_map(enc, &p.m_wus, d_in[8], F_, D_, 24, 160, CU_TENSOR_MAP_SWIZZLE_NONE);
  make_map(enc, &p.m_x1T, x1T, S_, D_, 64, 32, CU_TENSOR_MAP_SWIZZLE_128B);
  make_map(enc, &p.m_w2, d_in[9], D_, F_, 32, 64, CU_TENSOR_MAP_SWIZZLE_64B);
  make_map(enc, &p.m_h, h, F_, S_, 64, 64, CU_TENSOR_MAP_SWIZZLE_128B);
  make_map(enc, &p.m_out, d_out, D_, S_, 32, 64, CU_TENSOR_MAP_SWIZZLE_64B);
  p.q = (const __nv_bfloat16*)d_in[0];
  p.k = (const __nv_bfloat16*)d_in[1];
  p.v = (const __nv_bfloat16*)d_in[2];
  p.shift = (const __nv_bfloat16*)d_in[3];
  p.ssm = (const __nv_bfloat16*)d_in[4];
  p.ssmD = (const __nv_bfloat16*)d_in[5];
  p.c = (const __nv_bfloat16*)d_in[10];
  cudaFuncSetAttribute(fused_kernel, cudaFuncAttributeMaxDynamicSharedMemorySize, SMEM_BYTES);
  fused_kernel<<<128, 384, SMEM_BYTES, cudaStreamPerThread>>>(p);
}
```

```cpp
#include <cuda_runtime.h>
#include <cuda.h>
#include <cuda_bf16.h>
#include <cstdint>

namespace {

constexpr int S_ = 2048, D_ = 640, F_ = 1536;

__device__ __align__(1024) __nv_bfloat16 g_kvT[D_ * S_];
__device__ __align__(1024) __nv_bfloat16 g_qT[D_ * S_ * 2];
__device__ __align__(1024) __nv_bfloat16 g_x1T[D_ * S_];
__device__ __align__(1024) __nv_bfloat16 g_h[S_ * F_];
__device__ __align__(1024) uint32_t g_mod[6 * D_];
__device__ __align__(1024) float2 g_vv[2 * F_];
__device__ __align__(1024) uint32_t g_sync[32 * 32 + 64 * 8];
#define TSTAMP(i) do { } while (0)
#define T_SSM 600
#define T_PF 2400
#define PF_RATE 13

struct Params {
  CUtensorMap m_q, m_qT, m_kvT, m_wm, m_wg, m_wu, m_wgs, m_wus, m_x1T, m_w2, m_h, m_out;
  const __nv_bfloat16 *q, *k, *v, *shift, *ssm, *ssmD, *c, *wm, *wg, *wu, *w2;
};

constexpr uint32_t SLOT = 32768;
constexpr uint32_t O_KSTG = 0;
constexpr uint32_t O_WMOD = 65536;
constexpr uint32_t O_QIN = 106496;
constexpr uint32_t O_KV = 131072;
constexpr uint32_t O_QT = 153088;
constexpr uint32_t O_SSM = 196608;
constexpr uint32_t SEQ = 4112, KSEQ = 4368, KPAD = 272;
constexpr uint32_t O_CB = 217216;
constexpr uint32_t O_CS = O_CB + 1280;
constexpr uint32_t O_VV = O_CS + 2560;
constexpr uint32_t O_GB = O_VV + 3072;
constexpr uint32_t O_TMP = O_GB + 640;
constexpr uint32_t O_BAR = O_TMP + 1024;
constexpr uint32_t SMEM_BYTES = O_BAR + 1024;
enum { B_EMPTY = 0, B_W2E = 6, B_Y = 12, B_QST = 17, B_STAGED = 18, B_P2DONE = 20, B_RED = 21, B_RDY = 22, B_SILU = 23, B_FULL = 24, B_W2F = 30, B_HF = 36, B_HE = 44, B_SSM = 52, B_KV = 57,
       B_QIN = 62, B_QF = 63, B_WM = 64, B_MODDONE = 66, B_CB = 67, B_VV = 68, B_X1 = 69, B_STRIP = 70, B_NUM = 72 };
__device__ __forceinline__ uint32_t w2entry(int e) { return e < 3 ? 65536 + e * 20480 : (e - 3) * 20480; }

__device__ __forceinline__ uint32_t smem_u32(const void* p) { return (uint32_t)__cvta_generic_to_shared(p); }
__device__ __forceinline__ void mbar_init(uint32_t bar, uint32_t cnt) { asm volatile("mbarrier.init.shared::cta.b64 [%0], %1;" ::"r"(bar), "r"(cnt) : "memory"); }
__device__ __forceinline__ void mbar_expect(uint32_t bar, uint32_t bytes) { asm volatile("mbarrier.arrive.expect_tx.shared::cta.b64 _, [%0], %1;" ::"r"(bar), "r"(bytes) : "memory"); }
__device__ __forceinline__ void mbar_arrive(uint32_t bar) { asm volatile("mbarrier.arrive.shared::cta.b64 _, [%0];" ::"r"(bar) : "memory"); }
__device__ __forceinline__ void mbar_wait(uint32_t bar, uint32_t parity) {
  asm volatile("{\n .reg .pred p;\n .reg .u32 c;\n mov.u32 c, 0;\n LOOP:\n mbarrier.try_wait.parity.shared::cta.b64 p, [%0], %1;\n @p bra DONE;\n add.u32 c, c, 1;\n setp.lt.u32 p, c, 200000;\n @p bra LOOP;\n DONE:\n }" ::"r"(bar), "r"(parity) : "memory");
}
__device__ __forceinline__ void mbar_wait_cluster(uint32_t bar, uint32_t parity) {
  asm volatile("{\n .reg .pred p;\n .reg .u32 c;\n mov.u32 c, 0;\n LOOP:\n mbarrier.try_wait.parity.acquire.cluster.shared::cta.b64 p, [%0], %1;\n @p bra DONE;\n add.u32 c, c, 1;\n setp.lt.u32 p, c, 200000;\n @p bra LOOP;\n DONE:\n }" ::"r"(bar), "r"(parity) : "memory");
}
__device__ __forceinline__ uint32_t clk() { uint32_t c; asm volatile("mov.u32 %0, %%clock;" : "=r"(c)); return c; }
__device__ __forceinline__ uint32_t ldr(const uint32_t* p) { uint32_t v; asm volatile("ld.relaxed.gpu.global.u32 %0, [%1];" : "=r"(v) : "l"(p) : "memory"); return v; }
__device__ __forceinline__ uint4 ldr4(const uint32_t* p) {
  uint4 v; asm volatile("ld.relaxed.gpu.global.v4.u32 {%0,%1,%2,%3}, [%4];" : "=r"(v.x), "=r"(v.y), "=r"(v.z), "=r"(v.w) : "l"(p) : "memory"); return v;
}
__device__ __forceinline__ void poll_ge(const uint32_t* p, uint32_t target) {
  asm volatile("{\n .reg .pred p;\n .reg .u32 c, v;\n mov.u32 c, 0;\n LOOP:\n ld.relaxed.gpu.global.u32 v, [%0];\n sub.u32 v, v, %1;\n setp.ge.s32 p, v, 0;\n @p bra DONE;\n add.u32 c, c, 1;\n setp.lt.u32 p, c, 100000;\n @p bra LOOP;\n DONE:\n }" ::"l"(p), "r"(target) : "memory");
}
__device__ __forceinline__ uint32_t poll4(const uint32_t* p, uint32_t target, uint32_t need) {
  uint32_t m;
  int it = 0;
  do {
    const uint4 v = ldr4(p);
    m = (~(v.x - target) >> 31) | ((~(v.y - target) >> 31) << 1) | ((~(v.z - target) >> 31) << 2) | ((~(v.w - target) >> 31) << 3);
  } while ((m & need) != need && ++it < 100000);
  return m;
}
__device__ __forceinline__ uint32_t poll_tag(const uint32_t* p, uint32_t tag) {
  uint32_t v;
  asm volatile("{\n .reg .pred p;\n .reg .u32 c, t;\n mov.u32 c, 0;\n LOOP:\n ld.relaxed.gpu.global.u32 %0, [%1];\n shr.u32 t, %0, 16;\n setp.eq.u32 p, t, %2;\n @p bra DONE;\n add.u32 c, c, 1;\n setp.lt.u32 p, c, 100000;\n @p bra LOOP;\n DONE:\n }" : "=r"(v) : "l"(p), "r"(tag) : "memory");
  return v;
}
__device__ __forceinline__ void poll_tag20(const uint32_t* p, uint32_t tag, uint4* v) {
  int it = 0;
  uint32_t bad;
  do {
#pragma unroll
    for (int i = 0; i < 5; i++) v[i] = ldr4(p + i * 128);
    bad = 0;
#pragma unroll
    for (int i = 0; i < 5; i++) bad |= (v[i].x ^ (tag << 16)) | (v[i].y ^ (tag << 16)) | (v[i].z ^ (tag << 16)) | (v[i].w ^ (tag << 16));
  } while ((bad >> 16) && ++it < 100000);
}
__device__ __forceinline__ void signal_add(uint32_t* p) { asm volatile("red.relaxed.gpu.global.add.u32 [%0], 1;" ::"l"(p) : "memory"); }
__device__ __forceinline__ void tma3d(uint32_t dst, const CUtensorMap* m, int x, int y, int z, uint32_t bar) {
  asm volatile("cp.async.bulk.tensor.3d.shared::cluster.global.mbarrier::complete_tx::bytes [%0], [%1, {%3, %4, %5}], [%2];" ::"r"(dst), "l"(m), "r"(bar), "r"(x), "r"(y), "r"(z) : "memory");
}
__device__ __forceinline__ void tma3d_store(const CUtensorMap* m, uint32_t src, int x, int y, int z) {
  asm volatile("cp.async.bulk.tensor.3d.global.shared::cta.bulk_group [%0, {%2, %3, %4}], [%1];" ::"l"(m), "r"(src), "r"(x), "r"(y), "r"(z) : "memory");
}
__device__ __forceinline__ void bulk_st(void* dst, uint32_t src, uint32_t bytes) {
  asm volatile("cp.async.bulk.global.shared::cta.bulk_group [%0], [%1], %2;" ::"l"(dst), "r"(src), "r"(bytes) : "memory");
}
__device__ __forceinline__ void bulk_pf(const void* src, uint32_t bytes) { asm volatile("cp.async.bulk.prefetch.L2.global [%0], %1;" ::"l"(src), "r"(bytes) : "memory"); }
__device__ __forceinline__ void tma2d(uint32_t dst, const CUtensorMap* m, int x, int y, uint32_t bar) {
  asm volatile("cp.async.bulk.tensor.2d.shared::cluster.global.mbarrier::complete_tx::bytes [%0], [%1, {%3, %4}], [%2];" ::"r"(dst), "l"(m), "r"(bar), "r"(x), "r"(y) : "memory");
}
__device__ __forceinline__ void tma2d_store(const CUtensorMap* m, uint32_t src, int x, int y) {
  asm volatile("cp.async.bulk.tensor.2d.global.shared::cta.bulk_group [%0, {%2, %3}], [%1];" ::"l"(m), "r"(src), "r"(x), "r"(y) : "memory");
}
__device__ __forceinline__ void bulk_ld(uint32_t dst, const void* src, uint32_t bytes, uint32_t bar) {
  asm volatile("cp.async.bulk.shared::cluster.global.mbarrier::complete_tx::bytes [%0], [%1], %2, [%3];" ::"r"(dst), "l"(src), "r"(bytes), "r"(bar) : "memory");
}
__device__ __forceinline__ void bulk_commit() { asm volatile("cp.async.bulk.commit_group;" ::: "memory"); }
__device__ __forceinline__ void bulk_wait0() { asm volatile("cp.async.bulk.wait_group 0;" ::: "memory"); }
__device__ __forceinline__ void bulk_wait0_read() { asm volatile("cp.async.bulk.wait_group.read 0;" ::: "memory"); }
__device__ __forceinline__ void fence_async_smem() { asm volatile("fence.proxy.async.shared::cta;" ::: "memory"); }
__device__ __forceinline__ void bar_sync(int id, int n) { asm volatile("bar.sync %0, %1;" ::"r"(id), "r"(n) : "memory"); }
__device__ __forceinline__ void bar_arrive(int id, int n) { asm volatile("bar.arrive %0, %1;" ::"r"(id), "r"(n) : "memory"); }
__device__ __forceinline__ void wg_fence() { asm volatile("wgmma.fence.sync.aligned;" ::: "memory"); }
__device__ __forceinline__ void wg_commit() { asm volatile("wgmma.commit_group.sync.aligned;" ::: "memory"); }
template <int N> __device__ __forceinline__ void wg_wait() { asm volatile("wgmma.wait_group.sync.aligned %0;" ::"n"(N) : "memory"); }
__device__ __forceinline__ void ldsm4(uint32_t a, uint32_t& r0, uint32_t& r1, uint32_t& r2, uint32_t& r3) {
  asm volatile("ldmatrix.sync.aligned.m8n8.x4.shared.b16 {%0,%1,%2,%3}, [%4];" : "=r"(r0), "=r"(r1), "=r"(r2), "=r"(r3) : "r"(a) : "memory");
}
__device__ __forceinline__ void ldsm4t(uint32_t a, uint32_t& r0, uint32_t& r1, uint32_t& r2, uint32_t& r3) {
  asm volatile("ldmatrix.sync.aligned.m8n8.x4.trans.shared.b16 {%0,%1,%2,%3}, [%4];" : "=r"(r0), "=r"(r1), "=r"(r2), "=r"(r3) : "r"(a) : "memory");
}
__device__ __forceinline__ void stsm4t(uint32_t a, uint32_t r0, uint32_t r1, uint32_t r2, uint32_t r3) {
  asm volatile("stmatrix.sync.aligned.m8n8.x4.trans.shared.b16 [%0], {%1,%2,%3,%4};" ::"r"(a), "r"(r0), "r"(r1), "r"(r2), "r"(r3) : "memory");
}
__device__ __forceinline__ void stsm4(uint32_t a, uint32_t r0, uint32_t r1, uint32_t r2, uint32_t r3) {
  asm volatile("stmatrix.sync.aligned.m8n8.x4.shared.b16 [%0], {%1,%2,%3,%4};" ::"r"(a), "r"(r0), "r"(r1), "r"(r2), "r"(r3) : "memory");
}
__device__ __forceinline__ uint32_t lds32(uint32_t a) { uint32_t v; asm volatile("ld.shared.u32 %0, [%1];" : "=r"(v) : "r"(a) : "memory"); return v; }
__device__ __forceinline__ uint4 lds128(uint32_t a) { uint4 v; asm volatile("ld.shared.v4.u32 {%0,%1,%2,%3}, [%4];" : "=r"(v.x), "=r"(v.y), "=r"(v.z), "=r"(v.w) : "r"(a) : "memory"); return v; }
__device__ __forceinline__ float4 lds128f(uint32_t a) { float4 v; asm volatile("ld.shared.v4.f32 {%0,%1,%2,%3}, [%4];" : "=f"(v.x), "=f"(v.y), "=f"(v.z), "=f"(v.w) : "r"(a) : "memory"); return v; }
__device__ __forceinline__ float2 lds64f(uint32_t a) { float2 v; asm volatile("ld.shared.v2.f32 {%0,%1}, [%2];" : "=f"(v.x), "=f"(v.y) : "r"(a) : "memory"); return v; }
__device__ __forceinline__ void sts32(uint32_t a, uint32_t v) { asm volatile("st.shared.u32 [%0], %1;" ::"r"(a), "r"(v) : "memory"); }
__device__ __forceinline__ void sts64(uint32_t a, uint32_t x, uint32_t y) { asm volatile("st.shared.v2.u32 [%0], {%1,%2};" ::"r"(a), "r"(x), "r"(y) : "memory"); }
__device__ __forceinline__ void sts128(uint32_t a, uint32_t x, uint32_t y, uint32_t z, uint32_t w) { asm volatile("st.shared.v4.u32 [%0], {%1,%2,%3,%4};" ::"r"(a), "r"(x), "r"(y), "r"(z), "r"(w) : "memory"); }
__device__ __forceinline__ void sts16(uint32_t a, uint16_t v) { asm volatile("st.shared.u16 [%0], %1;" ::"r"(a), "h"(v) : "memory"); }
__device__ __forceinline__ uint32_t prmt(uint32_t a, uint32_t b, uint32_t s) { uint32_t r; asm("prmt.b32 %0, %1, %2, %3;" : "=r"(r) : "r"(a), "r"(b), "r"(s)); return r; }
__device__ __forceinline__ uint32_t hfma2(uint32_t a, uint32_t b, uint32_t c) { uint32_t r; asm("fma.rn.bf16x2 %0, %1, %2, %3;" : "=r"(r) : "r"(a), "r"(b), "r"(c)); return r; }
__device__ __forceinline__ uint32_t hmul2(uint32_t a, uint32_t b) { uint32_t r; asm("mul.rn.bf16x2 %0, %1, %2;" : "=r"(r) : "r"(a), "r"(b)); return r; }
__device__ __forceinline__ uint32_t pack2(float lo, float hi) { uint32_t r; asm("cvt.rn.bf16x2.f32 %0, %1, %2;" : "=r"(r) : "f"(hi), "f"(lo)); return r; }
__device__ __forceinline__ float blo(uint32_t v) { return __uint_as_float(v << 16); }
__device__ __forceinline__ float bhi(uint32_t v) { return __uint_as_float(v & 0xffff0000u); }
template <int N> __device__ __forceinline__ void halve(float* a, int lane, int bit) {
  const bool up = lane & bit;
#pragma unroll
  for (int i = 0; i < N / 2; i++) {
    const float keep = up ? a[i + N / 2] : a[i], send = up ? a[i] : a[i + N / 2];
    a[i] = keep + __shfl_xor_sync(0xffffffffu, send, bit);
  }
}
__device__ __forceinline__ float gemv16(uint32_t wa, uint32_t sa, int n, int lane) {
  float a[8] = {0, 0, 0, 0, 0, 0, 0, 0};
#pragma unroll 4
  for (int i = 0; i < n; i++) {
    const uint4 w = lds128(wa + i * 512 + lane * 16);
    const float x = __uint_as_float(lds32(sa + i * 64 + (lane >> 1) * 4));
    a[0] = fmaf(blo(w.x), x, a[0]); a[1] = fmaf(bhi(w.x), x, a[1]); a[2] = fmaf(blo(w.y), x, a[2]); a[3] = fmaf(bhi(w.y), x, a[3]);
    a[4] = fmaf(blo(w.z), x, a[4]); a[5] = fmaf(bhi(w.z), x, a[5]); a[6] = fmaf(blo(w.w), x, a[6]); a[7] = fmaf(bhi(w.w), x, a[7]);
  }
  halve<8>(a, lane, 16); halve<4>(a, lane, 8); halve<2>(a, lane, 4);
  return a[0] + __shfl_xor_sync(0xffffffffu, a[0], 2);
}
__device__ __forceinline__ uint64_t mkdesc(uint32_t addr, uint32_t lbo, uint32_t sbo, uint32_t swz) {
  return (uint64_t)((addr & 0x3FFFF) >> 4) | ((uint64_t)(lbo >> 4) << 16) | ((uint64_t)(sbo >> 4) << 32) | ((uint64_t)swz << 62);
}
template <int N> __device__ __forceinline__ void regfence(float* d) {
#pragma unroll
  for (int i = 0; i < N; i++) asm volatile("" : "+f"(d[i])::"memory");
}

__device__ __forceinline__ void wgmma_rs_32_0(float* d, uint32_t a0, uint32_t a1, uint32_t a2, uint32_t a3, uint64_t db, int sd) {
  asm volatile("{ .reg .pred p; setp.ne.b32 p, %21, 0; wgmma.mma_async.sync.aligned.m64n32k16.f32.bf16.bf16 {%0,%1,%2,%3,%4,%5,%6,%7,%8,%9,%10,%11,%12,%13,%14,%15}, {%16,%17,%18,%19}, %20, p, 1, 1, 0; }"
   : "+f"(d[0]), "+f"(d[1]), "+f"(d[2]), "+f"(d[3]), "+f"(d[4]), "+f"(d[5]), "+f"(d[6]), "+f"(d[7]), "+f"(d[8]), "+f"(d[9]), "+f"(d[10]), "+f"(d[11]), "+f"(d[12]), "+f"(d[13]), "+f"(d[14]), "+f"(d[15]) : "r"(a0), "r"(a1), "r"(a2), "r"(a3), "l"(db), "r"(sd));
}
__device__ __forceinline__ void wgmma_rs_160_1(float* d, uint32_t a0, uint32_t a1, uint32_t a2, uint32_t a3, uint64_t db, int sd) {
  asm volatile("{ .reg .pred p; setp.ne.b32 p, %85, 0; wgmma.mma_async.sync.aligned.m64n160k16.f32.bf16.bf16 {%0,%1,%2,%3,%4,%5,%6,%7,%8,%9,%10,%11,%12,%13,%14,%15,%16,%17,%18,%19,%20,%21,%22,%23,%24,%25,%26,%27,%28,%29,%30,%31,%32,%33,%34,%35,%36,%37,%38,%39,%40,%41,%42,%43,%44,%45,%46,%47,%48,%49,%50,%51,%52,%53,%54,%55,%56,%57,%58,%59,%60,%61,%62,%63,%64,%65,%66,%67,%68,%69,%70,%71,%72,%73,%74,%75,%76,%77,%78,%79}, {%80,%81,%82,%83}, %84, p, 1, 1, 1; }"
   : "+f"(d[0]), "+f"(d[1]), "+f"(d[2]), "+f"(d[3]), "+f"(d[4]), "+f"(d[5]), "+f"(d[6]), "+f"(d[7]), "+f"(d[8]), "+f"(d[9]), "+f"(d[10]), "+f"(d[11]), "+f"(d[12]), "+f"(d[13]), "+f"(d[14]), "+f"(d[15]), "+f"(d[16]), "+f"(d[17]), "+f"(d[18]), "+f"(d[19]), "+f"(d[20]), "+f"(d[21]), "+f"(d[22]), "+f"(d[23]), "+f"(d[24]), "+f"(d[25]), "+f"(d[26]), "+f"(d[27]), "+f"(d[28]), "+f"(d[29]), "+f"(d[30]), "+f"(d[31]), "+f"(d[32]), "+f"(d[33]), "+f"(d[34]), "+f"(d[35]), "+f"(d[36]), "+f"(d[37]), "+f"(d[38]), "+f"(d[39]), "+f"(d[40]), "+f"(d[41]), "+f"(d[42]), "+f"(d[43]), "+f"(d[44]), "+f"(d[45]), "+f"(d[46]), "+f"(d[47]), "+f"(d[48]), "+f"(d[49]), "+f"(d[50]), "+f"(d[51]), "+f"(d[52]), "+f"(d[53]), "+f"(d[54]), "+f"(d[55]), "+f"(d[56]), "+f"(d[57]), "+f"(d[58]), "+f"(d[59]), "+f"(d[60]), "+f"(d[61]), "+f"(d[62]), "+f"(d[63]), "+f"(d[64]), "+f"(d[65]), "+f"(d[66]), "+f"(d[67]), "+f"(d[68]), "+f"(d[69]), "+f"(d[70]), "+f"(d[71]), "+f"(d[72]), "+f"(d[73]), "+f"(d[74]), "+f"(d[75]), "+f"(d[76]), "+f"(d[77]), "+f"(d[78]), "+f"(d[79]) : "r"(a0), "r"(a1), "r"(a2), "r"(a3), "l"(db), "r"(sd));
}
__device__ __forceinline__ void wgmma_rs_192_1(float* d, uint32_t a0, uint32_t a1, uint32_t a2, uint32_t a3, uint64_t db, int sd) {
  asm volatile("{ .reg .pred p; setp.ne.b32 p, %101, 0; wgmma.mma_async.sync.aligned.m64n192k16.f32.bf16.bf16 {%0,%1,%2,%3,%4,%5,%6,%7,%8,%9,%10,%11,%12,%13,%14,%15,%16,%17,%18,%19,%20,%21,%22,%23,%24,%25,%26,%27,%28,%29,%30,%31,%32,%33,%34,%35,%36,%37,%38,%39,%40,%41,%42,%43,%44,%45,%46,%47,%48,%49,%50,%51,%52,%53,%54,%55,%56,%57,%58,%59,%60,%61,%62,%63,%64,%65,%66,%67,%68,%69,%70,%71,%72,%73,%74,%75,%76,%77,%78,%79,%80,%81,%82,%83,%84,%85,%86,%87,%88,%89,%90,%91,%92,%93,%94,%95}, {%96,%97,%98,%99}, %100, p, 1, 1, 1; }"
   : "+f"(d[0]), "+f"(d[1]), "+f"(d[2]), "+f"(d[3]), "+f"(d[4]), "+f"(d[5]), "+f"(d[6]), "+f"(d[7]), "+f"(d[8]), "+f"(d[9]), "+f"(d[10]), "+f"(d[11]), "+f"(d[12]), "+f"(d[13]), "+f"(d[14]), "+f"(d[15]), "+f"(d[16]), "+f"(d[17]), "+f"(d[18]), "+f"(d[19]), "+f"(d[20]), "+f"(d[21]), "+f"(d[22]), "+f"(d[23]), "+f"(d[24]), "+f"(d[25]), "+f"(d[26]), "+f"(d[27]), "+f"(d[28]), "+f"(d[29]), "+f"(d[30]), "+f"(d[31]), "+f"(d[32]), "+f"(d[33]), "+f"(d[34]), "+f"(d[35]), "+f"(d[36]), "+f"(d[37]), "+f"(d[38]), "+f"(d[39]), "+f"(d[40]), "+f"(d[41]), "+f"(d[42]), "+f"(d[43]), "+f"(d[44]), "+f"(d[45]), "+f"(d[46]), "+f"(d[47]), "+f"(d[48]), "+f"(d[49]), "+f"(d[50]), "+f"(d[51]), "+f"(d[52]), "+f"(d[53]), "+f"(d[54]), "+f"(d[55]), "+f"(d[56]), "+f"(d[57]), "+f"(d[58]), "+f"(d[59]), "+f"(d[60]), "+f"(d[61]), "+f"(d[62]), "+f"(d[63]), "+f"(d[64]), "+f"(d[65]), "+f"(d[66]), "+f"(d[67]), "+f"(d[68]), "+f"(d[69]), "+f"(d[70]), "+f"(d[71]), "+f"(d[72]), "+f"(d[73]), "+f"(d[74]), "+f"(d[75]), "+f"(d[76]), "+f"(d[77]), "+f"(d[78]), "+f"(d[79]), "+f"(d[80]), "+f"(d[81]), "+f"(d[82]), "+f"(d[83]), "+f"(d[84]), "+f"(d[85]), "+f"(d[86]), "+f"(d[87]), "+f"(d[88]), "+f"(d[89]), "+f"(d[90]), "+f"(d[91]), "+f"(d[92]), "+f"(d[93]), "+f"(d[94]), "+f"(d[95]) : "r"(a0), "r"(a1), "r"(a2), "r"(a3), "l"(db), "r"(sd));
}
__device__ __forceinline__ void wgmma_ss_160_01(float* d, uint64_t da, uint64_t db, int sd) {
  asm volatile("{ .reg .pred p; setp.ne.b32 p, %82, 0; wgmma.mma_async.sync.aligned.m64n160k16.f32.bf16.bf16 {%0,%1,%2,%3,%4,%5,%6,%7,%8,%9,%10,%11,%12,%13,%14,%15,%16,%17,%18,%19,%20,%21,%22,%23,%24,%25,%26,%27,%28,%29,%30,%31,%32,%33,%34,%35,%36,%37,%38,%39,%40,%41,%42,%43,%44,%45,%46,%47,%48,%49,%50,%51,%52,%53,%54,%55,%56,%57,%58,%59,%60,%61,%62,%63,%64,%65,%66,%67,%68,%69,%70,%71,%72,%73,%74,%75,%76,%77,%78,%79}, %80, %81, p, 1, 1, 0, 1; }"
   : "+f"(d[0]), "+f"(d[1]), "+f"(d[2]), "+f"(d[3]), "+f"(d[4]), "+f"(d[5]), "+f"(d[6]), "+f"(d[7]), "+f"(d[8]), "+f"(d[9]), "+f"(d[10]), "+f"(d[11]), "+f"(d[12]), "+f"(d[13]), "+f"(d[14]), "+f"(d[15]), "+f"(d[16]), "+f"(d[17]), "+f"(d[18]), "+f"(d[19]), "+f"(d[20]), "+f"(d[21]), "+f"(d[22]), "+f"(d[23]), "+f"(d[24]), "+f"(d[25]), "+f"(d[26]), "+f"(d[27]), "+f"(d[28]), "+f"(d[29]), "+f"(d[30]), "+f"(d[31]), "+f"(d[32]), "+f"(d[33]), "+f"(d[34]), "+f"(d[35]), "+f"(d[36]), "+f"(d[37]), "+f"(d[38]), "+f"(d[39]), "+f"(d[40]), "+f"(d[41]), "+f"(d[42]), "+f"(d[43]), "+f"(d[44]), "+f"(d[45]), "+f"(d[46]), "+f"(d[47]), "+f"(d[48]), "+f"(d[49]), "+f"(d[50]), "+f"(d[51]), "+f"(d[52]), "+f"(d[53]), "+f"(d[54]), "+f"(d[55]), "+f"(d[56]), "+f"(d[57]), "+f"(d[58]), "+f"(d[59]), "+f"(d[60]), "+f"(d[61]), "+f"(d[62]), "+f"(d[63]), "+f"(d[64]), "+f"(d[65]), "+f"(d[66]), "+f"(d[67]), "+f"(d[68]), "+f"(d[69]), "+f"(d[70]), "+f"(d[71]), "+f"(d[72]), "+f"(d[73]), "+f"(d[74]), "+f"(d[75]), "+f"(d[76]), "+f"(d[77]), "+f"(d[78]), "+f"(d[79]) : "l"(da), "l"(db), "r"(sd));
}

__global__ void __cluster_dims__(2, 1, 1) __launch_bounds__(384, 1) fused_kernel(const __grid_constant__ Params p) {
  extern __shared__ __align__(1024) uint8_t smem_raw[];
  const uint32_t t_start = clk();
  const uint32_t sb = smem_u32(smem_raw);
  const uint32_t bars = sb + O_BAR;
  const int tid = threadIdx.x, lane = tid & 31;
  const int warp = __shfl_sync(0xffffffffu, tid >> 5, 0);
  const int b = blockIdx.x;
  const int rb = b >> 3, cg = (b >> 1) & 3, kh = b & 1, fs = kh * 4 + cg;
  const int tb = b >> 2, cb = b & 3;
  auto BAR = [&](int i) { return bars + 8 * i; };
  auto init_bars = [&]() {
    if (lane == 0) {
#pragma unroll
      for (int i = 0; i < 6; i++) {
        const int x = warp * 6 + i;
        mbar_init(BAR(x), (x < B_Y || x == B_P2DONE || x == B_MODDONE) ? 2 : x < B_P2DONE ? 4 : 1);
      }
      if (warp == B_RED / 6) mbar_expect(BAR(B_RED), 40960);
      asm volatile("fence.mbarrier_init.release.cluster;" ::: "memory");
    }
  };
  if (tid == 0) TSTAMP(63);

  uint32_t epoch = 0;
  if (warp >= 2) {
    const int th = warp >= 7, g = (warp - 2 - 5 * th) * 8 + (lane & 7), run = th * 4 + (lane >> 3);
    const int ch = cb * 160 + g * 4, t0 = tb * 64 + run * 8;
    uint2 kk[11], vv[8];
    const __nv_bfloat16* kp = p.k + (size_t)t0 * D_ + ch;
    const __nv_bfloat16* vp = p.v + (size_t)t0 * D_ + ch;
#pragma unroll
    for (int i = 0; i < 8; i++) asm volatile("ld.global.nc.L1::no_allocate.v2.u32 {%0,%1}, [%2];" : "=r"(kk[i + 3].x), "=r"(kk[i + 3].y) : "l"(kp + i * D_));
#pragma unroll
    for (int i = 0; i < 8; i++) asm volatile("ld.global.nc.L1::no_allocate.v2.u32 {%0,%1}, [%2];" : "=r"(vv[i].x), "=r"(vv[i].y) : "l"(vp + i * D_));
    const __nv_bfloat16* kh_ = t0 ? kp - 3 * D_ : kp;
#pragma unroll
    for (int i = 0; i < 3; i++) asm volatile("ld.global.nc.L1::no_allocate.v2.u32 {%0,%1}, [%2];" : "=r"(kk[i].x), "=r"(kk[i].y) : "l"(kh_ + i * D_));
    uint4 s0 = __ldg((const uint4*)(p.shift + ch * 4)), s1 = __ldg((const uint4*)(p.shift + ch * 4 + 8));
    if (warp < 4) epoch = ldr(g_sync);
    init_bars();
    __syncthreads();
    if (t0 == 0) { kk[0] = kk[1] = kk[2] = make_uint2(0, 0); }
    uint32_t wx[4], wy[4];
    wx[0] = prmt(s0.x, s0.z, 0x5410); wx[1] = prmt(s0.x, s0.z, 0x7632); wx[2] = prmt(s0.y, s0.w, 0x5410); wx[3] = prmt(s0.y, s0.w, 0x7632);
    wy[0] = prmt(s1.x, s1.z, 0x5410); wy[1] = prmt(s1.x, s1.z, 0x7632); wy[2] = prmt(s1.y, s1.w, 0x5410); wy[3] = prmt(s1.y, s1.w, 0x7632);
    uint32_t rx[8], ry[8];
#pragma unroll
    for (int i = 0; i < 8; i++) {
      uint32_t ax = hmul2(kk[i].x, wx[3]), ay = hmul2(kk[i].y, wy[3]);
      ax = hfma2(kk[i + 1].x, wx[2], ax); ay = hfma2(kk[i + 1].y, wy[2], ay);
      ax = hfma2(kk[i + 2].x, wx[1], ax); ay = hfma2(kk[i + 2].y, wy[1], ay);
      ax = hfma2(kk[i + 3].x, wx[0], ax); ay = hfma2(kk[i + 3].y, wy[0], ay);
      rx[i] = hmul2(ax, vv[i].x); ry[i] = hmul2(ay, vv[i].y);
    }
    const uint32_t op = sb + O_KSTG + g * 128 + ((run ^ (lane & 7)) << 4);
    sts128(op, prmt(rx[0], rx[1], 0x5410), prmt(rx[2], rx[3], 0x5410), prmt(rx[4], rx[5], 0x5410), prmt(rx[6], rx[7], 0x5410));
    sts128(op + 5120, prmt(rx[0], rx[1], 0x7632), prmt(rx[2], rx[3], 0x7632), prmt(rx[4], rx[5], 0x7632), prmt(rx[6], rx[7], 0x7632));
    sts128(op + 10240, prmt(ry[0], ry[1], 0x5410), prmt(ry[2], ry[3], 0x5410), prmt(ry[4], ry[5], 0x5410), prmt(ry[6], ry[7], 0x5410));
    sts128(op + 15360, prmt(ry[0], ry[1], 0x7632), prmt(ry[2], ry[3], 0x7632), prmt(ry[4], ry[5], 0x7632), prmt(ry[6], ry[7], 0x7632));
    fence_async_smem();
    if (warp == 2) bar_sync(1, 320); else bar_arrive(1, 320);
  } else {
    epoch = ldr(g_sync);
    init_bars();
    if (warp == 1) {
      if (lane < 5) sts128(sb + O_SSM + lane * SEQ, 0, 0, 0, 0);
      if (lane < 17) {
#pragma unroll
        for (int j = 0; j < 5; j++) sts128(sb + O_KV + j * KSEQ + lane * 16, 0, 0, 0, 0);
      }
      fence_async_smem();
    }
    __syncthreads();
    if (tid == 0) TSTAMP(32);
  }
  asm volatile("barrier.cluster.arrive.relaxed.aligned;" ::: "memory");

  if (warp < 4) {
    asm volatile("setmaxnreg.dec.sync.aligned.u32 40;");
    if (warp == 0) {
      if (lane == 0) {
        auto loadS = [&](int j) { mbar_expect(BAR(B_SSM + j), 4096); bulk_ld(sb + O_SSM + j * SEQ + 16, p.ssm + (size_t)(j * 128 + b) * S_, 4096, BAR(B_SSM + j)); };
        auto loadM = [&](int h) {
          if (b < 120) {
            mbar_expect(BAR(B_WM + h), 20480);
#pragma unroll 1
            for (int i = 0; i < 4; i++) tma2d(sb + O_WMOD + h * 20480 + i * 5120, &p.m_wm, h * 1920 + b * 16, i * 160, BAR(B_WM + h));
          }
        };
        auto loadW = [&](int s) {
          const uint32_t dst = sb + (s % 6) * SLOT, bar = BAR(B_FULL + s % 6);
          mbar_expect(bar, SLOT);
#pragma unroll
          for (int i = 0; i < 3; i++) { tma2d(dst + i * 4096, &p.m_wg, fs * 192 + i * 64, s * 32, bar); tma2d(dst + 12288 + i * 4096, &p.m_wu, fs * 192 + i * 64, s * 32, bar); }
        };
        auto loadA = [&](int s) {
          const uint32_t dst = sb + (s % 6) * SLOT + 24576, bar = BAR(B_FULL + s % 6);
          tma2d(dst, &p.m_x1T, rb * 128, s * 32, bar);
          tma2d(dst + 4096, &p.m_x1T, rb * 128 + 64, s * 32, bar);
        };
        while (clk() - t_start < T_SSM) {}
        loadS(0); loadS(1);
        const uint32_t e1 = epoch + 1;
        uint32_t m = 0;
#pragma unroll 1
        for (int j = 0; j < 5; j++) {
          const int d = j * 128 + b;
          const uint32_t need = j == 4 ? 15 : 1u << (d / 160);
          if ((m & need) != need) m = poll4(g_sync + 32, e1 * 32, need);
          if (j == 0) TSTAMP(2);
          mbar_expect(BAR(B_KV + j), 4096);
          bulk_ld(sb + O_KV + j * KSEQ + KPAD, g_kvT + (size_t)d * S_, 4096, BAR(B_KV + j));
          if (j == 1) { mbar_expect(BAR(B_QIN), 20480); tma3d(sb + O_QIN, &p.m_q, 0, b * 16, 0, BAR(B_QIN)); }
        }
        loadS(2); loadM(0); loadS(3); loadS(4);
        poll_ge(g_sync + 2 * 32, e1 * 128);
        TSTAMP(3);
        mbar_expect(BAR(B_QF), 40960);
#pragma unroll 1
        for (int j = 0; j < 5; j++) bulk_ld(sb + O_QT + j * 8192, g_qT + (size_t)(j * 128 + b) * S_ * 2, 8192, BAR(B_QF));
        loadM(1);
        loadW(0); loadW(1);
        poll_ge(g_sync + 3 * 32 + 4, e1 * 128);
        TSTAMP(4);
        loadA(0); loadA(1);
        mbar_wait(BAR(B_MODDONE), 0);
        loadW(2); loadA(2); loadW(3); loadA(3);
        mbar_wait(BAR(B_P2DONE), 0);
        m = 0;
#pragma unroll 1
        for (int s = 4; s < 20; s++) {
          const uint32_t need = 1u << ((s >> 2) - 1);
          if (!(m & need)) m = poll4(g_sync + 3 * 32, e1 * 128, need);
          if (s >= 6) mbar_wait(BAR(B_EMPTY + s % 6), (s / 6 - 1) & 1);
          loadW(s);
          loadA(s);
        }
        if (b == 0) asm volatile("st.relaxed.gpu.global.u32 [%0], %1;" ::"l"(g_sync), "r"(e1) : "memory");
#pragma unroll 1
        for (int s = 0; s < 12; s++) {
          if (s == 0) { mbar_wait(BAR(B_EMPTY + 2), 0); }
          else if (s == 1) { mbar_wait(BAR(B_EMPTY + 3), 0); }
          else if (s == 3) { mbar_wait(BAR(B_EMPTY + 0), 1); }
          else if (s == 4) { mbar_wait(BAR(B_EMPTY + 1), 1); }
          else if (s >= 6) { mbar_wait(BAR(B_W2E + s - 6), 0); }
          const int e = s % 6;
          const int k0 = kh * 768 + ((cg + s / 3) & 3) * 192 + (s % 3) * 64;
          mbar_expect(BAR(B_W2F + e), 20480);
#pragma unroll
          for (int i = 0; i < 5; i++) tma2d(sb + w2entry(e) + i * 4096, &p.m_w2, cg * 160 + i * 32, k0, BAR(B_W2F + e));
        }
        mbar_wait(BAR(B_W2E + 0), 1);
        mbar_wait(BAR(B_W2E + 1), 1);
      }
      __syncwarp();
      asm volatile("barrier.cluster.wait.aligned;" ::: "memory");
      if (lane == 0)
        asm volatile("{ .reg .b32 r; mapa.shared::cluster.u32 r, %0, %1; mbarrier.arrive.shared::cluster.b64 _, [r]; }" ::"r"(BAR(B_RDY)), "r"(kh ^ 1) : "memory");
    } else if (warp == 1) {
      if (lane == 0) {
        uint32_t t = T_PF;
#pragma unroll 1
        for (int i = 0; i < 32; i++) {
          const __nv_bfloat16* a;
          uint32_t n = 3840;
          if (i < 5) { a = p.q + (b * 5 + i) * 2048; n = 4096; }
          else if (i == 5 || i == 11 || i == 12) { a = p.ssm + (size_t)((i == 5 ? 2 : i - 8) * 128 + b) * S_; n = 4096; }
          else if (i < 11) a = p.wm + (b * 5 + i - 6) * 3840;
          else if (i < 18) a = p.wm + (b * 5 + i - 13) * 3840 + 1920;
          else if (i < 28) { a = ((b & 1) ? p.wu : p.wg) + ((i - 18) * 64 + (b >> 1)) * F_; n = 3072; }
          else a = p.w2 + (b * 4 + i - 28) * 1920;
          while (clk() - t_start < t) {}
          bulk_pf(a, n);
          t += i < 20 ? n / PF_RATE : 64;
        }
        TSTAMP(35);
      }
      __syncwarp();
      const uint32_t e1 = epoch + 1, tag = e1 & 0xffff;
      if (b < 120) {
        mbar_wait(BAR(B_SILU), 0);
        mbar_wait(BAR(B_WM + 1), 0);
        if (lane == 0) TSTAMP(54);
        const float x = gemv16(sb + O_WMOD + 20480, sb + O_VV, 40, lane);
        if (!(lane & 2))
          asm volatile("st.relaxed.gpu.global.u32 [%0], %1;" ::"l"(g_mod + 1920 + b * 16 + (lane & 1) * 8 + ((lane >> 2) & 1) + ((lane >> 2) & 2) + ((lane >> 2) & 4)),
                       "r"(pack2(x, 0.f) | (tag << 16)) : "memory");
        if (lane == 0) TSTAMP(6);
      }
      __syncwarp();
      if (lane == 0) mbar_arrive(BAR(B_MODDONE));
      {
        uint4 v[5];
        poll_tag20(g_mod + 4 * D_ + lane * 4, tag, v);
#pragma unroll
        for (int i = 0; i < 5; i++) sts64(sb + O_CB + i * 256 + lane * 8, pack2(1.f + blo(v[i].x), 1.f + blo(v[i].y)), pack2(1.f + blo(v[i].z), 1.f + blo(v[i].w)));
        __syncwarp();
        if (lane == 0) { mbar_arrive(BAR(B_CB)); TSTAMP(7); }
        poll_tag20(g_mod + 3 * D_ + lane * 4, tag, v);
#pragma unroll
        for (int i = 0; i < 5; i++) {
          const float2 c2 = lds64f(sb + O_CB + i * 256 + lane * 8);
          const uint32_t c0 = __float_as_uint(c2.x), c1 = __float_as_uint(c2.y);
          sts128(sb + O_CS + i * 512 + lane * 16, prmt(c0, v[i].x, 0x5410), prmt(c0, v[i].y, 0x5432), prmt(c1, v[i].z, 0x5410), prmt(c1, v[i].w, 0x5432));
        }
#pragma unroll 1
        for (int i = 0; i < 5; i++) sts32(sb + O_GB + (lane + 32 * i) * 4, poll_tag(g_mod + 5 * D_ + cg * 160 + lane + 32 * i, tag) << 16);
      }
      mbar_wait(BAR(B_P2DONE), 0);
      if (b < 96) {
        float a[16];
#pragma unroll
        for (int i = 0; i < 16; i++) a[i] = 0.f;
        const int mat = b >= 48, col0 = (b - 48 * mat) * 32;
        const CUtensorMap* m = mat ? &p.m_wus : &p.m_wgs;
#pragma unroll 1
        for (int h = 0; h < 2; h++) {
          __syncwarp();
          if (lane == 0) {
            mbar_expect(BAR(B_STRIP), 20480);
            tma2d(sb + O_SSM, m, col0, h * 320, BAR(B_STRIP));
            tma2d(sb + O_SSM + 10240, m, col0, h * 320 + 160, BAR(B_STRIP));
          }
          mbar_wait(BAR(B_STRIP), h);
          if (lane == 0) TSTAMP(36 + h);
#pragma unroll 2
          for (int i = 0; i < 40; i++) {
            const uint4 w = lds128(sb + O_SSM + i * 512 + lane * 16);
            const uint32_t cs = lds32(sb + O_CS + h * 1280 + i * 32 + (lane >> 2) * 4);
            const float x = blo(cs), y = bhi(cs);
            float f;
            f = blo(w.x); a[0] = fmaf(f, x, a[0]); a[1] = fmaf(f, y, a[1]); f = bhi(w.x); a[2] = fmaf(f, x, a[2]); a[3] = fmaf(f, y, a[3]);
            f = blo(w.y); a[4] = fmaf(f, x, a[4]); a[5] = fmaf(f, y, a[5]); f = bhi(w.y); a[6] = fmaf(f, x, a[6]); a[7] = fmaf(f, y, a[7]);
            f = blo(w.z); a[8] = fmaf(f, x, a[8]); a[9] = fmaf(f, y, a[9]); f = bhi(w.z); a[10] = fmaf(f, x, a[10]); a[11] = fmaf(f, y, a[11]);
            f = blo(w.w); a[12] = fmaf(f, x, a[12]); a[13] = fmaf(f, y, a[13]); f = bhi(w.w); a[14] = fmaf(f, x, a[14]); a[15] = fmaf(f, y, a[15]);
          }
        }
        halve<16>(a, lane, 16); halve<8>(a, lane, 8); halve<4>(a, lane, 4);
        sts64(sb + O_TMP + ((lane & 3) * 8 + (lane >> 2)) * 8, __float_as_uint(a[0]), __float_as_uint(a[1]));
        fence_async_smem();
        __syncwarp();
        if (lane == 0) {
          bulk_st(g_vv + mat * F_ + col0, sb + O_TMP, 256);
          bulk_commit(); bulk_wait0();
          signal_add(g_sync + (4 + col0 / 192) * 32);
        }
      }
      if (lane == 0) {
        poll4(g_sync + 3 * 32, e1 * 128, 15);
        mbar_expect(BAR(B_X1), 20480);
#pragma unroll 1
        for (int i = 0; i < 5; i++) tma2d(sb + O_SSM + i * 4096, &p.m_x1T, rb * 128 + (kh ^ 1) * 64, cg * 160 + i * 32, BAR(B_X1));
        poll_ge(g_sync + (4 + fs) * 32, e1 * 12);
        mbar_expect(BAR(B_VV), 3072);
        bulk_ld(sb + O_VV, g_vv + fs * 192, 1536, BAR(B_VV));
        bulk_ld(sb + O_VV + 1536, g_vv + F_ + fs * 192, 1536, BAR(B_VV));
        TSTAMP(8);
      }
      __syncwarp();
      asm volatile("barrier.cluster.wait.aligned;" ::: "memory");
    } else {
      const int hw = warp - 2;
      const uint32_t e1 = epoch + 1, tag = e1 & 0xffff;
      if (hw == 0) {
        if (lane == 0) {
          TSTAMP(0);
          tma3d_store(&p.m_kvT, sb + O_KSTG, tb * 64, cb * 40, 0);
          bulk_commit(); bulk_wait0();
          signal_add(g_sync + 32 + cb);
          TSTAMP(1);
          mbar_wait(BAR(B_QST), 0);
#pragma unroll 1
          for (int i = 0; i < 4; i++) tma2d_store(&p.m_qT, sb + O_QT + i * 10240, b * 32, i * 160);
          bulk_commit(); bulk_wait0();
          signal_add(g_sync + 2 * 32);
          TSTAMP(10);
        }
      } else {
        uint32_t cv[10];
#pragma unroll
        for (int i = 0; i < 10; i++) cv[i] = __ldg((const uint32_t*)p.c + lane + 32 * i);
#pragma unroll
        for (int i = 0; i < 10; i++) {
          const float x = blo(cv[i]), y = bhi(cv[i]);
          const uint32_t s2 = pack2(__fdividef(x, 1.f + __expf(-x)), __fdividef(y, 1.f + __expf(-y)));
          sts64(sb + O_VV + (lane + 32 * i) * 8, s2 << 16, s2 & 0xffff0000u);
        }
        __syncwarp();
        if (lane == 0) mbar_arrive(BAR(B_SILU));
        if (b < 120) {
          mbar_wait(BAR(B_WM), 0);
          if (lane == 0) TSTAMP(53);
          const float x = gemv16(sb + O_WMOD, sb + O_VV, 40, lane);
          if (!(lane & 2))
            asm volatile("st.relaxed.gpu.global.u32 [%0], %1;" ::"l"(g_mod + b * 16 + (lane & 1) * 8 + ((lane >> 2) & 1) + ((lane >> 2) & 2) + ((lane >> 2) & 4)),
                         "r"(pack2(x, 0.f) | (tag << 16)) : "memory");
          if (lane == 0) TSTAMP(5);
        }
        __syncwarp();
        if (lane == 0) mbar_arrive(BAR(B_MODDONE));
      }
      __syncwarp();
      uint32_t mv = 0;
      if (lane < 15) mv = poll_tag(g_mod + (lane / 5) * D_ + (lane % 5) * 128 + b, tag);
      else if (lane < 20) mv = __ldg((const uint16_t*)p.ssmD + (lane - 15) * 128 + b);
      if (lane >= 5 && lane < 10) mv = pack2(1.f + blo(mv), 0.f);
      mv = prmt(mv, mv, 0x1010);
      __syncwarp();
      if (tid == 64) TSTAMP(11);
      mbar_wait(BAR(B_QF), 0);
      if (tid == 64) TSTAMP(56);
      const uint32_t qo = (lane >> 1) * 64 + (lane & 1) * 16 + (lane & 4) * 8;
#pragma unroll 1
      for (int j = hw; j < 5; j += 2) {
        const uint32_t sa = __shfl_sync(0xffffffffu, mv, j), c1 = __shfl_sync(0xffffffffu, mv, 5 + j);
        const uint32_t ga = __shfl_sync(0xffffffffu, mv, 10 + j), dv = __shfl_sync(0xffffffffu, mv, 15 + j);
        const uint32_t ya = sb + O_SSM + j * SEQ + 16 + lane * 16, ka = sb + O_KV + j * KSEQ + KPAD + lane * 16, qa = sb + O_QT + j * 8192 + qo;
        mbar_wait(BAR(B_Y + j), 0);
#pragma unroll 1
        for (int i = 0; i < 8; i++) {
          const uint4 y = lds128(ya + i * 512), kv = lds128(ka + i * 512), n = lds128((qa ^ 32) + i * 1024), q = lds128(qa + i * 1024);
          sts128(ya + i * 512, hfma2(ga, hmul2(hfma2(n.x, c1, sa), hfma2(kv.x, dv, y.x)), q.x), hfma2(ga, hmul2(hfma2(n.y, c1, sa), hfma2(kv.y, dv, y.y)), q.y),
                 hfma2(ga, hmul2(hfma2(n.z, c1, sa), hfma2(kv.z, dv, y.z)), q.z), hfma2(ga, hmul2(hfma2(n.w, c1, sa), hfma2(kv.w, dv, y.w)), q.w));
        }
        fence_async_smem();
        __syncwarp();
        if (lane == 0) {
          bulk_st(g_x1T + (size_t)(j * 128 + b) * S_, ya, 4096);
          bulk_commit();
          if (j >= 3) { bulk_wait0_read(); mbar_arrive(BAR(B_P2DONE)); }
          bulk_wait0();
          signal_add(g_sync + 3 * 32 + (j ? j - 1 : 4));
          TSTAMP(12 + j);
        }
        __syncwarp();
      }
      if (lane == 0) {
        const uint32_t reg = sb + (5 - hw) * SLOT;
        const int row0 = rb * 128 + (hw ^ kh) * 64;
        uint32_t* flags = g_sync + 32 * 32 + (rb * 4 + kh * 2 + hw) * 8;
        mbar_wait(BAR(B_STAGED + hw), 0);
#pragma unroll 1
        for (int i = 0; i < 3; i++) tma2d_store(&p.m_h, reg + i * 8192, fs * 192 + i * 64, row0);
        bulk_commit(); bulk_wait0();
        asm volatile("st.relaxed.gpu.global.u32 [%0], %1;" ::"l"(flags + cg), "r"(e1) : "memory");
        TSTAMP(17 + hw);
        uint32_t m = 0;
#pragma unroll 1
        for (int i = 0; i < 9; i++) {
          const int oc = (cg + 1 + i / 3) & 3;
          if (!(m & (1u << oc))) m = poll4(flags, e1, 1u << oc);
          if (i >= 4) mbar_wait(BAR(B_HE + hw * 4 + (i & 3)), ((i >> 2) - 1) & 1);
          mbar_expect(BAR(B_HF + hw * 4 + (i & 3)), 8192);
          tma2d(reg + (i & 3) * 8192, &p.m_h, kh * 768 + oc * 192 + (i % 3) * 64, row0, BAR(B_HF + hw * 4 + (i & 3)));
        }
      }
      __syncwarp();
      asm volatile("barrier.cluster.wait.aligned;" ::: "memory");
    }
  } else {
    asm volatile("setmaxnreg.inc.sync.aligned.u32 232;");
    const int isE = warp >= 8 ? 1 : 0;
    const int w = warp & 3, r = lane >> 2, c = lane & 3;
    if (isE) bar_arrive(2, 256);
    {
      const int nr = r & 3, low3 = w + 4 * (r >> 2);
      const int x0 = 16 * nr + low3 + 8 - 2 * c;
      const uint32_t offa = 16 + 4 * (x0 >> 1), offb = 16 + 4 * ((x0 - 1) >> 1);
      const uint32_t sel = (w & 1) ? 0x5432u : 0x7610u;
      const int cp = (c + nr) & 3;
      const bool carry = (c + nr) >= 4, b0 = nr & 1, b1 = nr & 2;
      const int ln1 = (lane & 16) | ((nr ^ 1) << 2) | ((cp - (nr ^ 1)) & 3);
      const int ln2 = (lane & 16) | ((nr ^ 2) << 2) | ((cp - (nr ^ 2)) & 3);
#pragma unroll 1
      for (int j = isE; j < 5; j += 2) {
        const uint32_t sa = sb + O_SSM + j * SEQ;
        uint32_t A[64];
        mbar_wait(BAR(B_SSM + j), 0);
        if (j == 0 && tid == 128) TSTAMP(34);
        if (w & 1) {
#pragma unroll
          for (int g = 0; g < 16; g++) {
            uint32_t u0 = lds32(sa + offa + g * 256), u1 = lds32(sa + offa + g * 256 + 128), u2 = lds32(sa + offa + g * 256 - 16), u3 = lds32(sa + offa + g * 256 + 112);
            A[4 * g] = prmt(u0, u0, sel); A[4 * g + 1] = prmt(u1, u1, sel); A[4 * g + 2] = prmt(u2, u2, sel); A[4 * g + 3] = prmt(u3, u3, sel);
          }
        } else {
#pragma unroll
          for (int g = 0; g < 16; g++) {
            A[4 * g] = prmt(lds32(sa + offa + g * 256), lds32(sa + offb + g * 256), sel);
            A[4 * g + 1] = prmt(lds32(sa + offa + g * 256 + 128), lds32(sa + offb + g * 256 + 128), sel);
            A[4 * g + 2] = prmt(lds32(sa + offa + g * 256 - 16), lds32(sa + offb + g * 256 - 16), sel);
            A[4 * g + 3] = prmt(lds32(sa + offa + g * 256 + 112), lds32(sa + offb + g * 256 + 112), sel);
          }
        }
        if (j == 1) {
          uint32_t x[40];
          mbar_wait(BAR(B_QIN), 0);
          if (tid == 256) TSTAMP(9);
          const uint32_t qa = sb + O_QIN + (lane & 15) * 128 + (((2 * w + (lane >> 4)) ^ (lane & 7)) << 4);
          float s1a = 0.f, s2a = 0.f, s1b = 0.f, s2b = 0.f;
#pragma unroll
          for (int i = 0; i < 10; i++) ldsm4(qa + i * 2048, x[4 * i], x[4 * i + 1], x[4 * i + 2], x[4 * i + 3]);
#pragma unroll
          for (int i = 0; i < 20; i++) {
            float f;
            f = blo(x[2 * i]); s1a += f; s2a = fmaf(f, f, s2a); f = bhi(x[2 * i]); s1a += f; s2a = fmaf(f, f, s2a);
            f = blo(x[2 * i + 1]); s1b += f; s2b = fmaf(f, f, s2b); f = bhi(x[2 * i + 1]); s1b += f; s2b = fmaf(f, f, s2b);
          }
          float z[4] = {s1a, s2a, s1b, s2b};
          halve<4>(z, lane, 2); halve<2>(z, lane, 1);
          sts32(sb + O_TMP + 512 + w * 128 + lane * 4, __float_as_uint(z[0]));
          bar_sync(6, 128);
          float4 t = lds128f(sb + O_TMP + 512 + r * 16);
#pragma unroll
          for (int i = 1; i < 4; i++) { const float4 u = lds128f(sb + O_TMP + 512 + i * 128 + r * 16); t.x += u.x; t.y += u.y; t.z += u.z; t.w += u.w; }
          const float ma = t.x * (1.f / D_), mb = t.z * (1.f / D_);
          const float ra = rsqrtf(fmaxf(t.y * (1.f / D_) - ma * ma, 0.f) + 1e-5f), rb_ = rsqrtf(fmaxf(t.w * (1.f / D_) - mb * mb, 0.f) + 1e-5f);
          const float oa = -ma * ra, ob = -mb * rb_;
          const uint32_t so = sb + O_QT + (16 * w + (lane & 7)) * 64 + (((lane >> 3) ^ (b & 2) ^ ((lane & 7) >> 1)) << 4);
#pragma unroll
          for (int i = 0; i < 20; i++)
            stsm4t(so + (i >> 1) * 4096 + (i & 1) * 512, x[2 * i], x[2 * i + 1], pack2(fmaf(blo(x[2 * i]), ra, oa), fmaf(bhi(x[2 * i]), ra, oa)),
                   pack2(fmaf(blo(x[2 * i + 1]), rb_, ob), fmaf(bhi(x[2 * i + 1]), rb_, ob)));
          fence_async_smem();
          __syncwarp();
          if (lane == 0) mbar_arrive(BAR(B_QST));
          if (tid == 256) TSTAMP(55);
        }
        float d[128];
        mbar_wait(BAR(B_KV + j), 0);
        bar_sync(2 + isE, 256);
        if (j == 0 && tid == 128) TSTAMP(19);
        const uint64_t db = mkdesc(sb + O_KV + j * KSEQ, 16, 128, 0);
        wg_fence();
        wgmma_rs_32_0(d + 112, A[0], A[1], A[2], A[3], db + 240, 0);
        wgmma_rs_32_0(d + 96, A[0], A[1], A[2], A[3], db + 208, 0);
        wgmma_rs_32_0(d + 80, A[0], A[1], A[2], A[3], db + 176, 0);
        wgmma_rs_32_0(d + 64, A[0], A[1], A[2], A[3], db + 144, 0);
        wgmma_rs_32_0(d + 112, A[4], A[5], A[6], A[7], db + 224, 1);
        wgmma_rs_32_0(d + 96, A[4], A[5], A[6], A[7], db + 192, 1);
        wgmma_rs_32_0(d + 80, A[4], A[5], A[6], A[7], db + 160, 1);
        wgmma_rs_32_0(d + 64, A[4], A[5], A[6], A[7], db + 128, 1);
        wgmma_rs_32_0(d + 112, A[8], A[9], A[10], A[11], db + 208, 1);
        wgmma_rs_32_0(d + 96, A[8], A[9], A[10], A[11], db + 176, 1);
        wgmma_rs_32_0(d + 80, A[8], A[9], A[10], A[11], db + 144, 1);
        wgmma_rs_32_0(d + 64, A[8], A[9], A[10], A[11], db + 112, 1);
        wgmma_rs_32_0(d + 112, A[12], A[13], A[14], A[15], db + 192, 1);
        wgmma_rs_32_0(d + 96, A[12], A[13], A[14], A[15], db + 160, 1);
        wgmma_rs_32_0(d + 80, A[12], A[13], A[14], A[15], db + 128, 1);
        wgmma_rs_32_0(d + 48, A[0], A[1], A[2], A[3], db + 112, 0);
        wgmma_rs_32_0(d + 112, A[16], A[17], A[18], A[19], db + 176, 1);
        wgmma_rs_32_0(d + 96, A[16], A[17], A[18], A[19], db + 144, 1);
        wgmma_rs_32_0(d + 80, A[16], A[17], A[18], A[19], db + 112, 1);
        wgmma_rs_32_0(d + 64, A[12], A[13], A[14], A[15], db + 96, 1);
        wgmma_rs_32_0(d + 112, A[20], A[21], A[22], A[23], db + 160, 1);
        wgmma_rs_32_0(d + 96, A[20], A[21], A[22], A[23], db + 128, 1);
        wgmma_rs_32_0(d + 80, A[20], A[21], A[22], A[23], db + 96, 1);
        wgmma_rs_32_0(d + 48, A[4], A[5], A[6], A[7], db + 96, 1);
        wgmma_rs_32_0(d + 112, A[24], A[25], A[26], A[27], db + 144, 1);
        wgmma_rs_32_0(d + 96, A[24], A[25], A[26], A[27], db + 112, 1);
        wgmma_rs_32_0(d + 80, A[24], A[25], A[26], A[27], db + 80, 1);
        wgmma_rs_32_0(d + 64, A[16], A[17], A[18], A[19], db + 80, 1);
        wgmma_rs_32_0(d + 112, A[28], A[29], A[30], A[31], db + 128, 1);
        wgmma_rs_32_0(d + 96, A[28], A[29], A[30], A[31], db + 96, 1);
        wgmma_rs_32_0(d + 48, A[8], A[9], A[10], A[11], db + 80, 1);
        wgmma_rs_32_0(d + 32, A[0], A[1], A[2], A[3], db + 80, 0);
        wgmma_rs_32_0(d + 112, A[32], A[33], A[34], A[35], db + 112, 1);
        wgmma_rs_32_0(d + 96, A[32], A[33], A[34], A[35], db + 80, 1);
        wgmma_rs_32_0(d + 80, A[28], A[29], A[30], A[31], db + 64, 1);
        wgmma_rs_32_0(d + 64, A[20], A[21], A[22], A[23], db + 64, 1);
        wgmma_rs_32_0(d + 112, A[36], A[37], A[38], A[39], db + 96, 1);
        wgmma_rs_32_0(d + 96, A[36], A[37], A[38], A[39], db + 64, 1);
        wgmma_rs_32_0(d + 48, A[12], A[13], A[14], A[15], db + 64, 1);
        wgmma_rs_32_0(d + 32, A[4], A[5], A[6], A[7], db + 64, 1);
        wgmma_rs_32_0(d + 112, A[40], A[41], A[42], A[43], db + 80, 1);
        wgmma_rs_32_0(d + 96, A[40], A[41], A[42], A[43], db + 48, 1);
        wgmma_rs_32_0(d + 80, A[32], A[33], A[34], A[35], db + 48, 1);
        wgmma_rs_32_0(d + 64, A[24], A[25], A[26], A[27], db + 48, 1);
        wgmma_rs_32_0(d + 112, A[44], A[45], A[46], A[47], db + 64, 1);
        wgmma_rs_32_0(d + 48, A[16], A[17], A[18], A[19], db + 48, 1);
        wgmma_rs_32_0(d + 32, A[8], A[9], A[10], A[11], db + 48, 1);
        wgmma_rs_32_0(d + 16, A[0], A[1], A[2], A[3], db + 48, 0);
        wgmma_rs_32_0(d + 112, A[48], A[49], A[50], A[51], db + 48, 1);
        wgmma_rs_32_0(d + 96, A[44], A[45], A[46], A[47], db + 32, 1);
        wgmma_rs_32_0(d + 80, A[36], A[37], A[38], A[39], db + 32, 1);
        wgmma_rs_32_0(d + 64, A[28], A[29], A[30], A[31], db + 32, 1);
        wgmma_rs_32_0(d + 112, A[52], A[53], A[54], A[55], db + 32, 1);
        wgmma_rs_32_0(d + 48, A[20], A[21], A[22], A[23], db + 32, 1);
        wgmma_rs_32_0(d + 32, A[12], A[13], A[14], A[15], db + 32, 1);
        wgmma_rs_32_0(d + 16, A[4], A[5], A[6], A[7], db + 32, 1);
        wgmma_rs_32_0(d + 112, A[56], A[57], A[58], A[59], db + 16, 1);
        wgmma_rs_32_0(d + 96, A[48], A[49], A[50], A[51], db + 16, 1);
        wgmma_rs_32_0(d + 80, A[40], A[41], A[42], A[43], db + 16, 1);
        wgmma_rs_32_0(d + 64, A[32], A[33], A[34], A[35], db + 16, 1);
        wgmma_rs_32_0(d + 48, A[24], A[25], A[26], A[27], db + 16, 1);
        wgmma_rs_32_0(d + 32, A[16], A[17], A[18], A[19], db + 16, 1);
        wgmma_rs_32_0(d + 16, A[8], A[9], A[10], A[11], db + 16, 1);
        wgmma_rs_32_0(d + 0, A[0], A[1], A[2], A[3], db + 16, 0);
        wgmma_rs_32_0(d + 112, A[60], A[61], A[62], A[63], db + 0, 1);
        wgmma_rs_32_0(d + 96, A[52], A[53], A[54], A[55], db + 0, 1);
        wgmma_rs_32_0(d + 80, A[44], A[45], A[46], A[47], db + 0, 1);
        wgmma_rs_32_0(d + 64, A[36], A[37], A[38], A[39], db + 0, 1);
        wgmma_rs_32_0(d + 48, A[28], A[29], A[30], A[31], db + 0, 1);
        wgmma_rs_32_0(d + 32, A[20], A[21], A[22], A[23], db + 0, 1);
        wgmma_rs_32_0(d + 16, A[12], A[13], A[14], A[15], db + 0, 1);
        wgmma_rs_32_0(d + 0, A[4], A[5], A[6], A[7], db + 0, 1);
        wg_commit();
        if (j < 4) bar_arrive(3 - isE, 256);
        wg_wait<0>();
        regfence<128>(d);
        if (lane == 0 && w == 0) TSTAMP(42 + j);
        float K[32];
        float pk = 0.f, ps = 0.f;
#pragma unroll
        for (int u = 0; u < 32; u++) {
          float e0 = d[4 * u], e1_ = d[4 * u + 1];
          if (u > 0) { e0 += d[4 * u - 2]; e1_ += d[4 * u - 1]; }
          float kx = b0 ? e1_ : e0, sx = b0 ? e0 : e1_;
          float kk = carry ? pk : kx, ss = carry ? ps : sx;
          pk = kx; ps = sx;
          K[u] = kk + __shfl_sync(0xffffffffu, ss, ln1);
        }
        const uint32_t ya = sa + 16 + 2 * (low3 + 16 * cp + 8 * (nr & 1) + 64 * (nr >> 1));
#pragma unroll
        for (int z = 0; z < 16; z++) {
          float kx = b1 ? K[2 * z + 1] : K[2 * z], sx = b1 ? K[2 * z] : K[2 * z + 1];
          float y = kx + __shfl_sync(0xffffffffu, sx, ln2);
          sts16(ya + z * 256, (uint16_t)pack2(y, 0.f));
        }
        __syncwarp();
        if (lane == 0) mbar_arrive(BAR(B_Y + j));
        if (lane == 0 && w == 0) TSTAMP(j >= 3 ? 17 + j : 47 + j);
      }
    }
    const int rh = isE ^ kh;
    uint32_t hA[48];
    {
      float ag[96], au[96];
      float s1a = 0.f, s2a = 0.f, s1b = 0.f, s2b = 0.f;
      const int kl = (lane & 7) + 8 * (lane >> 4);
      const uint32_t aoff = 24576 + rh * 4096 + kl * 128 + (((2 * w + ((lane >> 3) & 1)) ^ (lane & 7)) * 16);
      mbar_wait(BAR(B_CB), 0);
      int slot = 0, ph = 0;
#pragma unroll 1
      for (int s = 0; s < 20; s++) {
        const uint32_t st = sb + slot * SLOT;
        mbar_wait(BAR(B_FULL + slot), ph);
        if (s == 0 && lane == 0 && w == 0) TSTAMP(22 + isE);
        if (s && (s & 3) == 0 && tid == 128) TSTAMP(37 + (s >> 2));
#pragma unroll
        for (int kk = 0; kk < 2; kk++) {
          uint32_t a0, a1, a2, a3;
          ldsm4t(st + aoff + kk * 2048, a0, a1, a2, a3);
          const uint32_t c0 = lds32(sb + O_CB + s * 64 + kk * 32 + c * 4), c1 = lds32(sb + O_CB + s * 64 + kk * 32 + c * 4 + 16);
          float x;
          x = blo(a0); s1a += x; s2a = fmaf(x, x, s2a); x = bhi(a0); s1a += x; s2a = fmaf(x, x, s2a);
          x = blo(a1); s1b += x; s2b = fmaf(x, x, s2b); x = bhi(a1); s1b += x; s2b = fmaf(x, x, s2b);
          x = blo(a2); s1a += x; s2a = fmaf(x, x, s2a); x = bhi(a2); s1a += x; s2a = fmaf(x, x, s2a);
          x = blo(a3); s1b += x; s2b = fmaf(x, x, s2b); x = bhi(a3); s1b += x; s2b = fmaf(x, x, s2b);
          a0 = hmul2(a0, c0); a1 = hmul2(a1, c0); a2 = hmul2(a2, c1); a3 = hmul2(a3, c1);
          const uint64_t dg = mkdesc(st + kk * 2048, 4096, 1024, 1);
          wg_fence();
          wgmma_rs_192_1(ag, a0, a1, a2, a3, dg, (s | kk) ? 1 : 0);
          wgmma_rs_192_1(au, a0, a1, a2, a3, dg + (12288 >> 4), (s | kk) ? 1 : 0);
          wg_commit();
          wg_wait<1>();
          if (kk == 0 && s > 0 && lane == 0 && w == 0) mbar_arrive(BAR(B_EMPTY + (slot == 0 ? 5 : slot - 1)));
        }
        if (++slot == 6) { slot = 0; ph ^= 1; }
      }
      wg_wait<0>();
      regfence<96>(ag); regfence<96>(au);
      if (lane == 0 && w == 0) { mbar_arrive(BAR(B_EMPTY + 1)); TSTAMP(24 + isE); }
      s1a += __shfl_xor_sync(0xffffffffu, s1a, 1); s2a += __shfl_xor_sync(0xffffffffu, s2a, 1);
      s1b += __shfl_xor_sync(0xffffffffu, s1b, 1); s2b += __shfl_xor_sync(0xffffffffu, s2b, 1);
      s1a += __shfl_xor_sync(0xffffffffu, s1a, 2); s2a += __shfl_xor_sync(0xffffffffu, s2a, 2);
      s1b += __shfl_xor_sync(0xffffffffu, s1b, 2); s2b += __shfl_xor_sync(0xffffffffu, s2b, 2);
      const float ma = s1a * (1.f / D_), mb = s1b * (1.f / D_);
      const float ra = rsqrtf(fmaxf(s2a * (1.f / D_) - ma * ma, 0.f) + 1e-5f), rbb = rsqrtf(fmaxf(s2b * (1.f / D_) - mb * mb, 0.f) + 1e-5f);
      mbar_wait(BAR(B_VV), 0);
      if (tid == 128) TSTAMP(52);
      mbar_wait(BAR(B_EMPTY + 5 - isE), 0);
      const uint32_t stg = sb + (5 - isE) * SLOT + (16 * w + (lane & 15)) * 128;
#pragma unroll
      for (int u = 0; u < 24; u++) {
        const float4 vg = lds128f(sb + O_VV + (8 * u + 2 * c) * 8), vu = lds128f(sb + O_VV + 1536 + (8 * u + 2 * c) * 8);
        const float h0 = fmaf(ra, fmaf(-ma, vg.x, ag[4 * u]), vg.y) * fmaf(ra, fmaf(-ma, vu.x, au[4 * u]), vu.y);
        const float h1 = fmaf(ra, fmaf(-ma, vg.z, ag[4 * u + 1]), vg.w) * fmaf(ra, fmaf(-ma, vu.z, au[4 * u + 1]), vu.w);
        const float h2 = fmaf(rbb, fmaf(-mb, vg.x, ag[4 * u + 2]), vg.y) * fmaf(rbb, fmaf(-mb, vu.x, au[4 * u + 2]), vu.y);
        const float h3 = fmaf(rbb, fmaf(-mb, vg.z, ag[4 * u + 3]), vg.w) * fmaf(rbb, fmaf(-mb, vu.z, au[4 * u + 3]), vu.w);
        hA[2 * u] = pack2(h0, h1); hA[2 * u + 1] = pack2(h2, h3);
        if (u & 1) {
          const int kq = u >> 1;
          stsm4(stg + (kq >> 2) * 8192 + (((2 * (kq & 3) + (lane >> 4)) ^ (lane & 7)) * 16), hA[4 * kq], hA[4 * kq + 1], hA[4 * kq + 2], hA[4 * kq + 3]);
        }
      }
      fence_async_smem();
      __syncwarp();
      if (lane == 0) mbar_arrive(BAR(B_STAGED + isE));
      if (lane == 0 && w == 0) TSTAMP(50 + isE);
    }
    float o[80];
    {
#pragma unroll
      for (int s = 0; s < 3; s++) {
        mbar_wait(BAR(B_W2F + s), 0);
        const uint64_t dw = mkdesc(sb + w2entry(s), 4096, 512, 2);
        wg_fence();
#pragma unroll
        for (int kk = 0; kk < 4; kk++) wgmma_rs_160_1(o, hA[16 * s + 4 * kk], hA[16 * s + 4 * kk + 1], hA[16 * s + 4 * kk + 2], hA[16 * s + 4 * kk + 3], dw + kk * 64, (s | kk) ? 1 : 0);
        wg_commit();
        if (s > 0) { wg_wait<1>(); if (lane == 0 && w == 0) mbar_arrive(BAR(B_W2E + s - 1)); }
      }
      const uint32_t hreg = sb + (5 - isE) * SLOT;
#pragma unroll 1
      for (int i = 0; i < 9; i++) {
        const int e = i < 3 ? i + 3 : i - 3;
        mbar_wait(BAR(B_W2F + e), i >= 3);
        mbar_wait(BAR(B_HF + isE * 4 + (i & 3)), (i >> 2) & 1);
        if (i == 0 && lane == 0 && w == 0) TSTAMP(26 + isE);
        const uint64_t dw = mkdesc(sb + w2entry(e), 4096, 512, 2);
        const uint64_t dh = mkdesc(hreg + (i & 3) * 8192, 16, 1024, 1);
        wg_fence();
#pragma unroll
        for (int kk = 0; kk < 4; kk++) wgmma_ss_160_01(o, dh + kk * 2, dw + kk * 64, 1);
        wg_commit();
        wg_wait<1>();
        if (lane == 0 && w == 0) {
          mbar_arrive(BAR(B_W2E + (e == 0 ? 5 : e - 1)));
          if (i > 0) mbar_arrive(BAR(B_HE + isE * 4 + ((i - 1) & 3)));
        }
      }
      wg_wait<0>();
      regfence<80>(o);
      if (lane == 0 && w == 0) TSTAMP(28 + isE);
    }
    asm volatile("barrier.cluster.wait.aligned;" ::: "memory");
    const uint32_t red = sb + w2entry(0) + (tid & 127) * 16;
    if (isE) {
      mbar_wait(BAR(B_X1), 0);
      mbar_wait_cluster(BAR(B_RDY), 0);
      uint32_t rred, rbar;
      asm volatile("mapa.shared::cluster.u32 %0, %1, %2;" : "=r"(rred) : "r"(red), "r"(kh ^ 1));
      asm volatile("mapa.shared::cluster.u32 %0, %1, %2;" : "=r"(rbar) : "r"(BAR(B_RED)), "r"(kh ^ 1));
      const uint32_t xa = sb + O_SSM + ((lane & 7) + 8 * (lane >> 4)) * 128 + (((2 * w + ((lane >> 3) & 1)) ^ (lane & 7)) * 16);
#pragma unroll
      for (int u = 0; u < 10; u++) {
        uint32_t x0, x1, x2, x3;
        ldsm4t(xa + u * 2048, x0, x1, x2, x3);
        const float2 g0 = lds64f(sb + O_GB + (16 * u + 2 * c) * 4), g1 = lds64f(sb + O_GB + (16 * u + 8 + 2 * c) * 4);
        asm volatile("st.async.weak.shared::cluster.mbarrier::complete_tx::bytes.v4.f32 [%0], {%1,%2,%3,%4}, [%5];" ::"r"(rred + (2 * u) * 2048),
                     "f"(fmaf(g0.x, o[8 * u], blo(x0))), "f"(fmaf(g0.y, o[8 * u + 1], bhi(x0))), "f"(fmaf(g0.x, o[8 * u + 2], blo(x1))), "f"(fmaf(g0.y, o[8 * u + 3], bhi(x1))), "r"(rbar) : "memory");
        asm volatile("st.async.weak.shared::cluster.mbarrier::complete_tx::bytes.v4.f32 [%0], {%1,%2,%3,%4}, [%5];" ::"r"(rred + (2 * u + 1) * 2048),
                     "f"(fmaf(g1.x, o[8 * u + 4], blo(x2))), "f"(fmaf(g1.y, o[8 * u + 5], bhi(x2))), "f"(fmaf(g1.x, o[8 * u + 6], blo(x3))), "f"(fmaf(g1.y, o[8 * u + 7], bhi(x3))), "r"(rbar) : "memory");
      }
    } else {
      mbar_wait_cluster(BAR(B_RED), 0);
      if (tid == 128) TSTAMP(30);
      bar_sync(5, 128);
      const int row = 16 * w + (lane & 15);
      const uint32_t stg = sb + 5 * SLOT + row * 64;
#pragma unroll
      for (int u = 0; u < 10; u++) {
        const float4 p0 = lds128f(red + (2 * u) * 2048), p1 = lds128f(red + (2 * u + 1) * 2048);
        const float2 g0 = lds64f(sb + O_GB + (16 * u + 2 * c) * 4), g1 = lds64f(sb + O_GB + (16 * u + 8 + 2 * c) * 4);
        stsm4(stg + (u >> 1) * 4096 + (((2 * (u & 1) + (lane >> 4)) ^ ((row >> 1) & 3)) * 16),
              pack2(fmaf(g0.x, o[8 * u], p0.x), fmaf(g0.y, o[8 * u + 1], p0.y)), pack2(fmaf(g0.x, o[8 * u + 2], p0.z), fmaf(g0.y, o[8 * u + 3], p0.w)),
              pack2(fmaf(g1.x, o[8 * u + 4], p1.x), fmaf(g1.y, o[8 * u + 5], p1.y)), pack2(fmaf(g1.x, o[8 * u + 6], p1.z), fmaf(g1.y, o[8 * u + 7], p1.w)));
      }
      fence_async_smem();
      bar_sync(5, 128);
      if (tid == 128) {
#pragma unroll 1
        for (int i = 0; i < 5; i++) tma2d_store(&p.m_out, sb + 5 * SLOT + i * 4096, cg * 160 + i * 32, rb * 128 + kh * 64);
        bulk_commit(); bulk_wait0_read();
        TSTAMP(31);
      }
    }
  }
}

#define L2PROMO CU_TENSOR_MAP_L2_PROMOTION_L2_128B
typedef CUresult (*EncodeFn)(CUtensorMap*, CUtensorMapDataType, cuuint32_t, void*, const cuuint64_t*, const cuuint64_t*, const cuuint32_t*,
                             const cuuint32_t*, CUtensorMapInterleave, CUtensorMapSwizzle, CUtensorMapL2promotion, CUtensorMapFloatOOBfill);

void make_map(EncodeFn enc, CUtensorMap* m, const void* ptr, uint64_t inner, uint64_t outer, uint32_t bi, uint32_t bo, CUtensorMapSwizzle sw) {
  cuuint64_t d[2] = {inner, outer};
  cuuint64_t s[1] = {inner * 2};
  cuuint32_t bx[2] = {bi, bo};
  cuuint32_t e[2] = {1, 1};
  enc(m, CU_TENSOR_MAP_DATA_TYPE_BFLOAT16, 2, const_cast<void*>(ptr), d, s, bx, e, CU_TENSOR_MAP_INTERLEAVE_NONE, sw, L2PROMO,
      CU_TENSOR_MAP_FLOAT_OOB_FILL_NONE);
}

void make_map3(EncodeFn enc, CUtensorMap* m, const void* ptr, uint64_t d0, uint64_t d1, uint64_t d2, uint64_t s1, uint64_t s2, uint32_t b0, uint32_t b1, uint32_t b2) {
  cuuint64_t d[3] = {d0, d1, d2};
  cuuint64_t s[2] = {s1, s2};
  cuuint32_t bx[3] = {b0, b1, b2};
  cuuint32_t e[3] = {1, 1, 1};
  enc(m, CU_TENSOR_MAP_DATA_TYPE_BFLOAT16, 3, const_cast<void*>(ptr), d, s, bx, e, CU_TENSOR_MAP_INTERLEAVE_NONE, CU_TENSOR_MAP_SWIZZLE_128B, L2PROMO,
      CU_TENSOR_MAP_FLOAT_OOB_FILL_NONE);
}

}

extern "C" void kernel_launch(void* const* d_in, const int* in_sizes, int n_in, void* d_out, int out_size) {
  (void)in_sizes; (void)n_in; (void)out_size;
  void* f = nullptr;
  cudaDriverEntryPointQueryResult qr;
  cudaGetDriverEntryPoint("cuTensorMapEncodeTiled", &f, cudaEnableDefault, &qr);
  EncodeFn enc = (EncodeFn)f;
  void *qT, *kvT, *x1T, *h;
  cudaGetSymbolAddress(&kvT, g_kvT);
  cudaGetSymbolAddress(&qT, g_qT);
  cudaGetSymbolAddress(&x1T, g_x1T);
  cudaGetSymbolAddress(&h, g_h);
  Params p;
  make_map3(enc, &p.m_q, d_in[0], 64, S_, 10, D_ * 2, 128, 64, 16, 10);
  make_map3(enc, &p.m_kvT, kvT, S_, D_ / 4, 4, S_ * 8, S_ * 2, 64, 40, 4);
  make_map(enc, &p.m_qT, qT, 2 * S_, D_, 32, 160, CU_TENSOR_MAP_SWIZZLE_64B);
  make_map(enc, &p.m_wm, d_in[11], 6 * D_, D_, 16, 160, CU_TENSOR_MAP_SWIZZLE_NONE);
  make_map(enc, &p.m_wg, d_in[7], F_, D_, 64, 32, CU_TENSOR_MAP_SWIZZLE_128B);
  make_map(enc, &p.m_wu, d_in[8], F_, D_, 64, 32, CU_TENSOR_MAP_SWIZZLE_128B);
  make_map(enc, &p.m_wgs, d_in[7], F_, D_, 32, 160, CU_TENSOR_MAP_SWIZZLE_NONE);
  make_map(enc, &p.m_wus, d_in[8], F_, D_, 32, 160, CU_TENSOR_MAP_SWIZZLE_NONE);
  make_map(enc, &p.m_x1T, x1T, S_, D_, 64, 32, CU_TENSOR_MAP_SWIZZLE_128B);
  make_map(enc, &p.m_w2, d_in[9], D_, F_, 32, 64, CU_TENSOR_MAP_SWIZZLE_64B);
  make_map(enc, &p.m_h, h, F_, S_, 64, 64, CU_TENSOR_MAP_SWIZZLE_128B);
  make_map(enc, &p.m_out, d_out, D_, S_, 32, 64, CU_TENSOR_MAP_SWIZZLE_64B);
  p.q = (const __nv_bfloat16*)d_in[0];
  p.k = (const __nv_bfloat16*)d_in[1];
  p.v = (const __nv_bfloat16*)d_in[2];
  p.shift = (const __nv_bfloat16*)d_in[3];
  p.ssm = (const __nv_bfloat16*)d_in[4];
  p.ssmD = (const __nv_bfloat16*)d_in[5];
  p.c = (const __nv_bfloat16*)d_in[10];
  p.wm = (const __nv_bfloat16*)d_in[11];
  p.wg = (const __nv_bfloat16*)d_in[7];
  p.wu = (const __nv_bfloat16*)d_in[8];
  p.w2 = (const __nv_bfloat16*)d_in[9];
  cudaFuncSetAttribute(fused_kernel, cudaFuncAttributeMaxDynamicSharedMemorySize, SMEM_BYTES);
  fused_kernel<<<128, 384, SMEM_BYTES, cudaStreamPerThread>>>(p);
}
```

```cpp
#include <cuda_runtime.h>
#include <cuda.h>
#include <cuda_bf16.h>
#include <cstdint>

namespace {

constexpr int S_ = 2048, D_ = 640, F_ = 1536;

__device__ __align__(1024) __nv_bfloat16 g_kvT[D_ * S_];
__device__ __align__(1024) __nv_bfloat16 g_qT[D_ * S_ * 2];
__device__ __align__(1024) __nv_bfloat16 g_x1T[D_ * S_ * 2];
__device__ __align__(1024) __nv_bfloat16 g_h[S_ * F_];
__device__ __align__(1024) uint32_t g_mod[5 * 6 * D_];
__device__ __align__(1024) __nv_bfloat16 g_vv[8 * 5 * 48 * 16];
__device__ __align__(1024) uint32_t g_st[16 * 2 * 4 * 128];
__device__ __align__(1024) uint32_t g_sync[12 * 32 + 64 * 8];
#define TSTAMP(i) do { } while (0)
#define T_SSM 600
#define T_PF 2400
#define PF_RATE 13
#define PF_A 16
#define PF_B 28

struct Params {
  CUtensorMap m_q, m_qT, m_kvT, m_wm, m_wg, m_wu, m_xa, m_xr, m_w2, m_h, m_out, m_vv;
  const __nv_bfloat16 *q, *k, *v, *shift, *ssm, *ssmD, *c, *wg, *wu, *w2;
};

constexpr uint32_t SLOT = 32768;
constexpr uint32_t U_PART = 8192, U_RAW = 16400, U_ODD = U_RAW + 4160, U_KV = 28400;
constexpr uint32_t O_KSTG = SLOT;
constexpr uint32_t O_REG = 6 * SLOT;
constexpr uint32_t O_BP = O_REG + 20480;
constexpr uint32_t O_SILU = O_BP + 7808;
constexpr uint32_t O_CS = O_SILU + 384;
constexpr uint32_t O_GB = O_CS + 640;
constexpr uint32_t O_MV = O_GB + 640;
constexpr uint32_t O_EP = O_MV + 96;
constexpr uint32_t O_TMP = O_EP + 32;
constexpr uint32_t O_ST = O_TMP + 1152;
constexpr uint32_t O_BAR = O_ST + 1024;
constexpr uint32_t SMEM_BYTES = O_BAR + 1024;
enum { B_EMPTY = 0, B_W2E = 6, B_PL = 12, B_Y = 17, B_QST = 22, B_STAGED = 23, B_VVS = 25, B_RED = 26, B_RDY = 27, B_FULL = 28, B_W2F = 34, B_HF = 40, B_HE = 48,
       B_SSM = 56, B_KV = 61, B_QF = 66, B_QIN = 71, B_WM = 72, B_MOD = 74, B_CS = 76, B_VV = 77, B_X1 = 78, B_ST = 79, B_NUM = 81 };
__device__ __forceinline__ uint32_t w2entry(int e) { return e < 3 ? 65536 + e * 20480 : (e - 3) * 20480; }
__device__ __forceinline__ uint32_t bslot(int j) { return (j + (j > 0)) * SLOT; }

__device__ __forceinline__ uint32_t smem_u32(const void* p) { return (uint32_t)__cvta_generic_to_shared(p); }
__device__ __forceinline__ void mbar_init(uint32_t bar, uint32_t cnt) { asm volatile("mbarrier.init.shared::cta.b64 [%0], %1;" ::"r"(bar), "r"(cnt) : "memory"); }
__device__ __forceinline__ void mbar_expect(uint32_t bar, uint32_t bytes) { asm volatile("mbarrier.arrive.expect_tx.shared::cta.b64 _, [%0], %1;" ::"r"(bar), "r"(bytes) : "memory"); }
__device__ __forceinline__ void mbar_arrive(uint32_t bar) { asm volatile("mbarrier.arrive.shared::cta.b64 _, [%0];" ::"r"(bar) : "memory"); }
__device__ __forceinline__ void mbar_wait(uint32_t bar, uint32_t parity) {
  asm volatile("{\n .reg .pred p;\n .reg .u32 c;\n mov.u32 c, 0;\n LOOP:\n mbarrier.try_wait.parity.shared::cta.b64 p, [%0], %1;\n @p bra DONE;\n add.u32 c, c, 1;\n setp.lt.u32 p, c, 200000;\n @p bra LOOP;\n DONE:\n }" ::"r"(bar), "r"(parity) : "memory");
}
__device__ __forceinline__ void mbar_wait_cluster(uint32_t bar, uint32_t parity) {
  asm volatile("{\n .reg .pred p;\n .reg .u32 c;\n mov.u32 c, 0;\n LOOP:\n mbarrier.try_wait.parity.acquire.cluster.shared::cta.b64 p, [%0], %1;\n @p bra DONE;\n add.u32 c, c, 1;\n setp.lt.u32 p, c, 200000;\n @p bra LOOP;\n DONE:\n }" ::"r"(bar), "r"(parity) : "memory");
}
__device__ __forceinline__ uint32_t clk() { uint32_t c; asm volatile("mov.u32 %0, %%clock;" : "=r"(c)); return c; }
__device__ __forceinline__ uint32_t ldr(const uint32_t* p) { uint32_t v; asm volatile("ld.relaxed.gpu.global.u32 %0, [%1];" : "=r"(v) : "l"(p) : "memory"); return v; }
__device__ __forceinline__ uint4 ldr4(const uint32_t* p) {
  uint4 v; asm volatile("ld.relaxed.gpu.global.v4.u32 {%0,%1,%2,%3}, [%4];" : "=r"(v.x), "=r"(v.y), "=r"(v.z), "=r"(v.w) : "l"(p) : "memory"); return v;
}
__device__ __forceinline__ void poll_ge(const uint32_t* p, uint32_t target) {
  asm volatile("{\n .reg .pred p;\n .reg .u32 c, v;\n mov.u32 c, 0;\n LOOP:\n ld.relaxed.gpu.global.u32 v, [%0];\n sub.u32 v, v, %1;\n setp.ge.s32 p, v, 0;\n @p bra DONE;\n add.u32 c, c, 1;\n setp.lt.u32 p, c, 100000;\n @p bra LOOP;\n DONE:\n }" ::"l"(p), "r"(target) : "memory");
}
__device__ __forceinline__ uint32_t poll4(const uint32_t* p, uint32_t target, uint32_t need) {
  uint32_t m;
  int it = 0;
  do {
    const uint4 v = ldr4(p);
    m = (~(v.x - target) >> 31) | ((~(v.y - target) >> 31) << 1) | ((~(v.z - target) >> 31) << 2) | ((~(v.w - target) >> 31) << 3);
  } while ((m & need) != need && ++it < 100000);
  return m;
}
__device__ __forceinline__ void fence_gpu() { asm volatile("fence.acq_rel.gpu;" ::: "memory"); }
__device__ __forceinline__ void hint_add(uint32_t* p) { asm volatile("red.relaxed.gpu.global.add.u32 [%0], 1;" ::"l"(p) : "memory"); }
__device__ __forceinline__ void signal_add(uint32_t* p) { fence_gpu(); hint_add(p); }
__device__ __forceinline__ void tma3d(uint32_t dst, const CUtensorMap* m, int x, int y, int z, uint32_t bar) {
  asm volatile("cp.async.bulk.tensor.3d.shared::cluster.global.mbarrier::complete_tx::bytes [%0], [%1, {%3, %4, %5}], [%2];" ::"r"(dst), "l"(m), "r"(bar), "r"(x), "r"(y), "r"(z) : "memory");
}
__device__ __forceinline__ void tma3d_store(const CUtensorMap* m, uint32_t src, int x, int y, int z) {
  asm volatile("cp.async.bulk.tensor.3d.global.shared::cta.bulk_group [%0, {%2, %3, %4}], [%1];" ::"l"(m), "r"(src), "r"(x), "r"(y), "r"(z) : "memory");
}
__device__ __forceinline__ void bulk_st(void* dst, uint32_t src, uint32_t bytes) {
  asm volatile("cp.async.bulk.global.shared::cta.bulk_group [%0], [%1], %2;" ::"l"(dst), "r"(src), "r"(bytes) : "memory");
}
__device__ __forceinline__ void bulk_pf(const void* src, uint32_t bytes) { asm volatile("cp.async.bulk.prefetch.L2.global [%0], %1;" ::"l"(src), "r"(bytes) : "memory"); }
__device__ __forceinline__ void tma2d(uint32_t dst, const CUtensorMap* m, int x, int y, uint32_t bar) {
  asm volatile("cp.async.bulk.tensor.2d.shared::cluster.global.mbarrier::complete_tx::bytes [%0], [%1, {%3, %4}], [%2];" ::"r"(dst), "l"(m), "r"(bar), "r"(x), "r"(y) : "memory");
}
__device__ __forceinline__ void tma2d_store(const CUtensorMap* m, uint32_t src, int x, int y) {
  asm volatile("cp.async.bulk.tensor.2d.global.shared::cta.bulk_group [%0, {%2, %3}], [%1];" ::"l"(m), "r"(src), "r"(x), "r"(y) : "memory");
}
__device__ __forceinline__ void bulk_ld(uint32_t dst, const void* src, uint32_t bytes, uint32_t bar) {
  asm volatile("cp.async.bulk.shared::cluster.global.mbarrier::complete_tx::bytes [%0], [%1], %2, [%3];" ::"r"(dst), "l"(src), "r"(bytes), "r"(bar) : "memory");
}
__device__ __forceinline__ void bulk_commit() { asm volatile("cp.async.bulk.commit_group;" ::: "memory"); }
template <int N> __device__ __forceinline__ void bulk_wait() { asm volatile("cp.async.bulk.wait_group %0;" ::"n"(N) : "memory"); }
__device__ __forceinline__ void bulk_wait0_read() { asm volatile("cp.async.bulk.wait_group.read 0;" ::: "memory"); }
__device__ __forceinline__ void fence_async_smem() { asm volatile("fence.proxy.async.shared::cta;" ::: "memory"); }
__device__ __forceinline__ void bar_sync(int id, int n) { asm volatile("bar.sync %0, %1;" ::"r"(id), "r"(n) : "memory"); }
__device__ __forceinline__ void bar_arrive(int id, int n) { asm volatile("bar.arrive %0, %1;" ::"r"(id), "r"(n) : "memory"); }
__device__ __forceinline__ void wg_fence() { asm volatile("wgmma.fence.sync.aligned;" ::: "memory"); }
__device__ __forceinline__ void wg_commit() { asm volatile("wgmma.commit_group.sync.aligned;" ::: "memory"); }
template <int N> __device__ __forceinline__ void wg_wait() { asm volatile("wgmma.wait_group.sync.aligned %0;" ::"n"(N) : "memory"); }
__device__ __forceinline__ void ldsm4(uint32_t a, uint32_t& r0, uint32_t& r1, uint32_t& r2, uint32_t& r3) {
  asm volatile("ldmatrix.sync.aligned.m8n8.x4.shared.b16 {%0,%1,%2,%3}, [%4];" : "=r"(r0), "=r"(r1), "=r"(r2), "=r"(r3) : "r"(a) : "memory");
}
__device__ __forceinline__ void ldsm4t(uint32_t a, uint32_t& r0, uint32_t& r1, uint32_t& r2, uint32_t& r3) {
  asm volatile("ldmatrix.sync.aligned.m8n8.x4.trans.shared.b16 {%0,%1,%2,%3}, [%4];" : "=r"(r0), "=r"(r1), "=r"(r2), "=r"(r3) : "r"(a) : "memory");
}
__device__ __forceinline__ void stsm4t(uint32_t a, uint32_t r0, uint32_t r1, uint32_t r2, uint32_t r3) {
  asm volatile("stmatrix.sync.aligned.m8n8.x4.trans.shared.b16 [%0], {%1,%2,%3,%4};" ::"r"(a), "r"(r0), "r"(r1), "r"(r2), "r"(r3) : "memory");
}
__device__ __forceinline__ void stsm4(uint32_t a, uint32_t r0, uint32_t r1, uint32_t r2, uint32_t r3) {
  asm volatile("stmatrix.sync.aligned.m8n8.x4.shared.b16 [%0], {%1,%2,%3,%4};" ::"r"(a), "r"(r0), "r"(r1), "r"(r2), "r"(r3) : "memory");
}
__device__ __forceinline__ uint32_t lds32(uint32_t a) { uint32_t v; asm volatile("ld.shared.u32 %0, [%1];" : "=r"(v) : "r"(a) : "memory"); return v; }
__device__ __forceinline__ uint4 lds128(uint32_t a) { uint4 v; asm volatile("ld.shared.v4.u32 {%0,%1,%2,%3}, [%4];" : "=r"(v.x), "=r"(v.y), "=r"(v.z), "=r"(v.w) : "r"(a) : "memory"); return v; }
__device__ __forceinline__ float4 lds128f(uint32_t a) { float4 v; asm volatile("ld.shared.v4.f32 {%0,%1,%2,%3}, [%4];" : "=f"(v.x), "=f"(v.y), "=f"(v.z), "=f"(v.w) : "r"(a) : "memory"); return v; }
__device__ __forceinline__ float2 lds64f(uint32_t a) { float2 v; asm volatile("ld.shared.v2.f32 {%0,%1}, [%2];" : "=f"(v.x), "=f"(v.y) : "r"(a) : "memory"); return v; }
__device__ __forceinline__ void sts32(uint32_t a, uint32_t v) { asm volatile("st.shared.u32 [%0], %1;" ::"r"(a), "r"(v) : "memory"); }
__device__ __forceinline__ void sts64(uint32_t a, uint32_t x, uint32_t y) { asm volatile("st.shared.v2.u32 [%0], {%1,%2};" ::"r"(a), "r"(x), "r"(y) : "memory"); }
__device__ __forceinline__ void sts128(uint32_t a, uint32_t x, uint32_t y, uint32_t z, uint32_t w) { asm volatile("st.shared.v4.u32 [%0], {%1,%2,%3,%4};" ::"r"(a), "r"(x), "r"(y), "r"(z), "r"(w) : "memory"); }
__device__ __forceinline__ void sts16(uint32_t a, uint16_t v) { asm volatile("st.shared.u16 [%0], %1;" ::"r"(a), "h"(v) : "memory"); }
__device__ __forceinline__ uint32_t prmt(uint32_t a, uint32_t b, uint32_t s) { uint32_t r; asm("prmt.b32 %0, %1, %2, %3;" : "=r"(r) : "r"(a), "r"(b), "r"(s)); return r; }
__device__ __forceinline__ uint32_t hfma2(uint32_t a, uint32_t b, uint32_t c) { uint32_t r; asm("fma.rn.bf16x2 %0, %1, %2, %3;" : "=r"(r) : "r"(a), "r"(b), "r"(c)); return r; }
__device__ __forceinline__ uint32_t hmul2(uint32_t a, uint32_t b) { uint32_t r; asm("mul.rn.bf16x2 %0, %1, %2;" : "=r"(r) : "r"(a), "r"(b)); return r; }
__device__ __forceinline__ uint32_t pack2(float lo, float hi) { uint32_t r; asm("cvt.rn.bf16x2.f32 %0, %1, %2;" : "=r"(r) : "f"(hi), "f"(lo)); return r; }
__device__ __forceinline__ float blo(uint32_t v) { return __uint_as_float(v << 16); }
__device__ __forceinline__ float bhi(uint32_t v) { return __uint_as_float(v & 0xffff0000u); }
__device__ __forceinline__ uint32_t hadd2(uint32_t a, uint32_t b) { uint32_t r; asm("add.rn.bf16x2 %0, %1, %2;" : "=r"(r) : "r"(a), "r"(b)); return r; }
__device__ __forceinline__ void str(uint32_t* p, uint32_t v) { asm volatile("st.relaxed.gpu.global.u32 [%0], %1;" ::"l"(p), "r"(v) : "memory"); }
__device__ __forceinline__ uint32_t tagf(float x, uint32_t tag) { return (__float_as_uint(x) & ~3u) | tag; }
template <int N> __device__ __forceinline__ float4 gather4(const uint32_t* p, int stride, uint32_t tag) {
  uint4 v[N];
  int it = 0;
  uint32_t bad;
  do {
#pragma unroll
    for (int i = 0; i < N; i++) v[i] = ldr4(p + i * stride);
    bad = 0;
#pragma unroll
    for (int i = 0; i < N; i++) bad |= (v[i].x ^ tag) | (v[i].y ^ tag) | (v[i].z ^ tag) | (v[i].w ^ tag);
  } while ((bad & 3) && ++it < 100000);
  float4 s = make_float4(__uint_as_float(v[0].x), __uint_as_float(v[0].y), __uint_as_float(v[0].z), __uint_as_float(v[0].w));
#pragma unroll
  for (int i = 1; i < N; i++) { s.x += __uint_as_float(v[i].x); s.y += __uint_as_float(v[i].y); s.z += __uint_as_float(v[i].z); s.w += __uint_as_float(v[i].w); }
  return s;
}
__device__ __forceinline__ float gather1(const uint32_t* p, uint32_t tag) {
  uint32_t v[5], bad;
  int it = 0;
  do {
#pragma unroll
    for (int i = 0; i < 5; i++) v[i] = ldr(p + i * 6 * D_);
    bad = (v[0] ^ tag) | (v[1] ^ tag) | (v[2] ^ tag) | (v[3] ^ tag) | (v[4] ^ tag);
  } while ((bad & 3) && ++it < 100000);
  return __uint_as_float(v[0]) + __uint_as_float(v[1]) + __uint_as_float(v[2]) + __uint_as_float(v[3]) + __uint_as_float(v[4]);
}
__device__ __forceinline__ float rbf(float x) { return blo(pack2(x, 0.f)); }
template <int N> __device__ __forceinline__ void part2(uint32_t u, int half, int it0, int lane, uint4 mv) {
  const uint32_t pa = u + U_PART + half * 8192 + it0 * 512 + lane * 16;
  const uint32_t qa = u + half * 4096 + it0 * 1024 + (lane >> 1) * 64 + (lane & 1) * 16 + (lane & 4) * 8;
#pragma unroll(N > 2 ? 1 : 2)
  for (int i = 0; i < N; i++) {
    const uint4 p0 = lds128(pa + i * 512), p1 = lds128(pa + i * 512 + 2048), p2 = lds128(pa + i * 512 + 4096), p3 = lds128(pa + i * 512 + 6144);
    const uint4 n = lds128((qa ^ 32) + i * 1024), q = lds128(qa + i * 1024);
    const uint32_t x0 = hfma2(hfma2(n.x, mv.x, mv.y), hadd2(hadd2(p0.x, p1.x), hadd2(p2.x, p3.x)), q.x);
    const uint32_t x1 = hfma2(hfma2(n.y, mv.x, mv.y), hadd2(hadd2(p0.y, p1.y), hadd2(p2.y, p3.y)), q.y);
    const uint32_t x2 = hfma2(hfma2(n.z, mv.x, mv.y), hadd2(hadd2(p0.z, p1.z), hadd2(p2.z, p3.z)), q.z);
    const uint32_t x3 = hfma2(hfma2(n.w, mv.x, mv.y), hadd2(hadd2(p0.w, p1.w), hadd2(p2.w, p3.w)), q.w);
    sts128(pa + i * 512, x0, x1, x2, x3);
    sts128(pa + i * 512 + 2048, hmul2(x0, mv.z), hmul2(x1, mv.z), hmul2(x2, mv.z), hmul2(x3, mv.z));
  }
}
template <int N> __device__ __forceinline__ void halve(float* a, int lane, int bit) {
  const bool up = lane & bit;
#pragma unroll
  for (int i = 0; i < N / 2; i++) {
    const float keep = up ? a[i + N / 2] : a[i], send = up ? a[i] : a[i + N / 2];
    a[i] = keep + __shfl_xor_sync(0xffffffffu, send, bit);
  }
}
__device__ __forceinline__ uint64_t mkdesc(uint32_t addr, uint32_t lbo, uint32_t sbo, uint32_t swz) {
  return (uint64_t)((addr & 0x3FFFF) >> 4) | ((uint64_t)(lbo >> 4) << 16) | ((uint64_t)(sbo >> 4) << 32) | ((uint64_t)swz << 62);
}
template <int N> __device__ __forceinline__ void regfence(float* d) {
#pragma unroll
  for (int i = 0; i < N; i++) asm volatile("" : "+f"(d[i])::"memory");
}

__device__ __forceinline__ void wgmma_rs_32_0(float* d, uint32_t a0, uint32_t a1, uint32_t a2, uint32_t a3, uint64_t db, int sd) {
  asm volatile("{ .reg .pred p; setp.ne.b32 p, %21, 0; wgmma.mma_async.sync.aligned.m64n32k16.f32.bf16.bf16 {%0,%1,%2,%3,%4,%5,%6,%7,%8,%9,%10,%11,%12,%13,%14,%15}, {%16,%17,%18,%19}, %20, p, 1, 1, 0; }"
   : "+f"(d[0]), "+f"(d[1]), "+f"(d[2]), "+f"(d[3]), "+f"(d[4]), "+f"(d[5]), "+f"(d[6]), "+f"(d[7]), "+f"(d[8]), "+f"(d[9]), "+f"(d[10]), "+f"(d[11]), "+f"(d[12]), "+f"(d[13]), "+f"(d[14]), "+f"(d[15]) : "r"(a0), "r"(a1), "r"(a2), "r"(a3), "l"(db), "r"(sd));
}
__device__ __forceinline__ void wgmma_rs_160_1(float* d, uint32_t a0, uint32_t a1, uint32_t a2, uint32_t a3, uint64_t db, int sd) {
  asm volatile("{ .reg .pred p; setp.ne.b32 p, %85, 0; wgmma.mma_async.sync.aligned.m64n160k16.f32.bf16.bf16 {%0,%1,%2,%3,%4,%5,%6,%7,%8,%9,%10,%11,%12,%13,%14,%15,%16,%17,%18,%19,%20,%21,%22,%23,%24,%25,%26,%27,%28,%29,%30,%31,%32,%33,%34,%35,%36,%37,%38,%39,%40,%41,%42,%43,%44,%45,%46,%47,%48,%49,%50,%51,%52,%53,%54,%55,%56,%57,%58,%59,%60,%61,%62,%63,%64,%65,%66,%67,%68,%69,%70,%71,%72,%73,%74,%75,%76,%77,%78,%79}, {%80,%81,%82,%83}, %84, p, 1, 1, 1; }"
   : "+f"(d[0]), "+f"(d[1]), "+f"(d[2]), "+f"(d[3]), "+f"(d[4]), "+f"(d[5]), "+f"(d[6]), "+f"(d[7]), "+f"(d[8]), "+f"(d[9]), "+f"(d[10]), "+f"(d[11]), "+f"(d[12]), "+f"(d[13]), "+f"(d[14]), "+f"(d[15]), "+f"(d[16]), "+f"(d[17]), "+f"(d[18]), "+f"(d[19]), "+f"(d[20]), "+f"(d[21]), "+f"(d[22]), "+f"(d[23]), "+f"(d[24]), "+f"(d[25]), "+f"(d[26]), "+f"(d[27]), "+f"(d[28]), "+f"(d[29]), "+f"(d[30]), "+f"(d[31]), "+f"(d[32]), "+f"(d[33]), "+f"(d[34]), "+f"(d[35]), "+f"(d[36]), "+f"(d[37]), "+f"(d[38]), "+f"(d[39]), "+f"(d[40]), "+f"(d[41]), "+f"(d[42]), "+f"(d[43]), "+f"(d[44]), "+f"(d[45]), "+f"(d[46]), "+f"(d[47]), "+f"(d[48]), "+f"(d[49]), "+f"(d[50]), "+f"(d[51]), "+f"(d[52]), "+f"(d[53]), "+f"(d[54]), "+f"(d[55]), "+f"(d[56]), "+f"(d[57]), "+f"(d[58]), "+f"(d[59]), "+f"(d[60]), "+f"(d[61]), "+f"(d[62]), "+f"(d[63]), "+f"(d[64]), "+f"(d[65]), "+f"(d[66]), "+f"(d[67]), "+f"(d[68]), "+f"(d[69]), "+f"(d[70]), "+f"(d[71]), "+f"(d[72]), "+f"(d[73]), "+f"(d[74]), "+f"(d[75]), "+f"(d[76]), "+f"(d[77]), "+f"(d[78]), "+f"(d[79]) : "r"(a0), "r"(a1), "r"(a2), "r"(a3), "l"(db), "r"(sd));
}
__device__ __forceinline__ void wgmma_rs_192_1(float* d, uint32_t a0, uint32_t a1, uint32_t a2, uint32_t a3, uint64_t db, int sd) {
  asm volatile("{ .reg .pred p; setp.ne.b32 p, %101, 0; wgmma.mma_async.sync.aligned.m64n192k16.f32.bf16.bf16 {%0,%1,%2,%3,%4,%5,%6,%7,%8,%9,%10,%11,%12,%13,%14,%15,%16,%17,%18,%19,%20,%21,%22,%23,%24,%25,%26,%27,%28,%29,%30,%31,%32,%33,%34,%35,%36,%37,%38,%39,%40,%41,%42,%43,%44,%45,%46,%47,%48,%49,%50,%51,%52,%53,%54,%55,%56,%57,%58,%59,%60,%61,%62,%63,%64,%65,%66,%67,%68,%69,%70,%71,%72,%73,%74,%75,%76,%77,%78,%79,%80,%81,%82,%83,%84,%85,%86,%87,%88,%89,%90,%91,%92,%93,%94,%95}, {%96,%97,%98,%99}, %100, p, 1, 1, 1; }"
   : "+f"(d[0]), "+f"(d[1]), "+f"(d[2]), "+f"(d[3]), "+f"(d[4]), "+f"(d[5]), "+f"(d[6]), "+f"(d[7]), "+f"(d[8]), "+f"(d[9]), "+f"(d[10]), "+f"(d[11]), "+f"(d[12]), "+f"(d[13]), "+f"(d[14]), "+f"(d[15]), "+f"(d[16]), "+f"(d[17]), "+f"(d[18]), "+f"(d[19]), "+f"(d[20]), "+f"(d[21]), "+f"(d[22]), "+f"(d[23]), "+f"(d[24]), "+f"(d[25]), "+f"(d[26]), "+f"(d[27]), "+f"(d[28]), "+f"(d[29]), "+f"(d[30]), "+f"(d[31]), "+f"(d[32]), "+f"(d[33]), "+f"(d[34]), "+f"(d[35]), "+f"(d[36]), "+f"(d[37]), "+f"(d[38]), "+f"(d[39]), "+f"(d[40]), "+f"(d[41]), "+f"(d[42]), "+f"(d[43]), "+f"(d[44]), "+f"(d[45]), "+f"(d[46]), "+f"(d[47]), "+f"(d[48]), "+f"(d[49]), "+f"(d[50]), "+f"(d[51]), "+f"(d[52]), "+f"(d[53]), "+f"(d[54]), "+f"(d[55]), "+f"(d[56]), "+f"(d[57]), "+f"(d[58]), "+f"(d[59]), "+f"(d[60]), "+f"(d[61]), "+f"(d[62]), "+f"(d[63]), "+f"(d[64]), "+f"(d[65]), "+f"(d[66]), "+f"(d[67]), "+f"(d[68]), "+f"(d[69]), "+f"(d[70]), "+f"(d[71]), "+f"(d[72]), "+f"(d[73]), "+f"(d[74]), "+f"(d[75]), "+f"(d[76]), "+f"(d[77]), "+f"(d[78]), "+f"(d[79]), "+f"(d[80]), "+f"(d[81]), "+f"(d[82]), "+f"(d[83]), "+f"(d[84]), "+f"(d[85]), "+f"(d[86]), "+f"(d[87]), "+f"(d[88]), "+f"(d[89]), "+f"(d[90]), "+f"(d[91]), "+f"(d[92]), "+f"(d[93]), "+f"(d[94]), "+f"(d[95]) : "r"(a0), "r"(a1), "r"(a2), "r"(a3), "l"(db), "r"(sd));
}
__device__ __forceinline__ void wgmma_ss_8_10(float* d, uint64_t da, uint64_t db, int sd) {
  asm volatile("{ .reg .pred p; setp.ne.b32 p, %6, 0; wgmma.mma_async.sync.aligned.m64n8k16.f32.bf16.bf16 {%0,%1,%2,%3}, %4, %5, p, 1, 1, 1, 0; }"
   : "+f"(d[0]), "+f"(d[1]), "+f"(d[2]), "+f"(d[3]) : "l"(da), "l"(db), "r"(sd));
}
__device__ __forceinline__ void wgmma_ss_160_01(float* d, uint64_t da, uint64_t db, int sd) {
  asm volatile("{ .reg .pred p; setp.ne.b32 p, %82, 0; wgmma.mma_async.sync.aligned.m64n160k16.f32.bf16.bf16 {%0,%1,%2,%3,%4,%5,%6,%7,%8,%9,%10,%11,%12,%13,%14,%15,%16,%17,%18,%19,%20,%21,%22,%23,%24,%25,%26,%27,%28,%29,%30,%31,%32,%33,%34,%35,%36,%37,%38,%39,%40,%41,%42,%43,%44,%45,%46,%47,%48,%49,%50,%51,%52,%53,%54,%55,%56,%57,%58,%59,%60,%61,%62,%63,%64,%65,%66,%67,%68,%69,%70,%71,%72,%73,%74,%75,%76,%77,%78,%79}, %80, %81, p, 1, 1, 0, 1; }"
   : "+f"(d[0]), "+f"(d[1]), "+f"(d[2]), "+f"(d[3]), "+f"(d[4]), "+f"(d[5]), "+f"(d[6]), "+f"(d[7]), "+f"(d[8]), "+f"(d[9]), "+f"(d[10]), "+f"(d[11]), "+f"(d[12]), "+f"(d[13]), "+f"(d[14]), "+f"(d[15]), "+f"(d[16]), "+f"(d[17]), "+f"(d[18]), "+f"(d[19]), "+f"(d[20]), "+f"(d[21]), "+f"(d[22]), "+f"(d[23]), "+f"(d[24]), "+f"(d[25]), "+f"(d[26]), "+f"(d[27]), "+f"(d[28]), "+f"(d[29]), "+f"(d[30]), "+f"(d[31]), "+f"(d[32]), "+f"(d[33]), "+f"(d[34]), "+f"(d[35]), "+f"(d[36]), "+f"(d[37]), "+f"(d[38]), "+f"(d[39]), "+f"(d[40]), "+f"(d[41]), "+f"(d[42]), "+f"(d[43]), "+f"(d[44]), "+f"(d[45]), "+f"(d[46]), "+f"(d[47]), "+f"(d[48]), "+f"(d[49]), "+f"(d[50]), "+f"(d[51]), "+f"(d[52]), "+f"(d[53]), "+f"(d[54]), "+f"(d[55]), "+f"(d[56]), "+f"(d[57]), "+f"(d[58]), "+f"(d[59]), "+f"(d[60]), "+f"(d[61]), "+f"(d[62]), "+f"(d[63]), "+f"(d[64]), "+f"(d[65]), "+f"(d[66]), "+f"(d[67]), "+f"(d[68]), "+f"(d[69]), "+f"(d[70]), "+f"(d[71]), "+f"(d[72]), "+f"(d[73]), "+f"(d[74]), "+f"(d[75]), "+f"(d[76]), "+f"(d[77]), "+f"(d[78]), "+f"(d[79]) : "l"(da), "l"(db), "r"(sd));
}
__device__ __forceinline__ void wgmma_ss_192_11(float* d, uint64_t da, uint64_t db, int sd) {
  asm volatile("{ .reg .pred p; setp.ne.b32 p, %98, 0; wgmma.mma_async.sync.aligned.m64n192k16.f32.bf16.bf16 {%0,%1,%2,%3,%4,%5,%6,%7,%8,%9,%10,%11,%12,%13,%14,%15,%16,%17,%18,%19,%20,%21,%22,%23,%24,%25,%26,%27,%28,%29,%30,%31,%32,%33,%34,%35,%36,%37,%38,%39,%40,%41,%42,%43,%44,%45,%46,%47,%48,%49,%50,%51,%52,%53,%54,%55,%56,%57,%58,%59,%60,%61,%62,%63,%64,%65,%66,%67,%68,%69,%70,%71,%72,%73,%74,%75,%76,%77,%78,%79,%80,%81,%82,%83,%84,%85,%86,%87,%88,%89,%90,%91,%92,%93,%94,%95}, %96, %97, p, 1, 1, 1, 1; }"
   : "+f"(d[0]), "+f"(d[1]), "+f"(d[2]), "+f"(d[3]), "+f"(d[4]), "+f"(d[5]), "+f"(d[6]), "+f"(d[7]), "+f"(d[8]), "+f"(d[9]), "+f"(d[10]), "+f"(d[11]), "+f"(d[12]), "+f"(d[13]), "+f"(d[14]), "+f"(d[15]), "+f"(d[16]), "+f"(d[17]), "+f"(d[18]), "+f"(d[19]), "+f"(d[20]), "+f"(d[21]), "+f"(d[22]), "+f"(d[23]), "+f"(d[24]), "+f"(d[25]), "+f"(d[26]), "+f"(d[27]), "+f"(d[28]), "+f"(d[29]), "+f"(d[30]), "+f"(d[31]), "+f"(d[32]), "+f"(d[33]), "+f"(d[34]), "+f"(d[35]), "+f"(d[36]), "+f"(d[37]), "+f"(d[38]), "+f"(d[39]), "+f"(d[40]), "+f"(d[41]), "+f"(d[42]), "+f"(d[43]), "+f"(d[44]), "+f"(d[45]), "+f"(d[46]), "+f"(d[47]), "+f"(d[48]), "+f"(d[49]), "+f"(d[50]), "+f"(d[51]), "+f"(d[52]), "+f"(d[53]), "+f"(d[54]), "+f"(d[55]), "+f"(d[56]), "+f"(d[57]), "+f"(d[58]), "+f"(d[59]), "+f"(d[60]), "+f"(d[61]), "+f"(d[62]), "+f"(d[63]), "+f"(d[64]), "+f"(d[65]), "+f"(d[66]), "+f"(d[67]), "+f"(d[68]), "+f"(d[69]), "+f"(d[70]), "+f"(d[71]), "+f"(d[72]), "+f"(d[73]), "+f"(d[74]), "+f"(d[75]), "+f"(d[76]), "+f"(d[77]), "+f"(d[78]), "+f"(d[79]), "+f"(d[80]), "+f"(d[81]), "+f"(d[82]), "+f"(d[83]), "+f"(d[84]), "+f"(d[85]), "+f"(d[86]), "+f"(d[87]), "+f"(d[88]), "+f"(d[89]), "+f"(d[90]), "+f"(d[91]), "+f"(d[92]), "+f"(d[93]), "+f"(d[94]), "+f"(d[95]) : "l"(da), "l"(db), "r"(sd));
}

__device__ __forceinline__ void gemv_tile(uint32_t a0, uint32_t a1, uint32_t silu, uint32_t* dst, uint32_t tag, int lane) {
  float d[4];
  const uint64_t db = mkdesc(silu, 16, 128, 0), da0 = mkdesc(a0, 4096, 1024, 1), da1 = mkdesc(a1, 4096, 1024, 1);
  wg_fence();
#pragma unroll
  for (int kk = 0; kk < 8; kk++) wgmma_ss_8_10(d, (kk < 4 ? da0 : da1) + (kk & 3) * 128, db + kk * 2, kk);
  wg_commit();
  wg_wait<0>();
  regfence<4>(d);
  if (!(lane & 3)) { str(dst, tagf(d[0], tag)); str(dst + 8, tagf(d[2], tag)); }
}

__global__ void __cluster_dims__(2, 1, 1) __launch_bounds__(384, 1) fused_kernel(const __grid_constant__ Params p) {
  extern __shared__ __align__(1024) uint8_t smem_raw[];
  const uint32_t t_start = clk();
  const uint32_t sb = smem_u32(smem_raw);
  const uint32_t bars = sb + O_BAR;
  const int tid = threadIdx.x, lane = tid & 31;
  const int warp = __shfl_sync(0xffffffffu, tid >> 5, 0);
  const int b = blockIdx.x;
  const int rb = b >> 3, cg = (b >> 1) & 3, kh = b & 1, fs = kh * 4 + cg;
  const int tb = b >> 2, cb = b & 3;
  const int vr = min(rb, 14) / 3, vt = min(rb, 14) % 3;
  auto BAR = [&](int i) { return bars + 8 * i; };
  if (tid == 0) TSTAMP(63);

  uint32_t dv = 0;
  if (warp >= 2) {
    const int th = warp >= 7, g = (warp - 2 - 5 * th) * 8 + (lane & 7), run = th * 4 + (lane >> 3);
    const int ch = cb * 160 + g * 4, t0 = tb * 64 + run * 8;
    uint2 kk[11], vv[8];
    const __nv_bfloat16* kp = p.k + (size_t)t0 * D_ + ch;
    const __nv_bfloat16* vp = p.v + (size_t)t0 * D_ + ch;
#pragma unroll
    for (int i = 0; i < 8; i++) asm volatile("ld.global.nc.L1::no_allocate.v2.u32 {%0,%1}, [%2];" : "=r"(kk[i + 3].x), "=r"(kk[i + 3].y) : "l"(kp + i * D_));
#pragma unroll
    for (int i = 0; i < 8; i++) asm volatile("ld.global.nc.L1::no_allocate.v2.u32 {%0,%1}, [%2];" : "=r"(vv[i].x), "=r"(vv[i].y) : "l"(vp + i * D_));
    const __nv_bfloat16* kh_ = t0 ? kp - 3 * D_ : kp;
#pragma unroll
    for (int i = 0; i < 3; i++) asm volatile("ld.global.nc.L1::no_allocate.v2.u32 {%0,%1}, [%2];" : "=r"(kk[i].x), "=r"(kk[i].y) : "l"(kh_ + i * D_));
    uint4 s0 = __ldg((const uint4*)(p.shift + ch * 4)), s1 = __ldg((const uint4*)(p.shift + ch * 4 + 8));
    if (warp == 2 && lane < 5) dv = __ldg((const uint16_t*)p.ssmD + lane * 128 + b);
    if (t0 == 0) { kk[0] = kk[1] = kk[2] = make_uint2(0, 0); }
    uint32_t wx[4], wy[4];
    wx[0] = prmt(s0.x, s0.z, 0x5410); wx[1] = prmt(s0.x, s0.z, 0x7632); wx[2] = prmt(s0.y, s0.w, 0x5410); wx[3] = prmt(s0.y, s0.w, 0x7632);
    wy[0] = prmt(s1.x, s1.z, 0x5410); wy[1] = prmt(s1.x, s1.z, 0x7632); wy[2] = prmt(s1.y, s1.w, 0x5410); wy[3] = prmt(s1.y, s1.w, 0x7632);
    uint32_t rx[8], ry[8];
#pragma unroll
    for (int i = 0; i < 8; i++) {
      uint32_t ax = hmul2(kk[i].x, wx[3]), ay = hmul2(kk[i].y, wy[3]);
      ax = hfma2(kk[i + 1].x, wx[2], ax); ay = hfma2(kk[i + 1].y, wy[2], ay);
      ax = hfma2(kk[i + 2].x, wx[1], ax); ay = hfma2(kk[i + 2].y, wy[1], ay);
      ax = hfma2(kk[i + 3].x, wx[0], ax); ay = hfma2(kk[i + 3].y, wy[0], ay);
      rx[7 - i] = hmul2(ax, vv[i].x); ry[7 - i] = hmul2(ay, vv[i].y);
    }
    const uint32_t op = sb + O_KSTG + g * 128 + (((7 - run) ^ (lane & 7)) << 4);
    sts128(op, prmt(rx[0], rx[1], 0x5410), prmt(rx[2], rx[3], 0x5410), prmt(rx[4], rx[5], 0x5410), prmt(rx[6], rx[7], 0x5410));
    sts128(op + 5120, prmt(rx[0], rx[1], 0x7632), prmt(rx[2], rx[3], 0x7632), prmt(rx[4], rx[5], 0x7632), prmt(rx[6], rx[7], 0x7632));
    sts128(op + 10240, prmt(ry[0], ry[1], 0x5410), prmt(ry[2], ry[3], 0x5410), prmt(ry[4], ry[5], 0x5410), prmt(ry[6], ry[7], 0x5410));
    sts128(op + 15360, prmt(ry[0], ry[1], 0x7632), prmt(ry[2], ry[3], 0x7632), prmt(ry[4], ry[5], 0x7632), prmt(ry[6], ry[7], 0x7632));
    fence_async_smem();
    bar_sync(1, 384);
  } else if (warp == 0) {
    if (lane == 0) {
#pragma unroll
      for (int x = 0; x < B_NUM; x++) mbar_init(BAR(x), x < B_Y ? 2 : x < B_VVS ? 4 : x == B_VVS ? 8 : 1);
      mbar_expect(BAR(B_RED), 40960);
      TSTAMP(62);
    }
    __syncwarp();
    asm volatile("fence.mbarrier_init.release.cluster;" ::: "memory");
    bar_arrive(7, 64);
    if (lane < 2) {
      while (clk() - t_start < T_SSM) {}
      mbar_expect(BAR(B_SSM + lane), 4096);
      bulk_ld(sb + bslot(lane) + U_RAW, p.ssm + (size_t)(lane * 128 + b) * S_, 4096, BAR(B_SSM + lane));
    }
    __syncwarp();
    bar_sync(1, 384);
  } else {
    const uint2 cv = __ldg((const uint2*)p.c + (b % 5) * 32 + lane);
    if (lane < 7) {
      const uint32_t n = lane == 0 ? 32 : lane < 3 ? 128 : lane == 3 ? 256 : lane == 4 ? 16 : 1;
      const uint32_t v = ldr(g_sync + (lane == 0 ? cb : lane < 4 ? lane * 32 : lane == 4 ? (4 + fs) * 32 : 12 * 32 + (rb * 4 + kh * 2 + lane - 5) * 8 + cg));
      sts32(sb + O_EP + lane * 4, (v & -n) + n);
    }
#pragma unroll
    for (int j = 0; j < 5; j++) {
      if (lane < 19) sts128(sb + bslot(j) + (lane < 17 ? U_KV + 4096 + lane * 16 : lane == 17 ? U_RAW - 16 : U_ODD - 16), 0, 0, 0, 0);
    }
    if (lane < 8) sts128(sb + O_BP + 7680 + lane * 16, 0, 0, 0, 0);
    const float x = blo(cv.x), y = bhi(cv.x), z = blo(cv.y), u = bhi(cv.y);
    sts64(sb + O_SILU + lane * 8, pack2(__fdividef(x, 1.f + __expf(-x)), __fdividef(y, 1.f + __expf(-y))), pack2(__fdividef(z, 1.f + __expf(-z)), __fdividef(u, 1.f + __expf(-u))));
    fence_async_smem();
    bar_sync(7, 64);
    bar_arrive(1, 384);
  }
  asm volatile("barrier.cluster.arrive.relaxed.aligned;" ::: "memory");

  if (warp < 4) {
    asm volatile("setmaxnreg.dec.sync.aligned.u32 40;");
    const int hw = warp - 2;
    const uint32_t tag = lds32(sb + O_EP + 20) & 3;
    const int mu = b / 5, mk = (b % 5) * 128;
    auto wmcol = [&](int pc) { return pc == 2 && mu >= 10 ? 2560 + mu * 64 : ((mu % 10) >> 1) * D_ + (2 * pc + (mu >= 10)) * 128 + (mu & 1) * 64; };
    auto EP = [&](int i) { return lds32(sb + O_EP + 4 * i); };
    auto loadS = [&](int j) { mbar_expect(BAR(B_SSM + j), 4096); bulk_ld(sb + bslot(j) + U_RAW, p.ssm + (size_t)(j * 128 + b) * S_, 4096, BAR(B_SSM + j)); };
    auto loadQ = [&](int j) { mbar_expect(BAR(B_QF + j), 8192); bulk_ld(sb + bslot(j), g_qT + (size_t)(j * 128 + b) * S_ * 2, 8192, BAR(B_QF + j)); };
    auto loadW = [&](int slot, int k0) {
      mbar_expect(BAR(B_FULL + slot), SLOT);
      tma3d(sb + slot * SLOT, &p.m_wg, 0, k0, fs * 3, BAR(B_FULL + slot));
      tma3d(sb + slot * SLOT + 12288, &p.m_wu, 0, k0, fs * 3, BAR(B_FULL + slot));
    };
    auto loadA = [&](int slot, int k0) { tma3d(sb + slot * SLOT + 24576, &p.m_xa, 0, k0, (rb >> 3) * 32 + 16 + (rb & 7) * 2, BAR(B_FULL + slot)); };
    uint32_t tpf = T_PF;
    auto prefetch = [&](int i0, int i1) {
#pragma unroll 1
      for (int i = i0; i < i1; i++) {
        while (clk() - t_start < tpf) {}
        if (i == 6 || i == 7 || (i >= 10 && i < 14)) {
          if (b < 100)
            asm volatile("cp.async.bulk.prefetch.tensor.2d.L2.global [%0, {%1, %2}];" ::"l"(&p.m_wm), "r"(wmcol(i < 8 ? 0 : (i >> 1) - 4)), "r"(mk + (i & 1) * 64) : "memory");
          tpf += 6400 / PF_RATE;
        } else {
          const __nv_bfloat16* a;
          uint32_t n = 4096;
          if (i < 5) a = p.q + (b * 5 + i) * 2048;
          else if (i < 10) a = p.ssm + (size_t)((i == 5 ? 2 : i - 5) * 128 + b) * S_;
          else if (i < 24) { a = ((b & 1) ? p.wu : p.wg) + ((i - 14) * 64 + (b >> 1)) * F_; n = 3072; }
          else { a = p.w2 + (b * 4 + i - 24) * 1920; n = 3840; }
          bulk_pf(a, n);
          tpf += n / PF_RATE;
        }
      }
    };
    auto build = [&](int j) {
      const uint32_t ra = sb + bslot(j) + U_RAW + hw * 2048 + lane * 16;
      const float dj = blo(__shfl_sync(0xffffffffu, dv, j));
      mbar_wait(BAR(B_SSM + j), 0);
#pragma unroll
      for (int i = 0; i < 4; i++) {
        uint4 w = lds128(ra + i * 512);
        const uint32_t pv = lds32(ra + i * 512 - 4);
        if (i == 0 && tid == 64) { w.x = prmt(pack2(blo(w.x) + dj, 0.f), w.x, 0x7610); sts32(ra, w.x); }
        sts128(ra + (U_ODD - U_RAW) + i * 512, prmt(pv, w.x, 0x5432), prmt(w.x, w.y, 0x5432), prmt(w.y, w.z, 0x5432), prmt(w.z, w.w, 0x5432));
      }
      __syncwarp();
      if (lane == 0) mbar_arrive(BAR(B_PL + j));
      if (tid == 64 && !(j & 1)) TSTAMP(32 + (j >> 1));
    };
    auto gather = [&](int pc) {
      if (lane == 0) poll_ge(g_sync + 2 * 32 + pc, EP(2));
      __syncwarp();
      const int j = min(2 * pc + (lane >> 2), 1 + 3 * pc), sg = lane & 3;
      const float x = rbf(gather1(g_mod + (sg + (sg == 3)) * D_ + j * 128 + b, tag));
      const float ga = __shfl_sync(0xffffffffu, x, (lane & 28) + 2);
      const float y = sg == 0 ? ga * x : sg == 1 ? ga * rbf(1.f + x) : 1.f + x;
      if (sg != 2) sts32(sb + O_MV + j * 16 + (sg == 3 ? 8 : (sg ^ 1) * 4), pack2(y, y));
      __syncwarp();
      if (lane == 0) { mbar_arrive(BAR(B_MOD + pc)); TSTAMP(7 + pc); }
      if ((vr >= 2) == pc) {
        float4 s = gather4<5>(g_mod + 4 * D_ + vr * 128 + lane * 4, 6 * D_, tag);
        const uint32_t a = sb + O_CS + (lane >> 1) * 32 + (lane & 1) * 8;
        sts64(a, pack2(1.f + rbf(s.x), 1.f + rbf(s.y)), pack2(1.f + rbf(s.z), 1.f + rbf(s.w)));
        s = gather4<5>(g_mod + 3 * D_ + vr * 128 + lane * 4, 6 * D_, tag);
        sts64(a + 16, pack2(s.x, s.y), pack2(s.z, s.w));
        fence_async_smem();
        __syncwarp();
        if (lane == 0) { mbar_arrive(BAR(B_CS)); TSTAMP(11); }
      }
    };
    auto storeX = [&](int j) {
      bulk_st(g_x1T + (size_t)(j * 128 + b) * S_ * 2 + hw * 2048, sb + bslot(j) + U_PART + hw * 8192, 4096);
      bulk_commit();
    };

    if (warp == 0) {
      if (lane == 0) {
        TSTAMP(0);
        tma3d_store(&p.m_kvT, sb + O_KSTG, S_ - 64 - tb * 64, cb * 40, 0);
        bulk_commit(); bulk_wait<0>();
        signal_add(g_sync + cb);
        TSTAMP(1);
        mbar_expect(BAR(B_QIN), 20480);
        tma3d(sb + O_REG, &p.m_q, 0, b * 16, 0, BAR(B_QIN));
        const uint32_t tg = EP(0);
        uint32_t m = 0;
#pragma unroll 1
        for (int j = 0; j < 5; j++) {
          const int d = j * 128 + b;
          const uint32_t need = 1u << (d / 160);
          if (!(m & need)) m = poll4(g_sync, tg, need);
          if (j == 0) TSTAMP(2);
          mbar_expect(BAR(B_KV + j), 4096);
          bulk_ld(sb + bslot(j) + U_KV, g_kvT + (size_t)d * S_, 4096, BAR(B_KV + j));
        }
        loadS(2);
        if (b < 100) {
          mbar_expect(BAR(B_WM), 16384);
          tma2d(sb + bslot(3) + U_PART, &p.m_wm, wmcol(0), mk, BAR(B_WM));
          tma2d(sb + bslot(4) + U_PART, &p.m_wm, wmcol(0), mk + 64, BAR(B_WM));
        }
        mbar_wait(BAR(B_QST), 0);
#pragma unroll 1
        for (int j = 0; j < 5; j++) { tma2d_store(&p.m_qT, sb + bslot(j), b * 32, j * 128); if (j == 0) bulk_commit(); }
        bulk_commit();
        loadS(3); loadS(4);
      }
    } else if (warp == 1) {
      if (lane == 0) prefetch(0, PF_A);
    } else {
#pragma unroll 1
      for (int j = 0; j < 3; j++) build(j);
    }
    __syncwarp();
    uint32_t* const mdst = g_mod + (b % 5) * 6 * D_ + warp * 16 + (lane >> 2);
    if (b < 100) {
      mbar_wait(BAR(B_WM), 0);
      if (tid == 64) TSTAMP(53);
      gemv_tile(sb + bslot(3) + U_PART, sb + bslot(4) + U_PART, sb + O_SILU, mdst + wmcol(0), tag, lane);
    }
    if (tid == 96) { hint_add(g_sync + 2 * 32); TSTAMP(5); }
    if (warp == 0) {
      if (lane == 0) {
        bulk_wait<1>();
        signal_add(g_sync + 32);
        TSTAMP(10);
        bulk_wait<0>();
        signal_add(g_sync + 33);
        const uint32_t tg = EP(1);
        poll_ge(g_sync + 32, tg);
        TSTAMP(3);
        loadQ(0);
        poll_ge(g_sync + 33, tg);
        loadQ(1);
        if (b < 100) {
          mbar_expect(BAR(B_WM + 1), 32768);
#pragma unroll 1
          for (int i = 0; i < 4; i++) tma2d(sb + O_KSTG + i * 8192, &p.m_wm, wmcol(1 + (i >> 1)), mk + (i & 1) * 64, BAR(B_WM + 1));
        }
        loadQ(2); loadQ(3); loadQ(4);
        mbar_wait(BAR(B_EMPTY), 0);
        loadW(0, 0);
      }
    } else if (warp == 1) {
      gather(0);
      if (lane == 0) prefetch(PF_A, PF_B);
    } else {
      build(3); build(4);
      mbar_wait(BAR(B_MOD), 0);
      const uint4 mv = lds128(sb + O_MV);
      mbar_wait(BAR(B_QF), 0);
      if (tid == 64) TSTAMP(56);
      mbar_wait(BAR(B_Y), 0);
      part2<4>(sb, hw, 0, lane, mv);
      fence_async_smem();
      __syncwarp();
      if (lane == 0) { storeX(0); bulk_wait0_read(); mbar_arrive(BAR(B_EMPTY)); }
      if (tid == 64) TSTAMP(57);
    }
    __syncwarp();
    if (b < 100) {
      mbar_wait(BAR(B_WM + 1), 0);
      if (tid == 64) TSTAMP(54);
#pragma unroll 1
      for (int i = 0; i < 2; i++) gemv_tile(sb + O_KSTG + i * 16384, sb + O_KSTG + i * 16384 + 8192, sb + O_SILU, mdst + wmcol(1 + i), tag, lane);
    }
    if (tid == 96) { hint_add(g_sync + 2 * 32 + 1); TSTAMP(6); }
    if (warp == 0) {
      if (lane == 0) {
        loadW(1, 32);
        const uint32_t tg = EP(3);
        poll_ge(g_sync + 3 * 32 + 4, tg);
        TSTAMP(4);
        loadA(0, 0); loadA(1, 32);
        const uint32_t ord = vr == 3 ? 0x42310 : vr == 4 ? 0x32410 : 0x43210;
        uint32_t m = 0;
        int slot = 2, ph = 0;
#pragma unroll 1
        for (int s = 2; s < 20; s++) {
          const int rd = (ord >> (s & 28)) & 7, k0 = rd * 128 + (s & 3) * 32;
          const uint32_t need = (1u << rd) >> 1;
          if ((m & need) != need) m = poll4(g_sync + 3 * 32, tg, need);
          mbar_wait(BAR(B_EMPTY + slot), ph);
          loadW(slot, k0);
          loadA(slot, k0);
          if (++slot == 6) { slot = 0; ph ^= 1; }
        }
#pragma unroll 1
        for (int s = 0; s < 12; s++) {
          if (s == 0) { mbar_wait(BAR(B_EMPTY + 2), 1); }
          else if (s == 1) { mbar_wait(BAR(B_EMPTY + 3), 1); }
          else if (s == 3) { mbar_wait(BAR(B_EMPTY + 0), 0); }
          else if (s == 4) { mbar_wait(BAR(B_EMPTY + 1), 0); }
          else if (s >= 6) { mbar_wait(BAR(B_W2E + s - 6), 0); }
          const int e = s % 6;
          mbar_expect(BAR(B_W2F + e), 20480);
          tma3d(sb + w2entry(e), &p.m_w2, 0, kh * 768 + ((cg + s / 3) & 3) * 192 + (s % 3) * 64, cg * 5, BAR(B_W2F + e));
        }
        mbar_wait(BAR(B_W2E + 0), 1);
        mbar_wait(BAR(B_W2E + 1), 1);
      }
      __syncwarp();
      asm volatile("barrier.cluster.wait.aligned;" ::: "memory");
      if (lane == 0)
        asm volatile("{ .reg .b32 r; mapa.shared::cluster.u32 r, %0, %1; mbarrier.arrive.shared::cluster.b64 _, [r]; }" ::"r"(BAR(B_RDY)), "r"(kh ^ 1) : "memory");
    } else if (warp == 1) {
      if (lane == 0) { prefetch(PF_B, 28); TSTAMP(35); }
      gather(1);
#pragma unroll 1
      for (int i = 0; i < 2; i++) {
        if (i == 0 || lane < 8) {
          const float4 s = gather4<5>(g_mod + 5 * D_ + cg * 160 + i * 128 + lane * 4, 6 * D_, tag);
          sts128(sb + O_GB + i * 512 + lane * 16, __float_as_uint(rbf(s.x)), __float_as_uint(rbf(s.y)), __float_as_uint(rbf(s.z)), __float_as_uint(rbf(s.w)));
        }
      }
      __syncwarp();
      if (lane == 0) {
        poll4(g_sync + 3 * 32, EP(3), 15);
        mbar_expect(BAR(B_X1), 20480);
        tma2d(sb + O_REG, &p.m_xr, (rb >> 3) * 2048 + (rb & 7) * 128 + (kh ^ 1) * 64, cg * 160, BAR(B_X1));
        mbar_wait(BAR(B_VVS), 0);
        TSTAMP(36);
        bulk_st(g_vv + ((fs * 5 + vr) * 48 + vt * 16) * 16, sb + O_TMP + 512, 512);
        bulk_commit(); bulk_wait<0>();
        signal_add(g_sync + (4 + fs) * 32);
        poll_ge(g_sync + (4 + fs) * 32, EP(4));
        mbar_expect(BAR(B_VV), 7680);
        tma3d(sb + O_BP, &p.m_vv, 0, fs * 5, 0, BAR(B_VV));
        TSTAMP(37);
      }
      __syncwarp();
      asm volatile("barrier.cluster.wait.aligned;" ::: "memory");
    } else {
      if (lane == 0) { bulk_wait<0>(); signal_add(g_sync + 3 * 32 + 4); mbar_arrive(BAR(B_EMPTY + 1)); }
      if (tid == 64) TSTAMP(12);
#pragma unroll 1
      for (int j = 1; j < 5; j++) {
        if (j < 3) {
          mbar_wait(BAR(B_MOD + j - 1), 0);
          const uint4 mv = lds128(sb + O_MV + j * 16);
          mbar_wait(BAR(B_QF + j), 0);
          mbar_wait(BAR(B_Y + j), 0);
          part2<4>(sb + bslot(j), hw, 0, lane, mv);
          fence_async_smem();
          __syncwarp();
          if (tid == 64 && j == 1) TSTAMP(60 + j);
        }
        if (lane == 0) {
          if (j >= 3) mbar_wait(BAR(B_Y + j), 0);
          storeX(j);
          if (j > 1) { bulk_wait<1>(); signal_add(g_sync + 3 * 32 + j - 2); if (hw == 0) TSTAMP(11 + j); }
          bulk_wait0_read();
          mbar_arrive(BAR(B_EMPTY + j + 1));
        }
        __syncwarp();
      }
      if (lane == 0) { bulk_wait<0>(); signal_add(g_sync + 3 * 32 + 3); }
      if (tid == 64) TSTAMP(16);
      {
        float s1a = 0.f, s2a = 0.f, s1b = 0.f, s2b = 0.f;
        mbar_wait(BAR(B_X1), 0);
        if (tid == 64) TSTAMP(58);
#pragma unroll 1
        for (int k = 0; k < 8; k++) {
          const uint32_t a = ((sb + O_REG + hw * 10240 + lane * 4) ^ (k << 4)) + k * 128;
          uint32_t v[10];
#pragma unroll
          for (int i = 0; i < 10; i++) v[i] = lds32(a + i * 1024);
#pragma unroll
          for (int i = 0; i < 10; i++) { const float x = blo(v[i]), y = bhi(v[i]); s1a += x; s2a = fmaf(x, x, s2a); s1b += y; s2b = fmaf(y, y, s2b); }
        }
        if (hw) sts128(sb + O_TMP + lane * 16, __float_as_uint(s1a), __float_as_uint(s2a), __float_as_uint(s1b), __float_as_uint(s2b));
        bar_sync(4, 64);
        if (!hw) {
          const float4 o = lds128f(sb + O_TMP + lane * 16);
          asm volatile("st.relaxed.gpu.global.v4.u32 [%0], {%1,%2,%3,%4};" ::"l"(g_st + ((rb * 2 + (kh ^ 1)) * 4 + cg) * 128 + lane * 4), "r"(tagf(s1a + o.x, tag)),
                       "r"(tagf(s2a + o.y, tag)), "r"(tagf(s1b + o.z, tag)), "r"(tagf(s2b + o.w, tag)) : "memory");
        }
        const float4 s = gather4<4>(g_st + (rb * 2 + hw) * 512 + lane * 4, 128, tag);
        const float ma = s.x * (1.f / D_), mb = s.z * (1.f / D_);
        const uint32_t pa = pack2(-ma, sqrtf(fmaxf(s.y * (1.f / D_) - ma * ma, 0.f) + 1e-5f)), pb = pack2(-mb, sqrtf(fmaxf(s.w * (1.f / D_) - mb * mb, 0.f) + 1e-5f));
        sts128(sb + O_ST + hw * 512 + lane * 16, pa, __float_as_uint(__fdividef(1.f, bhi(pa) * bhi(pa))), pb, __float_as_uint(__fdividef(1.f, bhi(pb) * bhi(pb))));
        __syncwarp();
        if (lane == 0) mbar_arrive(BAR(B_ST + hw));
        if (tid == 64) TSTAMP(52);
      }
      if (lane == 0) {
        const uint32_t reg = sb + (5 - hw) * SLOT, e1 = EP(5 + hw);
        const int row0 = rb * 128 + (hw ^ kh) * 64;
        uint32_t* flags = g_sync + 12 * 32 + (rb * 4 + kh * 2 + hw) * 8;
        mbar_wait(BAR(B_STAGED + hw), 0);
#pragma unroll 1
        for (int i = 0; i < 3; i++) tma2d_store(&p.m_h, reg + i * 8192, fs * 192 + i * 64, row0);
        bulk_commit(); bulk_wait<0>();
        fence_gpu();
        str(flags + cg, e1);
        TSTAMP(17 + hw);
        uint32_t m = 0;
#pragma unroll 1
        for (int i = 0; i < 9; i++) {
          const int oc = (cg + 1 + i / 3) & 3;
          if (!(m & (1u << oc))) m = poll4(flags, e1, 1u << oc);
          if (i >= 4) mbar_wait(BAR(B_HE + hw * 4 + (i & 3)), ((i >> 2) - 1) & 1);
          mbar_expect(BAR(B_HF + hw * 4 + (i & 3)), 8192);
          tma2d(reg + (i & 3) * 8192, &p.m_h, kh * 768 + oc * 192 + (i % 3) * 64, row0, BAR(B_HF + hw * 4 + (i & 3)));
        }
      }
      __syncwarp();
      asm volatile("barrier.cluster.wait.aligned;" ::: "memory");
    }
  } else {
    asm volatile("setmaxnreg.inc.sync.aligned.u32 232;");
    const int isE = warp >= 8 ? 1 : 0;
    const int w = warp & 3, r = lane >> 2, c = lane & 3;
    if (isE) bar_arrive(2, 256);
    {
      const uint32_t aoff = ((r & 1) ? U_RAW : U_ODD) + 4 * (8 * w + (r >> 1) - 3 + c);
      const uint32_t yoff = U_PART + w * 2048 + (127 + 2 * w - lane) * 16;
      const uint32_t yoff0 = yoff + (lane < 2 * w ? -2048 : 8192), yoff4 = yoff + (lane < 2 * w ? 6144 : 0);
      uint32_t A[64];
      mbar_wait(BAR(B_PL + isE), 0);
      {
        const uint32_t sa = sb + isE * 2 * SLOT + aoff;
#pragma unroll
        for (int g = 0; g < 16; g++) { A[4 * g] = lds32(sa + g * 256); A[4 * g + 1] = lds32(sa + g * 256 + 128); A[4 * g + 2] = lds32(sa + g * 256 + 16); A[4 * g + 3] = lds32(sa + g * 256 + 144); }
      }
      if (lane == 0 && w == 0) TSTAMP(59 + isE);
      if (isE) {
        uint32_t x[40];
        mbar_wait(BAR(B_QIN), 0);
        if (tid == 256) TSTAMP(9);
        const uint32_t qa = sb + O_REG + (lane & 15) * 128 + (((2 * w + (lane >> 4)) ^ (lane & 7)) << 4);
        float s1a = 0.f, s2a = 0.f, s1b = 0.f, s2b = 0.f;
#pragma unroll
        for (int i = 0; i < 10; i++) ldsm4(qa + i * 2048, x[4 * i], x[4 * i + 1], x[4 * i + 2], x[4 * i + 3]);
#pragma unroll
        for (int i = 0; i < 20; i++) {
          float f;
          f = blo(x[2 * i]); s1a += f; s2a = fmaf(f, f, s2a); f = bhi(x[2 * i]); s1a += f; s2a = fmaf(f, f, s2a);
          f = blo(x[2 * i + 1]); s1b += f; s2b = fmaf(f, f, s2b); f = bhi(x[2 * i + 1]); s1b += f; s2b = fmaf(f, f, s2b);
        }
        float z[4] = {s1a, s2a, s1b, s2b};
        halve<4>(z, lane, 2); halve<2>(z, lane, 1);
        sts32(sb + O_TMP + w * 128 + lane * 4, __float_as_uint(z[0]));
        bar_sync(6, 128);
        float4 t = lds128f(sb + O_TMP + r * 16);
#pragma unroll
        for (int i = 1; i < 4; i++) { const float4 u = lds128f(sb + O_TMP + i * 128 + r * 16); t.x += u.x; t.y += u.y; t.z += u.z; t.w += u.w; }
        const float ma = t.x * (1.f / D_), mb = t.z * (1.f / D_);
        const float ra = rsqrtf(fmaxf(t.y * (1.f / D_) - ma * ma, 0.f) + 1e-5f), rb_ = rsqrtf(fmaxf(t.w * (1.f / D_) - mb * mb, 0.f) + 1e-5f);
        const float oa = -ma * ra, ob = -mb * rb_;
        const uint32_t so = sb + (16 * w + (lane & 7)) * 64 + (((lane >> 3) ^ (b & 2) ^ ((lane & 7) >> 1)) << 4);
#pragma unroll
        for (int i = 0; i < 20; i++)
          stsm4t(so + bslot(i >> 2) + (i & 2) * 2048 + (i & 1) * 512, x[2 * i], x[2 * i + 1], pack2(fmaf(blo(x[2 * i]), ra, oa), fmaf(bhi(x[2 * i]), ra, oa)),
                 pack2(fmaf(blo(x[2 * i + 1]), rb_, ob), fmaf(bhi(x[2 * i + 1]), rb_, ob)));
        fence_async_smem();
        __syncwarp();
        if (lane == 0) mbar_arrive(BAR(B_QST));
        if (tid == 256) TSTAMP(55);
      }
#pragma unroll 1
      for (int j = isE; j < 5; j += 2) {
        const uint32_t ub = sb + bslot(j);
        float d[128];
        mbar_wait(BAR(B_KV + j), 0);
        bar_sync(2 + isE, 256);
        if (j == 0 && tid == 128) TSTAMP(19);
        const uint64_t db = mkdesc(ub + U_KV, 16, 128, 0);
        wg_fence();
        wgmma_rs_32_0(d + 0, A[0], A[1], A[2], A[3], db + 0, 0);
        wgmma_rs_32_0(d + 16, A[0], A[1], A[2], A[3], db + 32, 0);
        wgmma_rs_32_0(d + 32, A[0], A[1], A[2], A[3], db + 64, 0);
        wgmma_rs_32_0(d + 48, A[0], A[1], A[2], A[3], db + 96, 0);
        wgmma_rs_32_0(d + 0, A[4], A[5], A[6], A[7], db + 16, 1);
        wgmma_rs_32_0(d + 16, A[4], A[5], A[6], A[7], db + 48, 1);
        wgmma_rs_32_0(d + 32, A[4], A[5], A[6], A[7], db + 80, 1);
        wgmma_rs_32_0(d + 48, A[4], A[5], A[6], A[7], db + 112, 1);
        wgmma_rs_32_0(d + 0, A[8], A[9], A[10], A[11], db + 32, 1);
        wgmma_rs_32_0(d + 16, A[8], A[9], A[10], A[11], db + 64, 1);
        wgmma_rs_32_0(d + 32, A[8], A[9], A[10], A[11], db + 96, 1);
        wgmma_rs_32_0(d + 64, A[0], A[1], A[2], A[3], db + 128, 0);
        wgmma_rs_32_0(d + 0, A[12], A[13], A[14], A[15], db + 48, 1);
        wgmma_rs_32_0(d + 16, A[12], A[13], A[14], A[15], db + 80, 1);
        wgmma_rs_32_0(d + 32, A[12], A[13], A[14], A[15], db + 112, 1);
        wgmma_rs_32_0(d + 48, A[8], A[9], A[10], A[11], db + 128, 1);
        wgmma_rs_32_0(d + 0, A[16], A[17], A[18], A[19], db + 64, 1);
        wgmma_rs_32_0(d + 16, A[16], A[17], A[18], A[19], db + 96, 1);
        wgmma_rs_32_0(d + 32, A[16], A[17], A[18], A[19], db + 128, 1);
        wgmma_rs_32_0(d + 64, A[4], A[5], A[6], A[7], db + 144, 1);
        wgmma_rs_32_0(d + 0, A[20], A[21], A[22], A[23], db + 80, 1);
        wgmma_rs_32_0(d + 16, A[20], A[21], A[22], A[23], db + 112, 1);
        wgmma_rs_32_0(d + 48, A[12], A[13], A[14], A[15], db + 144, 1);
        wgmma_rs_32_0(d + 32, A[20], A[21], A[22], A[23], db + 144, 1);
        wgmma_rs_32_0(d + 0, A[24], A[25], A[26], A[27], db + 96, 1);
        wgmma_rs_32_0(d + 16, A[24], A[25], A[26], A[27], db + 128, 1);
        wgmma_rs_32_0(d + 80, A[0], A[1], A[2], A[3], db + 160, 0);
        wgmma_rs_32_0(d + 64, A[8], A[9], A[10], A[11], db + 160, 1);
        wgmma_rs_32_0(d + 0, A[28], A[29], A[30], A[31], db + 112, 1);
        wgmma_rs_32_0(d + 16, A[28], A[29], A[30], A[31], db + 144, 1);
        wgmma_rs_32_0(d + 48, A[16], A[17], A[18], A[19], db + 160, 1);
        wgmma_rs_32_0(d + 32, A[24], A[25], A[26], A[27], db + 160, 1);
        wgmma_rs_32_0(d + 0, A[32], A[33], A[34], A[35], db + 128, 1);
        wgmma_rs_32_0(d + 16, A[32], A[33], A[34], A[35], db + 160, 1);
        wgmma_rs_32_0(d + 80, A[4], A[5], A[6], A[7], db + 176, 1);
        wgmma_rs_32_0(d + 64, A[12], A[13], A[14], A[15], db + 176, 1);
        wgmma_rs_32_0(d + 0, A[36], A[37], A[38], A[39], db + 144, 1);
        wgmma_rs_32_0(d + 48, A[20], A[21], A[22], A[23], db + 176, 1);
        wgmma_rs_32_0(d + 32, A[28], A[29], A[30], A[31], db + 176, 1);
        wgmma_rs_32_0(d + 16, A[36], A[37], A[38], A[39], db + 176, 1);
        wgmma_rs_32_0(d + 0, A[40], A[41], A[42], A[43], db + 160, 1);
        wgmma_rs_32_0(d + 96, A[0], A[1], A[2], A[3], db + 192, 0);
        wgmma_rs_32_0(d + 80, A[8], A[9], A[10], A[11], db + 192, 1);
        wgmma_rs_32_0(d + 64, A[16], A[17], A[18], A[19], db + 192, 1);
        wgmma_rs_32_0(d + 0, A[44], A[45], A[46], A[47], db + 176, 1);
        wgmma_rs_32_0(d + 48, A[24], A[25], A[26], A[27], db + 192, 1);
        wgmma_rs_32_0(d + 32, A[32], A[33], A[34], A[35], db + 192, 1);
        wgmma_rs_32_0(d + 16, A[40], A[41], A[42], A[43], db + 192, 1);
        wgmma_rs_32_0(d + 0, A[48], A[49], A[50], A[51], db + 192, 1);
        wgmma_rs_32_0(d + 96, A[4], A[5], A[6], A[7], db + 208, 1);
        wgmma_rs_32_0(d + 80, A[12], A[13], A[14], A[15], db + 208, 1);
        wgmma_rs_32_0(d + 64, A[20], A[21], A[22], A[23], db + 208, 1);
        wgmma_rs_32_0(d + 48, A[28], A[29], A[30], A[31], db + 208, 1);
        wgmma_rs_32_0(d + 32, A[36], A[37], A[38], A[39], db + 208, 1);
        wgmma_rs_32_0(d + 16, A[44], A[45], A[46], A[47], db + 208, 1);
        wgmma_rs_32_0(d + 0, A[52], A[53], A[54], A[55], db + 208, 1);
        wgmma_rs_32_0(d + 112, A[0], A[1], A[2], A[3], db + 224, 0);
        wgmma_rs_32_0(d + 96, A[8], A[9], A[10], A[11], db + 224, 1);
        wgmma_rs_32_0(d + 80, A[16], A[17], A[18], A[19], db + 224, 1);
        wgmma_rs_32_0(d + 64, A[24], A[25], A[26], A[27], db + 224, 1);
        wgmma_rs_32_0(d + 48, A[32], A[33], A[34], A[35], db + 224, 1);
        wgmma_rs_32_0(d + 32, A[40], A[41], A[42], A[43], db + 224, 1);
        wgmma_rs_32_0(d + 16, A[48], A[49], A[50], A[51], db + 224, 1);
        wgmma_rs_32_0(d + 0, A[56], A[57], A[58], A[59], db + 224, 1);
        wgmma_rs_32_0(d + 112, A[4], A[5], A[6], A[7], db + 240, 1);
        wgmma_rs_32_0(d + 96, A[12], A[13], A[14], A[15], db + 240, 1);
        wgmma_rs_32_0(d + 80, A[20], A[21], A[22], A[23], db + 240, 1);
        wgmma_rs_32_0(d + 64, A[28], A[29], A[30], A[31], db + 240, 1);
        wgmma_rs_32_0(d + 48, A[36], A[37], A[38], A[39], db + 240, 1);
        wgmma_rs_32_0(d + 32, A[44], A[45], A[46], A[47], db + 240, 1);
        wgmma_rs_32_0(d + 16, A[52], A[53], A[54], A[55], db + 240, 1);
        wgmma_rs_32_0(d + 0, A[60], A[61], A[62], A[63], db + 240, 1);
        wg_commit();
        bar_arrive(3 - isE, 256);
        if (j < 3) mbar_wait(BAR(B_PL + j + 2), 0);
        wg_wait<0>();
        regfence<128>(d);
        if (lane == 0 && w == 0) TSTAMP(42 + j);
        const uint32_t sa = sb + (j + 3) * SLOT + aoff;
        auto post = [&](int z) {
          uint32_t e[4];
#pragma unroll
          for (int i = 0; i < 4; i++) {
            const int u = 4 * z + i;
            e[i] = u < 31 ? pack2(d[4 * u] + d[4 * u + 6], d[4 * u + 1] + d[4 * u + 7]) : pack2(d[4 * u], d[4 * u + 1]);
          }
          if (z == 0 && c < w) e[0] = 0;
          stsm4t(ub + (z == 0 ? yoff0 : z == 4 ? yoff4 : z < 4 ? yoff + 8192 - 512 * z : yoff - 512 * (z - 4)), e[0], e[1], e[2], e[3]);
        };
        if (j < 3) {
#pragma unroll
          for (int z = 0; z < 8; z++) {
#pragma unroll
            for (int g = 2 * z; g < 2 * z + 2; g++) { A[4 * g] = lds32(sa + g * 256); A[4 * g + 1] = lds32(sa + g * 256 + 128); A[4 * g + 2] = lds32(sa + g * 256 + 16); A[4 * g + 3] = lds32(sa + g * 256 + 144); }
            post(z);
          }
        } else {
#pragma unroll
          for (int z = 0; z < 8; z++) post(z);
          mbar_wait(BAR(B_MOD + 1), 0);
          const uint4 mv = lds128(sb + O_MV + j * 16);
          mbar_wait(BAR(B_QF + j), 0);
          bar_sync(5 + isE, 128);
          part2<2>(ub, w >> 1, (w & 1) * 2, lane, mv);
          fence_async_smem();
        }
        __syncwarp();
        if (lane == 0) mbar_arrive(BAR(B_Y + j));
        if (lane == 0 && w == 0) TSTAMP(j >= 3 ? 17 + j : 47 + j);
      }
    }
    if (isE) bar_sync(3, 256);
    const int rh = isE ^ kh;
    uint32_t hA[48];
    {
      float ag[96], au[96];
      int slot = 0, ph = 0, s = 0;
      const int v0 = min(vr, 2) * 4;
      const uint64_t dbase = mkdesc(sb, 4096, 1024, 1);
      auto stage = [&](float* vv) {
        const uint64_t dg = dbase + slot * (SLOT >> 4), da = dg + ((24576 + rh * 4096) >> 4);
        mbar_wait(BAR(B_FULL + slot), ph);
        if (s == 0 && lane == 0 && w == 0) TSTAMP(22 + isE);
        if (s && (s & 3) == 0 && tid == 128) TSTAMP(37 + (s >> 2));
        wg_fence();
        wgmma_ss_192_11(ag, da, dg, s);
        wgmma_ss_192_11(au, da, dg + 768, s);
        if (vv) wgmma_ss_8_10(vv, dg + (2 * vt + isE) * 256, mkdesc(sb + O_CS, 32, 128, 0) + (s & 3) * 8, s & 3);
        wgmma_ss_192_11(ag, da + 128, dg + 128, 1);
        wgmma_ss_192_11(au, da + 128, dg + 896, 1);
        if (vv) wgmma_ss_8_10(vv, dg + (2 * vt + isE) * 256 + 128, mkdesc(sb + O_CS, 32, 128, 0) + (s & 3) * 8 + 4, 1);
        wg_commit();
        wg_wait<1>();
        if (s > 0 && lane == 0 && w == 0) mbar_arrive(BAR(B_EMPTY + (slot == 0 ? 5 : slot - 1)));
        if (++slot == 6) { slot = 0; ph ^= 1; }
        ++s;
      };
#pragma unroll 1
      while (s < v0) stage(nullptr);
      {
        float vv[4];
        mbar_wait(BAR(B_CS), 0);
#pragma unroll 1
        while (s < v0 + 4) stage(vv);
        wg_wait<0>();
        regfence<4>(vv);
        asm volatile("stmatrix.sync.aligned.m8n8.x2.trans.shared.b16 [%0], {%1,%2};" ::"r"(sb + O_TMP + ((lane & 6) ? 1024 : 512 + isE * 256 + w * 64 + (lane & 8) * 4 + (lane & 1) * 16)),
                     "r"(pack2(vv[0], vv[1])), "r"(pack2(vv[2], vv[3])) : "memory");
        fence_async_smem();
        __syncwarp();
        if (lane == 0) mbar_arrive(BAR(B_VVS));
      }
#pragma unroll 1
      while (s < 20) stage(nullptr);
      {
        mbar_wait(BAR(B_ST + rh), 0);
        const uint32_t a0 = lds32(sb + O_ST + rh * 512 + w * 128 + r * 8), a1 = lds32(sb + O_ST + rh * 512 + w * 128 + r * 8 + 64);
        const uint32_t a2 = c ? 0 : a0, a3 = c ? 0 : a1;
        mbar_wait(BAR(B_VV), 0);
        const uint64_t dp = mkdesc(sb + O_BP, 128, 160, 0);
        wg_fence();
        wgmma_rs_192_1(ag, a0, a1, a2, a3, dp, 1);
        wgmma_rs_192_1(au, a0, a1, a2, a3, dp + 240, 1);
        wg_commit();
        wg_wait<1>();
        if (lane == 0 && w == 0) mbar_arrive(BAR(B_EMPTY + 1));
        mbar_wait(BAR(B_EMPTY + 5 - isE), 1);
        wg_wait<0>();
      }
      regfence<96>(ag); regfence<96>(au);
      if (lane == 0 && w == 0) TSTAMP(24 + isE);
      const uint32_t stg = sb + (5 - isE) * SLOT + (16 * w + (lane & 15)) * 128;
#pragma unroll
      for (int kq = 0; kq < 12; kq++) {
#pragma unroll
        for (int i = 0; i < 4; i++) hA[4 * kq + i] = pack2(ag[8 * kq + 2 * i] * au[8 * kq + 2 * i], ag[8 * kq + 2 * i + 1] * au[8 * kq + 2 * i + 1]);
        stsm4(stg + (kq >> 2) * 8192 + (((2 * (kq & 3) + (lane >> 4)) ^ (lane & 7)) * 16), hA[4 * kq], hA[4 * kq + 1], hA[4 * kq + 2], hA[4 * kq + 3]);
      }
      fence_async_smem();
      __syncwarp();
      if (lane == 0) mbar_arrive(BAR(B_STAGED + isE));
      if (lane == 0 && w == 0) TSTAMP(50 + isE);
    }
    float o[80];
    {
#pragma unroll
      for (int s = 0; s < 3; s++) {
        mbar_wait(BAR(B_W2F + s), 0);
        const uint64_t dw = mkdesc(sb + w2entry(s), 4096, 512, 2);
        wg_fence();
#pragma unroll
        for (int kk = 0; kk < 4; kk++) wgmma_rs_160_1(o, hA[16 * s + 4 * kk], hA[16 * s + 4 * kk + 1], hA[16 * s + 4 * kk + 2], hA[16 * s + 4 * kk + 3], dw + kk * 64, (s | kk) ? 1 : 0);
        wg_commit();
        if (s > 0) { wg_wait<1>(); if (lane == 0 && w == 0) mbar_arrive(BAR(B_W2E + s - 1)); }
      }
      const uint32_t hreg = sb + (5 - isE) * SLOT;
#pragma unroll 1
      for (int i = 0; i < 9; i++) {
        const int e = i < 3 ? i + 3 : i - 3;
        mbar_wait(BAR(B_W2F + e), i >= 3);
        mbar_wait(BAR(B_HF + isE * 4 + (i & 3)), (i >> 2) & 1);
        if (i == 0 && lane == 0 && w == 0) TSTAMP(26 + isE);
        const uint64_t dw = mkdesc(sb + w2entry(e), 4096, 512, 2);
        const uint64_t dh = mkdesc(hreg + (i & 3) * 8192, 16, 1024, 1);
        wg_fence();
#pragma unroll
        for (int kk = 0; kk < 4; kk++) wgmma_ss_160_01(o, dh + kk * 2, dw + kk * 64, 1);
        wg_commit();
        wg_wait<1>();
        if (lane == 0 && w == 0) {
          mbar_arrive(BAR(B_W2E + (e == 0 ? 5 : e - 1)));
          if (i > 0) mbar_arrive(BAR(B_HE + isE * 4 + ((i - 1) & 3)));
        }
      }
      wg_wait<0>();
      regfence<80>(o);
      if (lane == 0 && w == 0) TSTAMP(28 + isE);
      const float ia = __uint_as_float(lds32(sb + O_ST + rh * 512 + w * 128 + r * 8 + 4)), ib = __uint_as_float(lds32(sb + O_ST + rh * 512 + w * 128 + r * 8 + 68));
#pragma unroll
      for (int u = 0; u < 20; u++) { o[4 * u] *= ia; o[4 * u + 1] *= ia; o[4 * u + 2] *= ib; o[4 * u + 3] *= ib; }
    }
    asm volatile("barrier.cluster.wait.aligned;" ::: "memory");
    const uint32_t red = sb + w2entry(0) + (tid & 127) * 16;
    if (isE) {
      mbar_wait(BAR(B_X1), 0);
      mbar_wait_cluster(BAR(B_RDY), 0);
      uint32_t rred, rbar;
      asm volatile("mapa.shared::cluster.u32 %0, %1, %2;" : "=r"(rred) : "r"(red), "r"(kh ^ 1));
      asm volatile("mapa.shared::cluster.u32 %0, %1, %2;" : "=r"(rbar) : "r"(BAR(B_RED)), "r"(kh ^ 1));
      const uint32_t xa = sb + O_REG + ((lane & 7) + 8 * (lane >> 4)) * 128 + (((2 * w + ((lane >> 3) & 1)) ^ (lane & 7)) * 16);
#pragma unroll
      for (int u = 0; u < 10; u++) {
        uint32_t x0, x1, x2, x3;
        ldsm4t(xa + u * 2048, x0, x1, x2, x3);
        const float2 g0 = lds64f(sb + O_GB + (16 * u + 2 * c) * 4), g1 = lds64f(sb + O_GB + (16 * u + 8 + 2 * c) * 4);
        asm volatile("st.async.weak.shared::cluster.mbarrier::complete_tx::bytes.v4.f32 [%0], {%1,%2,%3,%4}, [%5];" ::"r"(rred + (2 * u) * 2048),
                     "f"(fmaf(g0.x, o[8 * u], blo(x0))), "f"(fmaf(g0.y, o[8 * u + 1], bhi(x0))), "f"(fmaf(g0.x, o[8 * u + 2], blo(x1))), "f"(fmaf(g0.y, o[8 * u + 3], bhi(x1))), "r"(rbar) : "memory");
        asm volatile("st.async.weak.shared::cluster.mbarrier::complete_tx::bytes.v4.f32 [%0], {%1,%2,%3,%4}, [%5];" ::"r"(rred + (2 * u + 1) * 2048),
                     "f"(fmaf(g1.x, o[8 * u + 4], blo(x2))), "f"(fmaf(g1.y, o[8 * u + 5], bhi(x2))), "f"(fmaf(g1.x, o[8 * u + 6], blo(x3))), "f"(fmaf(g1.y, o[8 * u + 7], bhi(x3))), "r"(rbar) : "memory");
      }
    } else {
      mbar_wait_cluster(BAR(B_RED), 0);
      if (tid == 128) TSTAMP(30);
      bar_sync(5, 128);
      const int row = 16 * w + (lane & 15);
      const uint32_t stg = sb + 5 * SLOT + row * 64;
#pragma unroll
      for (int u = 0; u < 10; u++) {
        const float4 p0 = lds128f(red + (2 * u) * 2048), p1 = lds128f(red + (2 * u + 1) * 2048);
        const float2 g0 = lds64f(sb + O_GB + (16 * u + 2 * c) * 4), g1 = lds64f(sb + O_GB + (16 * u + 8 + 2 * c) * 4);
        stsm4(stg + (u >> 1) * 4096 + (((2 * (u & 1) + (lane >> 4)) ^ ((row >> 1) & 3)) * 16),
              pack2(fmaf(g0.x, o[8 * u], p0.x), fmaf(g0.y, o[8 * u + 1], p0.y)), pack2(fmaf(g0.x, o[8 * u + 2], p0.z), fmaf(g0.y, o[8 * u + 3], p0.w)),
              pack2(fmaf(g1.x, o[8 * u + 4], p1.x), fmaf(g1.y, o[8 * u + 5], p1.y)), pack2(fmaf(g1.x, o[8 * u + 6], p1.z), fmaf(g1.y, o[8 * u + 7], p1.w)));
      }
      fence_async_smem();
      bar_sync(5, 128);
      if (tid == 128) {
        tma3d_store(&p.m_out, sb + 5 * SLOT, 0, rb * 128 + kh * 64, cg * 5);
        bulk_commit(); bulk_wait0_read();
        TSTAMP(31);
      }
    }
  }
}

#define L2PROMO CU_TENSOR_MAP_L2_PROMOTION_L2_128B
typedef CUresult (*EncodeFn)(CUtensorMap*, CUtensorMapDataType, cuuint32_t, void*, const cuuint64_t*, const cuuint64_t*, const cuuint32_t*,
                             const cuuint32_t*, CUtensorMapInterleave, CUtensorMapSwizzle, CUtensorMapL2promotion, CUtensorMapFloatOOBfill);

void make_map(EncodeFn enc, CUtensorMap* m, const void* ptr, uint64_t inner, uint64_t outer, uint32_t bi, uint32_t bo, CUtensorMapSwizzle sw) {
  cuuint64_t d[2] = {inner, outer};
  cuuint64_t s[1] = {inner * 2};
  cuuint32_t bx[2] = {bi, bo};
  cuuint32_t e[2] = {1, 1};
  enc(m, CU_TENSOR_MAP_DATA_TYPE_BFLOAT16, 2, const_cast<void*>(ptr), d, s, bx, e, CU_TENSOR_MAP_INTERLEAVE_NONE, sw, L2PROMO,
      CU_TENSOR_MAP_FLOAT_OOB_FILL_NONE);
}

void make_map3(EncodeFn enc, CUtensorMap* m, const void* ptr, uint64_t d0, uint64_t d1, uint64_t d2, uint64_t s1, uint64_t s2, uint32_t b0, uint32_t b1, uint32_t b2,
               CUtensorMapSwizzle sw) {
  cuuint64_t d[3] = {d0, d1, d2};
  cuuint64_t s[2] = {s1, s2};
  cuuint32_t bx[3] = {b0, b1, b2};
  cuuint32_t e[3] = {1, 1, 1};
  enc(m, CU_TENSOR_MAP_DATA_TYPE_BFLOAT16, 3, const_cast<void*>(ptr), d, s, bx, e, CU_TENSOR_MAP_INTERLEAVE_NONE, sw, L2PROMO,
      CU_TENSOR_MAP_FLOAT_OOB_FILL_NONE);
}

}

extern "C" void kernel_launch(void* const* d_in, const int* in_sizes, int n_in, void* d_out, int out_size) {
  (void)in_sizes; (void)n_in; (void)out_size;
  void* f = nullptr;
  cudaDriverEntryPointQueryResult qr;
  cudaGetDriverEntryPoint("cuTensorMapEncodeTiled", &f, cudaEnableDefault, &qr);
  EncodeFn enc = (EncodeFn)f;
  void *qT, *kvT, *x1T, *h, *vv;
  cudaGetSymbolAddress(&kvT, g_kvT);
  cudaGetSymbolAddress(&qT, g_qT);
  cudaGetSymbolAddress(&x1T, g_x1T);
  cudaGetSymbolAddress(&h, g_h);
  cudaGetSymbolAddress(&vv, g_vv);
  Params p;
  make_map3(enc, &p.m_q, d_in[0], 64, S_, 10, D_ * 2, 128, 64, 16, 10, CU_TENSOR_MAP_SWIZZLE_128B);
  make_map3(enc, &p.m_kvT, kvT, S_, D_ / 4, 4, S_ * 8, S_ * 2, 64, 40, 4, CU_TENSOR_MAP_SWIZZLE_128B);
  make_map(enc, &p.m_qT, qT, 2 * S_, D_, 32, 128, CU_TENSOR_MAP_SWIZZLE_64B);
  make_map(enc, &p.m_wm, d_in[11], 6 * D_, D_, 64, 64, CU_TENSOR_MAP_SWIZZLE_128B);
  make_map3(enc, &p.m_wg, d_in[7], 64, D_, F_ / 64, F_ * 2, 128, 64, 32, 3, CU_TENSOR_MAP_SWIZZLE_128B);
  make_map3(enc, &p.m_wu, d_in[8], 64, D_, F_ / 64, F_ * 2, 128, 64, 32, 3, CU_TENSOR_MAP_SWIZZLE_128B);
  make_map3(enc, &p.m_xa, x1T, 64, D_, 64, S_ * 4, 128, 64, 32, 2, CU_TENSOR_MAP_SWIZZLE_128B);
  make_map(enc, &p.m_xr, x1T, 2 * S_, D_, 64, 160, CU_TENSOR_MAP_SWIZZLE_128B);
  make_map3(enc, &p.m_w2, d_in[9], 32, F_, D_ / 32, D_ * 2, 64, 32, 64, 5, CU_TENSOR_MAP_SWIZZLE_64B);
  make_map(enc, &p.m_h, h, F_, S_, 64, 64, CU_TENSOR_MAP_SWIZZLE_128B);
  make_map3(enc, &p.m_out, d_out, 32, S_, D_ / 32, D_ * 2, 64, 32, 64, 5, CU_TENSOR_MAP_SWIZZLE_64B);
  make_map3(enc, &p.m_vv, vv, 16, 40, 48, 1536, 32, 16, 5, 48, CU_TENSOR_MAP_SWIZZLE_NONE);
  p.q = (const __nv_bfloat16*)d_in[0];
  p.k = (const __nv_bfloat16*)d_in[1];
  p.v = (const __nv_bfloat16*)d_in[2];
  p.shift = (const __nv_bfloat16*)d_in[3];
  p.ssm = (const __nv_bfloat16*)d_in[4];
  p.ssmD = (const __nv_bfloat16*)d_in[5];
  p.c = (const __nv_bfloat16*)d_in[10];
  p.wg = (const __nv_bfloat16*)d_in[7];
  p.wu = (const __nv_bfloat16*)d_in[8];
  p.w2 = (const __nv_bfloat16*)d_in[9];
  cudaFuncSetAttribute(fused_kernel, cudaFuncAttributeMaxDynamicSharedMemorySize, SMEM_BYTES);
  fused_kernel<<<128, 384, SMEM_BYTES, cudaStreamPerThread>>>(p);
}
```

```cpp
#include <cuda_runtime.h>
#include <cuda.h>
#include <cuda_bf16.h>
#include <cstdint>

namespace {

constexpr int S_ = 2048, D_ = 640, F_ = 1536;

__device__ __align__(1024) __nv_bfloat16 g_kvT[D_ * S_];
__device__ __align__(1024) __nv_bfloat16 g_qT[D_ * S_ * 2];
__device__ __align__(1024) __nv_bfloat16 g_x1T[D_ * S_ * 2];
__device__ __align__(1024) __nv_bfloat16 g_h[S_ * F_];
__device__ __align__(1024) uint32_t g_mod[5 * 6 * D_];
__device__ __align__(1024) uint32_t g_vv[8 * 5 * 384];
__device__ __align__(1024) uint32_t g_st[16 * 2 * 4 * 128];
__device__ __align__(1024) uint32_t g_sync[128 * 32];
enum { Y_KV = 0, Y_X1 = 20 * 32, Y_Q = 30 * 32, Y_MOD = 31 * 32, Y_VV = 34 * 32, Y_H = 64 * 32, Y_EP = 7 };
#define TSTAMP(i) do { } while (0)
#define T_K1 1300
#define T_S1 2580
#define T_K2 3060
#define T_Q 4020
#define T_S2 6420
#define T_K3 6900
#define T_WM0 7860
#define T_S3 9300
#define T_K4 9780
#define T_S4 10740
#define T_W0 11220
#define T_WM1 11940
#define T_REST 13380
#define SCHED_E (STEP(0, 0, 0, -1, 0) | STEP(1, 0, -1, -1, 1) | STEP(2, 0, 4, -1, 3) | STEP(3, 0, -1, 1, -1))
#define SCHED_L (STEP(0, 0, 1, -1, -1) | STEP(1, 0, 2, -1, -1) | STEP(2, 1, 3, 0, 2) | STEP(3, 0, -1, -1, 4) | STEP(4, 0, -1, 2, -1))
#define LH 10
#define LEAD 3

struct Params {
  CUtensorMap m_k, m_kh, m_v, m_q, m_wm, m_wg, m_wu, m_xa, m_xr, m_w2a, m_w2b, m_h, m_outa, m_outb;
  const __nv_bfloat16 *k, *v, *shift, *ssm, *ssmD, *c, *wg, *wu, *w2;
  int zero;
};

constexpr uint32_t SLOT = 32768;
constexpr uint32_t U_RAW = 16, U_ODD = U_RAW + 4160, U_KV = 8448;
constexpr uint32_t O_REG = 6 * SLOT;
constexpr uint32_t O_BP = O_REG + 20736;
constexpr uint32_t O_SILU = O_BP + 6144;
constexpr uint32_t O_CS = O_SILU + 384;
constexpr uint32_t O_GB = O_CS + 640;
constexpr uint32_t O_TMP = O_GB + 640;
constexpr uint32_t O_ST = O_TMP + 512;
constexpr uint32_t O_BAR = O_ST + 1024;
constexpr uint32_t SMEM_BYTES = O_BAR + 1024;
enum { B_EMPTY = 0, B_W2E = 6, B_PL = 11, B_Y = 16, B_QST = 21, B_STAGED = 22, B_RED = 28, B_RDY = 29, B_FULL = 30, B_W2F = 36, B_HF = 41, B_HE = 49,
       B_KIN = 57, B_KV = 62, B_QF = 67, B_QIN = 72, B_WM = 73, B_CS = 76, B_VV = 77, B_X1 = 78, B_ST = 80, B_SSM = 84 };
__device__ __forceinline__ uint32_t kreg(int n) { return n ? 2 * SLOT - 6144 + n * 6144 : 4 * SLOT + 24576; }
__device__ __forceinline__ uint32_t w2entry(int e) { return e == 3 ? SLOT + 24576 : (e + 1) * SLOT; }
__device__ __forceinline__ uint32_t bnd(int j) { return j < 2 ? (j + 4) * SLOT : (j - 2) * 16384; }
__device__ __forceinline__ uint32_t qreg(int j) { return j < 2 ? (j + 4) * SLOT + 16384 : j < 4 ? SLOT + j * 8192 : O_REG; }

__device__ __forceinline__ uint32_t smem_u32(const void* p) { return (uint32_t)__cvta_generic_to_shared(p); }
__device__ __forceinline__ void mbar_init(uint32_t bar, uint32_t cnt) { asm volatile("mbarrier.init.shared::cta.b64 [%0], %1;" ::"r"(bar), "r"(cnt) : "memory"); }
__device__ __forceinline__ void mbar_expect(uint32_t bar, uint32_t bytes) { asm volatile("mbarrier.arrive.expect_tx.shared::cta.b64 _, [%0], %1;" ::"r"(bar), "r"(bytes) : "memory"); }
__device__ __forceinline__ void mbar_arrive(uint32_t bar) { asm volatile("mbarrier.arrive.shared::cta.b64 _, [%0];" ::"r"(bar) : "memory"); }
__device__ __forceinline__ void mbar_wait(uint32_t bar, uint32_t parity) {
  asm volatile("{\n .reg .pred p;\n .reg .u32 c;\n mov.u32 c, 0;\n LOOP:\n mbarrier.try_wait.parity.shared::cta.b64 p, [%0], %1;\n @p bra DONE;\n add.u32 c, c, 1;\n setp.lt.u32 p, c, 200000;\n @p bra LOOP;\n DONE:\n }" ::"r"(bar), "r"(parity) : "memory");
}
__device__ __forceinline__ void mbar_wait_cluster(uint32_t bar, uint32_t parity) {
  asm volatile("{\n .reg .pred p;\n .reg .u32 c;\n mov.u32 c, 0;\n LOOP:\n mbarrier.try_wait.parity.acquire.cluster.shared::cta.b64 p, [%0], %1;\n @p bra DONE;\n add.u32 c, c, 1;\n setp.lt.u32 p, c, 200000;\n @p bra LOOP;\n DONE:\n }" ::"r"(bar), "r"(parity) : "memory");
}
__device__ __forceinline__ uint32_t clk() { uint32_t c; asm volatile("mov.u32 %0, %%clock;" : "=r"(c)); return c; }
__device__ __forceinline__ uint32_t ldr(const uint32_t* p) { uint32_t v; asm volatile("ld.relaxed.gpu.global.u32 %0, [%1];" : "=r"(v) : "l"(p) : "memory"); return v; }
__device__ __forceinline__ uint4 ldr4(const uint32_t* p) {
  uint4 v; asm volatile("ld.relaxed.gpu.global.v4.u32 {%0,%1,%2,%3}, [%4];" : "=r"(v.x), "=r"(v.y), "=r"(v.z), "=r"(v.w) : "l"(p) : "memory"); return v;
}
__device__ __forceinline__ void poll_ge(const uint32_t* p, uint32_t target) {
  asm volatile("{\n .reg .pred p;\n .reg .u32 c, v;\n mov.u32 c, 0;\n LOOP:\n ld.relaxed.gpu.global.u32 v, [%0];\n sub.u32 v, v, %1;\n setp.ge.s32 p, v, 0;\n @p bra DONE;\n add.u32 c, c, 1;\n setp.lt.u32 p, c, 100000;\n @p bra LOOP;\n DONE:\n }" ::"l"(p), "r"(target) : "memory");
}
__device__ __forceinline__ uint32_t poll4(const uint32_t* p, uint32_t target, uint32_t need) {
  uint32_t m;
  int it = 0;
  do {
    const uint4 v = ldr4(p);
    m = (~(v.x - target) >> 31) | ((~(v.y - target) >> 31) << 1) | ((~(v.z - target) >> 31) << 2) | ((~(v.w - target) >> 31) << 3);
  } while ((m & need) != need && ++it < 100000);
  return m;
}
__device__ __forceinline__ void hint_add(uint32_t* p) { asm volatile("red.relaxed.gpu.global.add.u32 [%0], 1;" ::"l"(p) : "memory"); }
__device__ __forceinline__ void refetch(const void* g, uint32_t off, uint32_t a, uint32_t tag) {
  asm volatile("{\n .reg .pred p;\n .reg .u32 c, v, x, y, z;\n .reg .u64 q;\n mov.u32 c, 0;\n cvt.u64.u32 q, %1;\n add.u64 q, q, %0;\n"
               " LOOP:\n ld.relaxed.gpu.global.u32 v, [q];\n xor.b32 v, v, %3;\n and.b32 v, v, 1;\n setp.eq.u32 p, v, 0;\n @p bra DONE;\n add.u32 c, c, 1;\n setp.lt.u32 p, c, 100000;\n @p bra LOOP;\n"
               " DONE:\n ld.relaxed.gpu.global.v4.u32 {v, x, y, z}, [%0];\n st.shared.v4.u32 [%2], {v, x, y, z};\n ld.relaxed.gpu.global.v4.u32 {v, x, y, z}, [%0+16];\n xor.b32 c, %2, 16;\n"
               " st.shared.v4.u32 [c], {v, x, y, z};\n fence.proxy.async.shared::cta;\n }" ::"l"(g), "r"(off), "r"(a), "r"(tag) : "memory");
}
__device__ __forceinline__ uint32_t settag(uint32_t x, uint32_t m, uint32_t t) { return (x & ~m) | (t & m); }
__device__ __forceinline__ void stg128(void* p, uint32_t x, uint32_t y, uint32_t z, uint32_t w) {
  asm volatile("st.global.v4.u32 [%0], {%1,%2,%3,%4};" ::"l"(p), "r"(x), "r"(y), "r"(z), "r"(w) : "memory");
}
__device__ __forceinline__ void cpa16(uint32_t dst, const void* src, uint32_t n) { asm volatile("cp.async.cg.shared.global [%0], [%1], 16, %2;" ::"r"(dst), "l"(src), "r"(n) : "memory"); }
__device__ __forceinline__ void tma3d(uint32_t dst, const CUtensorMap* m, int x, int y, int z, uint32_t bar) {
  asm volatile("cp.async.bulk.tensor.3d.shared::cluster.global.mbarrier::complete_tx::bytes [%0], [%1, {%3, %4, %5}], [%2];" ::"r"(dst), "l"(m), "r"(bar), "r"(x), "r"(y), "r"(z) : "memory");
}
__device__ __forceinline__ void tma3d_store(const CUtensorMap* m, uint32_t src, int x, int y, int z) {
  asm volatile("cp.async.bulk.tensor.3d.global.shared::cta.bulk_group [%0, {%2, %3, %4}], [%1];" ::"l"(m), "r"(src), "r"(x), "r"(y), "r"(z) : "memory");
}
__device__ __forceinline__ void bulk_st(void* dst, uint32_t src, uint32_t bytes) {
  asm volatile("cp.async.bulk.global.shared::cta.bulk_group [%0], [%1], %2;" ::"l"(dst), "r"(src), "r"(bytes) : "memory");
}
__device__ __forceinline__ void bulk_pf(const void* src, uint32_t bytes) { asm volatile("cp.async.bulk.prefetch.L2.global [%0], %1;" ::"l"(src), "r"(bytes) : "memory"); }
__device__ __forceinline__ void tma2d(uint32_t dst, const CUtensorMap* m, int x, int y, uint32_t bar) {
  asm volatile("cp.async.bulk.tensor.2d.shared::cluster.global.mbarrier::complete_tx::bytes [%0], [%1, {%3, %4}], [%2];" ::"r"(dst), "l"(m), "r"(bar), "r"(x), "r"(y) : "memory");
}
__device__ __forceinline__ void tma2d_store(const CUtensorMap* m, uint32_t src, int x, int y) {
  asm volatile("cp.async.bulk.tensor.2d.global.shared::cta.bulk_group [%0, {%2, %3}], [%1];" ::"l"(m), "r"(src), "r"(x), "r"(y) : "memory");
}
__device__ __forceinline__ void bulk_ld(uint32_t dst, const void* src, uint32_t bytes, uint32_t bar) {
  asm volatile("cp.async.bulk.shared::cluster.global.mbarrier::complete_tx::bytes [%0], [%1], %2, [%3];" ::"r"(dst), "l"(src), "r"(bytes), "r"(bar) : "memory");
}
__device__ __forceinline__ void bulk_commit() { asm volatile("cp.async.bulk.commit_group;" ::: "memory"); }
template <int N> __device__ __forceinline__ void bulk_wait() { asm volatile("cp.async.bulk.wait_group %0;" ::"n"(N) : "memory"); }
__device__ __forceinline__ void bulk_wait0_read() { asm volatile("cp.async.bulk.wait_group.read 0;" ::: "memory"); }
__device__ __forceinline__ void fence_async_smem() { asm volatile("fence.proxy.async.shared::cta;" ::: "memory"); }
__device__ __forceinline__ void bar_sync(int id, int n) { asm volatile("bar.sync %0, %1;" ::"r"(id), "r"(n) : "memory"); }
__device__ __forceinline__ void bar_arrive(int id, int n) { asm volatile("bar.arrive %0, %1;" ::"r"(id), "r"(n) : "memory"); }
__device__ __forceinline__ void wg_fence() { asm volatile("wgmma.fence.sync.aligned;" ::: "memory"); }
__device__ __forceinline__ void wg_commit() { asm volatile("wgmma.commit_group.sync.aligned;" ::: "memory"); }
template <int N> __device__ __forceinline__ void wg_wait() { asm volatile("wgmma.wait_group.sync.aligned %0;" ::"n"(N) : "memory"); }
__device__ __forceinline__ void ldsm4(uint32_t a, uint32_t& r0, uint32_t& r1, uint32_t& r2, uint32_t& r3) {
  asm volatile("ldmatrix.sync.aligned.m8n8.x4.shared.b16 {%0,%1,%2,%3}, [%4];" : "=r"(r0), "=r"(r1), "=r"(r2), "=r"(r3) : "r"(a) : "memory");
}
__device__ __forceinline__ void ldsm4t(uint32_t a, uint32_t& r0, uint32_t& r1, uint32_t& r2, uint32_t& r3) {
  asm volatile("ldmatrix.sync.aligned.m8n8.x4.trans.shared.b16 {%0,%1,%2,%3}, [%4];" : "=r"(r0), "=r"(r1), "=r"(r2), "=r"(r3) : "r"(a) : "memory");
}
__device__ __forceinline__ void stsm4t(uint32_t a, uint32_t r0, uint32_t r1, uint32_t r2, uint32_t r3) {
  asm volatile("stmatrix.sync.aligned.m8n8.x4.trans.shared.b16 [%0], {%1,%2,%3,%4};" ::"r"(a), "r"(r0), "r"(r1), "r"(r2), "r"(r3) : "memory");
}
__device__ __forceinline__ void stsm4(uint32_t a, uint32_t r0, uint32_t r1, uint32_t r2, uint32_t r3) {
  asm volatile("stmatrix.sync.aligned.m8n8.x4.shared.b16 [%0], {%1,%2,%3,%4};" ::"r"(a), "r"(r0), "r"(r1), "r"(r2), "r"(r3) : "memory");
}
__device__ __forceinline__ uint32_t lds32(uint32_t a) { uint32_t v; asm volatile("ld.shared.u32 %0, [%1];" : "=r"(v) : "r"(a) : "memory"); return v; }
__device__ __forceinline__ uint4 lds128(uint32_t a) { uint4 v; asm volatile("ld.shared.v4.u32 {%0,%1,%2,%3}, [%4];" : "=r"(v.x), "=r"(v.y), "=r"(v.z), "=r"(v.w) : "r"(a) : "memory"); return v; }
__device__ __forceinline__ float4 lds128f(uint32_t a) { float4 v; asm volatile("ld.shared.v4.f32 {%0,%1,%2,%3}, [%4];" : "=f"(v.x), "=f"(v.y), "=f"(v.z), "=f"(v.w) : "r"(a) : "memory"); return v; }
__device__ __forceinline__ float2 lds64f(uint32_t a) { float2 v; asm volatile("ld.shared.v2.f32 {%0,%1}, [%2];" : "=f"(v.x), "=f"(v.y) : "r"(a) : "memory"); return v; }
__device__ __forceinline__ void sts32(uint32_t a, uint32_t v) { asm volatile("st.shared.u32 [%0], %1;" ::"r"(a), "r"(v) : "memory"); }
__device__ __forceinline__ void sts64(uint32_t a, uint32_t x, uint32_t y) { asm volatile("st.shared.v2.u32 [%0], {%1,%2};" ::"r"(a), "r"(x), "r"(y) : "memory"); }
__device__ __forceinline__ void sts128(uint32_t a, uint32_t x, uint32_t y, uint32_t z, uint32_t w) { asm volatile("st.shared.v4.u32 [%0], {%1,%2,%3,%4};" ::"r"(a), "r"(x), "r"(y), "r"(z), "r"(w) : "memory"); }
__device__ __forceinline__ void sts16(uint32_t a, uint16_t v) { asm volatile("st.shared.u16 [%0], %1;" ::"r"(a), "h"(v) : "memory"); }
__device__ __forceinline__ uint32_t prmt(uint32_t a, uint32_t b, uint32_t s) { uint32_t r; asm("prmt.b32 %0, %1, %2, %3;" : "=r"(r) : "r"(a), "r"(b), "r"(s)); return r; }
__device__ __forceinline__ uint32_t hfma2(uint32_t a, uint32_t b, uint32_t c) { uint32_t r; asm("fma.rn.bf16x2 %0, %1, %2, %3;" : "=r"(r) : "r"(a), "r"(b), "r"(c)); return r; }
__device__ __forceinline__ uint32_t hmul2(uint32_t a, uint32_t b) { uint32_t r; asm("mul.rn.bf16x2 %0, %1, %2;" : "=r"(r) : "r"(a), "r"(b)); return r; }
__device__ __forceinline__ uint32_t pack2(float lo, float hi) { uint32_t r; asm("cvt.rn.bf16x2.f32 %0, %1, %2;" : "=r"(r) : "f"(hi), "f"(lo)); return r; }
__device__ __forceinline__ float blo(uint32_t v) { return __uint_as_float(v << 16); }
__device__ __forceinline__ float bhi(uint32_t v) { return __uint_as_float(v & 0xffff0000u); }
__device__ __forceinline__ uint32_t hadd2(uint32_t a, uint32_t b) { uint32_t r; asm("add.rn.bf16x2 %0, %1, %2;" : "=r"(r) : "r"(a), "r"(b)); return r; }
__device__ __forceinline__ void str(uint32_t* p, uint32_t v) { asm volatile("st.relaxed.gpu.global.u32 [%0], %1;" ::"l"(p), "r"(v) : "memory"); }
__device__ __forceinline__ uint32_t tagf(float x, uint32_t tag) { return (__float_as_uint(x) & ~3u) | (tag & 3); }
template <int N> __device__ __forceinline__ float4 gather4(const uint32_t* p, int stride, uint32_t tag) {
  uint4 v[N];
  int it = 0;
  uint32_t bad;
  do {
#pragma unroll
    for (int i = 0; i < N; i++) v[i] = ldr4(p + i * stride);
    bad = 0;
#pragma unroll
    for (int i = 0; i < N; i++) bad |= (v[i].x ^ tag) | (v[i].y ^ tag) | (v[i].z ^ tag) | (v[i].w ^ tag);
  } while ((bad & 3) && ++it < 100000);
  float4 s = make_float4(__uint_as_float(v[0].x), __uint_as_float(v[0].y), __uint_as_float(v[0].z), __uint_as_float(v[0].w));
#pragma unroll
  for (int i = 1; i < N; i++) { s.x += __uint_as_float(v[i].x); s.y += __uint_as_float(v[i].y); s.z += __uint_as_float(v[i].z); s.w += __uint_as_float(v[i].w); }
  return s;
}
__device__ __forceinline__ float gather1(const uint32_t* p, uint32_t tag) {
  uint32_t v[5], bad;
  int it = 0;
  do {
#pragma unroll
    for (int i = 0; i < 5; i++) v[i] = ldr(p + i * 6 * D_);
    bad = (v[0] ^ tag) | (v[1] ^ tag) | (v[2] ^ tag) | (v[3] ^ tag) | (v[4] ^ tag);
  } while ((bad & 3) && ++it < 100000);
  return __uint_as_float(v[0]) + __uint_as_float(v[1]) + __uint_as_float(v[2]) + __uint_as_float(v[3]) + __uint_as_float(v[4]);
}
__device__ __forceinline__ float rbf(float x) { return blo(pack2(x, 0.f)); }
template <int N> __device__ __forceinline__ void halve(float* a, int lane, int bit) {
  const bool up = lane & bit;
#pragma unroll
  for (int i = 0; i < N / 2; i++) {
    const float keep = up ? a[i + N / 2] : a[i], send = up ? a[i] : a[i + N / 2];
    a[i] = keep + __shfl_xor_sync(0xffffffffu, send, bit);
  }
}
__device__ __forceinline__ uint64_t mkdesc(uint32_t addr, uint32_t lbo, uint32_t sbo, uint32_t swz) {
  return (uint64_t)((addr & 0x3FFFF) >> 4) | ((uint64_t)(lbo >> 4) << 16) | ((uint64_t)(sbo >> 4) << 32) | ((uint64_t)swz << 62);
}
template <int N> __device__ __forceinline__ void regfence(float* d) {
#pragma unroll
  for (int i = 0; i < N; i++) asm volatile("" : "+f"(d[i])::"memory");
}

__device__ __forceinline__ void wgmma_rs_32_0(float* d, uint32_t a0, uint32_t a1, uint32_t a2, uint32_t a3, uint64_t db, int sd) {
  asm volatile("{ .reg .pred p; setp.ne.b32 p, %21, 0; wgmma.mma_async.sync.aligned.m64n32k16.f32.bf16.bf16 {%0,%1,%2,%3,%4,%5,%6,%7,%8,%9,%10,%11,%12,%13,%14,%15}, {%16,%17,%18,%19}, %20, p, 1, 1, 0; }"
   : "+f"(d[0]), "+f"(d[1]), "+f"(d[2]), "+f"(d[3]), "+f"(d[4]), "+f"(d[5]), "+f"(d[6]), "+f"(d[7]), "+f"(d[8]), "+f"(d[9]), "+f"(d[10]), "+f"(d[11]), "+f"(d[12]), "+f"(d[13]), "+f"(d[14]), "+f"(d[15]) : "r"(a0), "r"(a1), "r"(a2), "r"(a3), "l"(db), "r"(sd));
}
__device__ __forceinline__ void wgmma_rs_160_1(float* d, uint32_t a0, uint32_t a1, uint32_t a2, uint32_t a3, uint64_t db, int sd) {
  asm volatile("{ .reg .pred p; setp.ne.b32 p, %85, 0; wgmma.mma_async.sync.aligned.m64n160k16.f32.bf16.bf16 {%0,%1,%2,%3,%4,%5,%6,%7,%8,%9,%10,%11,%12,%13,%14,%15,%16,%17,%18,%19,%20,%21,%22,%23,%24,%25,%26,%27,%28,%29,%30,%31,%32,%33,%34,%35,%36,%37,%38,%39,%40,%41,%42,%43,%44,%45,%46,%47,%48,%49,%50,%51,%52,%53,%54,%55,%56,%57,%58,%59,%60,%61,%62,%63,%64,%65,%66,%67,%68,%69,%70,%71,%72,%73,%74,%75,%76,%77,%78,%79}, {%80,%81,%82,%83}, %84, p, 1, 1, 1; }"
   : "+f"(d[0]), "+f"(d[1]), "+f"(d[2]), "+f"(d[3]), "+f"(d[4]), "+f"(d[5]), "+f"(d[6]), "+f"(d[7]), "+f"(d[8]), "+f"(d[9]), "+f"(d[10]), "+f"(d[11]), "+f"(d[12]), "+f"(d[13]), "+f"(d[14]), "+f"(d[15]), "+f"(d[16]), "+f"(d[17]), "+f"(d[18]), "+f"(d[19]), "+f"(d[20]), "+f"(d[21]), "+f"(d[22]), "+f"(d[23]), "+f"(d[24]), "+f"(d[25]), "+f"(d[26]), "+f"(d[27]), "+f"(d[28]), "+f"(d[29]), "+f"(d[30]), "+f"(d[31]), "+f"(d[32]), "+f"(d[33]), "+f"(d[34]), "+f"(d[35]), "+f"(d[36]), "+f"(d[37]), "+f"(d[38]), "+f"(d[39]), "+f"(d[40]), "+f"(d[41]), "+f"(d[42]), "+f"(d[43]), "+f"(d[44]), "+f"(d[45]), "+f"(d[46]), "+f"(d[47]), "+f"(d[48]), "+f"(d[49]), "+f"(d[50]), "+f"(d[51]), "+f"(d[52]), "+f"(d[53]), "+f"(d[54]), "+f"(d[55]), "+f"(d[56]), "+f"(d[57]), "+f"(d[58]), "+f"(d[59]), "+f"(d[60]), "+f"(d[61]), "+f"(d[62]), "+f"(d[63]), "+f"(d[64]), "+f"(d[65]), "+f"(d[66]), "+f"(d[67]), "+f"(d[68]), "+f"(d[69]), "+f"(d[70]), "+f"(d[71]), "+f"(d[72]), "+f"(d[73]), "+f"(d[74]), "+f"(d[75]), "+f"(d[76]), "+f"(d[77]), "+f"(d[78]), "+f"(d[79]) : "r"(a0), "r"(a1), "r"(a2), "r"(a3), "l"(db), "r"(sd));
}
__device__ __forceinline__ void wgmma_rs_192_0(float* d, uint32_t a0, uint32_t a1, uint32_t a2, uint32_t a3, uint64_t db, int sd) {
  asm volatile("{ .reg .pred p; setp.ne.b32 p, %101, 0; wgmma.mma_async.sync.aligned.m64n192k16.f32.bf16.bf16 {%0,%1,%2,%3,%4,%5,%6,%7,%8,%9,%10,%11,%12,%13,%14,%15,%16,%17,%18,%19,%20,%21,%22,%23,%24,%25,%26,%27,%28,%29,%30,%31,%32,%33,%34,%35,%36,%37,%38,%39,%40,%41,%42,%43,%44,%45,%46,%47,%48,%49,%50,%51,%52,%53,%54,%55,%56,%57,%58,%59,%60,%61,%62,%63,%64,%65,%66,%67,%68,%69,%70,%71,%72,%73,%74,%75,%76,%77,%78,%79,%80,%81,%82,%83,%84,%85,%86,%87,%88,%89,%90,%91,%92,%93,%94,%95}, {%96,%97,%98,%99}, %100, p, 1, 1, 0; }"
   : "+f"(d[0]), "+f"(d[1]), "+f"(d[2]), "+f"(d[3]), "+f"(d[4]), "+f"(d[5]), "+f"(d[6]), "+f"(d[7]), "+f"(d[8]), "+f"(d[9]), "+f"(d[10]), "+f"(d[11]), "+f"(d[12]), "+f"(d[13]), "+f"(d[14]), "+f"(d[15]), "+f"(d[16]), "+f"(d[17]), "+f"(d[18]), "+f"(d[19]), "+f"(d[20]), "+f"(d[21]), "+f"(d[22]), "+f"(d[23]), "+f"(d[24]), "+f"(d[25]), "+f"(d[26]), "+f"(d[27]), "+f"(d[28]), "+f"(d[29]), "+f"(d[30]), "+f"(d[31]), "+f"(d[32]), "+f"(d[33]), "+f"(d[34]), "+f"(d[35]), "+f"(d[36]), "+f"(d[37]), "+f"(d[38]), "+f"(d[39]), "+f"(d[40]), "+f"(d[41]), "+f"(d[42]), "+f"(d[43]), "+f"(d[44]), "+f"(d[45]), "+f"(d[46]), "+f"(d[47]), "+f"(d[48]), "+f"(d[49]), "+f"(d[50]), "+f"(d[51]), "+f"(d[52]), "+f"(d[53]), "+f"(d[54]), "+f"(d[55]), "+f"(d[56]), "+f"(d[57]), "+f"(d[58]), "+f"(d[59]), "+f"(d[60]), "+f"(d[61]), "+f"(d[62]), "+f"(d[63]), "+f"(d[64]), "+f"(d[65]), "+f"(d[66]), "+f"(d[67]), "+f"(d[68]), "+f"(d[69]), "+f"(d[70]), "+f"(d[71]), "+f"(d[72]), "+f"(d[73]), "+f"(d[74]), "+f"(d[75]), "+f"(d[76]), "+f"(d[77]), "+f"(d[78]), "+f"(d[79]), "+f"(d[80]), "+f"(d[81]), "+f"(d[82]), "+f"(d[83]), "+f"(d[84]), "+f"(d[85]), "+f"(d[86]), "+f"(d[87]), "+f"(d[88]), "+f"(d[89]), "+f"(d[90]), "+f"(d[91]), "+f"(d[92]), "+f"(d[93]), "+f"(d[94]), "+f"(d[95]) : "r"(a0), "r"(a1), "r"(a2), "r"(a3), "l"(db), "r"(sd));
}
__device__ __forceinline__ void wgmma_ss_8_10(float* d, uint64_t da, uint64_t db, int sd) {
  asm volatile("{ .reg .pred p; setp.ne.b32 p, %6, 0; wgmma.mma_async.sync.aligned.m64n8k16.f32.bf16.bf16 {%0,%1,%2,%3}, %4, %5, p, 1, 1, 1, 0; }"
   : "+f"(d[0]), "+f"(d[1]), "+f"(d[2]), "+f"(d[3]) : "l"(da), "l"(db), "r"(sd));
}
__device__ __forceinline__ void wgmma_ss_160_01(float* d, uint64_t da, uint64_t db, int sd) {
  asm volatile("{ .reg .pred p; setp.ne.b32 p, %82, 0; wgmma.mma_async.sync.aligned.m64n160k16.f32.bf16.bf16 {%0,%1,%2,%3,%4,%5,%6,%7,%8,%9,%10,%11,%12,%13,%14,%15,%16,%17,%18,%19,%20,%21,%22,%23,%24,%25,%26,%27,%28,%29,%30,%31,%32,%33,%34,%35,%36,%37,%38,%39,%40,%41,%42,%43,%44,%45,%46,%47,%48,%49,%50,%51,%52,%53,%54,%55,%56,%57,%58,%59,%60,%61,%62,%63,%64,%65,%66,%67,%68,%69,%70,%71,%72,%73,%74,%75,%76,%77,%78,%79}, %80, %81, p, 1, 1, 0, 1; }"
   : "+f"(d[0]), "+f"(d[1]), "+f"(d[2]), "+f"(d[3]), "+f"(d[4]), "+f"(d[5]), "+f"(d[6]), "+f"(d[7]), "+f"(d[8]), "+f"(d[9]), "+f"(d[10]), "+f"(d[11]), "+f"(d[12]), "+f"(d[13]), "+f"(d[14]), "+f"(d[15]), "+f"(d[16]), "+f"(d[17]), "+f"(d[18]), "+f"(d[19]), "+f"(d[20]), "+f"(d[21]), "+f"(d[22]), "+f"(d[23]), "+f"(d[24]), "+f"(d[25]), "+f"(d[26]), "+f"(d[27]), "+f"(d[28]), "+f"(d[29]), "+f"(d[30]), "+f"(d[31]), "+f"(d[32]), "+f"(d[33]), "+f"(d[34]), "+f"(d[35]), "+f"(d[36]), "+f"(d[37]), "+f"(d[38]), "+f"(d[39]), "+f"(d[40]), "+f"(d[41]), "+f"(d[42]), "+f"(d[43]), "+f"(d[44]), "+f"(d[45]), "+f"(d[46]), "+f"(d[47]), "+f"(d[48]), "+f"(d[49]), "+f"(d[50]), "+f"(d[51]), "+f"(d[52]), "+f"(d[53]), "+f"(d[54]), "+f"(d[55]), "+f"(d[56]), "+f"(d[57]), "+f"(d[58]), "+f"(d[59]), "+f"(d[60]), "+f"(d[61]), "+f"(d[62]), "+f"(d[63]), "+f"(d[64]), "+f"(d[65]), "+f"(d[66]), "+f"(d[67]), "+f"(d[68]), "+f"(d[69]), "+f"(d[70]), "+f"(d[71]), "+f"(d[72]), "+f"(d[73]), "+f"(d[74]), "+f"(d[75]), "+f"(d[76]), "+f"(d[77]), "+f"(d[78]), "+f"(d[79]) : "l"(da), "l"(db), "r"(sd));
}
__device__ __forceinline__ void wgmma_ss_192_11(float* d, uint64_t da, uint64_t db, int sd) {
  asm volatile("{ .reg .pred p; setp.ne.b32 p, %98, 0; wgmma.mma_async.sync.aligned.m64n192k16.f32.bf16.bf16 {%0,%1,%2,%3,%4,%5,%6,%7,%8,%9,%10,%11,%12,%13,%14,%15,%16,%17,%18,%19,%20,%21,%22,%23,%24,%25,%26,%27,%28,%29,%30,%31,%32,%33,%34,%35,%36,%37,%38,%39,%40,%41,%42,%43,%44,%45,%46,%47,%48,%49,%50,%51,%52,%53,%54,%55,%56,%57,%58,%59,%60,%61,%62,%63,%64,%65,%66,%67,%68,%69,%70,%71,%72,%73,%74,%75,%76,%77,%78,%79,%80,%81,%82,%83,%84,%85,%86,%87,%88,%89,%90,%91,%92,%93,%94,%95}, %96, %97, p, 1, 1, 1, 1; }"
   : "+f"(d[0]), "+f"(d[1]), "+f"(d[2]), "+f"(d[3]), "+f"(d[4]), "+f"(d[5]), "+f"(d[6]), "+f"(d[7]), "+f"(d[8]), "+f"(d[9]), "+f"(d[10]), "+f"(d[11]), "+f"(d[12]), "+f"(d[13]), "+f"(d[14]), "+f"(d[15]), "+f"(d[16]), "+f"(d[17]), "+f"(d[18]), "+f"(d[19]), "+f"(d[20]), "+f"(d[21]), "+f"(d[22]), "+f"(d[23]), "+f"(d[24]), "+f"(d[25]), "+f"(d[26]), "+f"(d[27]), "+f"(d[28]), "+f"(d[29]), "+f"(d[30]), "+f"(d[31]), "+f"(d[32]), "+f"(d[33]), "+f"(d[34]), "+f"(d[35]), "+f"(d[36]), "+f"(d[37]), "+f"(d[38]), "+f"(d[39]), "+f"(d[40]), "+f"(d[41]), "+f"(d[42]), "+f"(d[43]), "+f"(d[44]), "+f"(d[45]), "+f"(d[46]), "+f"(d[47]), "+f"(d[48]), "+f"(d[49]), "+f"(d[50]), "+f"(d[51]), "+f"(d[52]), "+f"(d[53]), "+f"(d[54]), "+f"(d[55]), "+f"(d[56]), "+f"(d[57]), "+f"(d[58]), "+f"(d[59]), "+f"(d[60]), "+f"(d[61]), "+f"(d[62]), "+f"(d[63]), "+f"(d[64]), "+f"(d[65]), "+f"(d[66]), "+f"(d[67]), "+f"(d[68]), "+f"(d[69]), "+f"(d[70]), "+f"(d[71]), "+f"(d[72]), "+f"(d[73]), "+f"(d[74]), "+f"(d[75]), "+f"(d[76]), "+f"(d[77]), "+f"(d[78]), "+f"(d[79]), "+f"(d[80]), "+f"(d[81]), "+f"(d[82]), "+f"(d[83]), "+f"(d[84]), "+f"(d[85]), "+f"(d[86]), "+f"(d[87]), "+f"(d[88]), "+f"(d[89]), "+f"(d[90]), "+f"(d[91]), "+f"(d[92]), "+f"(d[93]), "+f"(d[94]), "+f"(d[95]) : "l"(da), "l"(db), "r"(sd));
}

__device__ __forceinline__ void gemv_tile(uint32_t a0, uint32_t a1, uint32_t silu, uint32_t* dst, uint32_t tag, int lane) {
  float d[4];
  const uint64_t db = mkdesc(silu, 16, 128, 0), da0 = mkdesc(a0, 4096, 1024, 1), da1 = mkdesc(a1, 4096, 1024, 1);
  wg_fence();
#pragma unroll
  for (int kk = 0; kk < 8; kk++) wgmma_ss_8_10(d, (kk < 4 ? da0 : da1) + (kk & 3) * 128, db + kk * 2, kk);
  wg_commit();
  wg_wait<0>();
  regfence<4>(d);
  if (!(lane & 3)) { str(dst, tagf(d[0], tag)); str(dst + 8, tagf(d[2], tag)); }
}

#define HINT(x) x

__global__ void __cluster_dims__(2, 1, 1) __launch_bounds__(384, 1) fused_kernel(const __grid_constant__ Params p) {
  extern __shared__ __align__(1024) uint8_t smem_raw[];
  const uint32_t t_start = clk();
  const uint32_t sb = smem_u32(smem_raw);
  const uint32_t bars = sb + O_BAR;
  const int tid = threadIdx.x, lane = tid & 31;
  const int warp = __shfl_sync(0xffffffffu, tid >> 5, 0);
  const int b = blockIdx.x;
  const int rb = b >> 3, cg = (b >> 1) & 3, kh = b & 1, fs = kh * 4 + cg;
  const int vr = min(rb, 14) / 3, vt = min(rb, 14) % 3;
  const uint32_t ord = vr == 3 ? 0x42310 : vr == 4 ? 0x32410 : 0x43210;
  const int mu = b / 5;
  auto wmcol = [&](int pc) { return pc == 2 && mu >= 10 ? 2560 + mu * 64 : ((mu % 10) >> 1) * D_ + (2 * pc + (mu >= 10)) * 128 + (mu & 1) * 64; };
  auto BAR = [&](int i) { return bars + 8 * i; };
  auto until = [&](uint32_t t) { while (clk() - t_start < t) {} };
  auto loadQ = [&](int j) { mbar_expect(BAR(B_QF + j), 8192); bulk_ld(sb + qreg(j), g_qT + (size_t)(j * 128 + b) * S_ * 2, 8192, BAR(B_QF + j)); };
  if (tid == 0) TSTAMP(63);
  const uint32_t e0 = ldr(g_sync + Y_EP + b * 32 + lane * p.zero);
#define EPOCH uint32_t ep; asm volatile("add.u32 %0, %1, 1;" : "=r"(ep) : "r"(e0) : "memory")

  if (warp < 4) {
    asm volatile("setmaxnreg.dec.sync.aligned.u32 40;");
    const int hw = warp - 2;
    auto loadW = [&](int slot, int k0) {
      mbar_expect(BAR(B_FULL + slot), SLOT);
      tma3d(sb + slot * SLOT, &p.m_wg, 0, k0, fs * 3, BAR(B_FULL + slot));
      tma3d(sb + slot * SLOT + 12288, &p.m_wu, 0, k0, fs * 3, BAR(B_FULL + slot));
    };
    if (warp == 1) {
      auto loadS = [&](int j) { mbar_expect(BAR(B_SSM + j), 4096); bulk_ld(sb + bnd(j) + U_RAW, p.ssm + (size_t)(j * 128 + b) * S_, 4096, BAR(B_SSM + j)); };
      auto loadM = [&](int pc, uint32_t d0, uint32_t d1) {
        if (b < 100) {
          mbar_expect(BAR(B_WM + pc), 16384);
          tma2d(sb + d0, &p.m_wm, wmcol(pc), (b % 5) * 128, BAR(B_WM + pc));
          tma2d(sb + d1, &p.m_wm, wmcol(pc), (b % 5) * 128 + 64, BAR(B_WM + pc));
        }
      };
      auto loadK = [&](int n) {
        const uint32_t d = sb + kreg(n), bar = BAR(B_KIN + n);
        const int ch = n * 128 + (b & 3) * 32, tg = (b >> 2) * 8;
        mbar_expect(bar, 9984);
        tma3d(d, &p.m_k, ch, tg, 0, bar);
        tma3d(d + SLOT, &p.m_v, ch, tg, 0, bar);
        tma3d(d + 4096, &p.m_kh, ch, tg - 1, 5, bar);
        bulk_ld(d + 5632, p.shift + ch * 4, 256, bar);
      };
      auto pfW = [&](int i0, int i1) {
#pragma unroll 1
        for (int i = i0; i < i1; i++) bulk_pf(((b & 1) ? p.wu : p.wg) + (i * 64 + (b >> 1)) * F_, 3072);
      };
      if (lane == 0) {
#pragma unroll
        for (int j = 0; j < 5; j++) mbar_init(BAR(B_SSM + j), 1);
        asm volatile("fence.mbarrier_init.release.cluster;" ::: "memory");
        loadS(0);
        TSTAMP(62);
      }
      __syncwarp();
      bar_sync(1, 384);
      asm volatile("barrier.cluster.arrive.relaxed.aligned;" ::: "memory");
      if (lane == 0) {
        mbar_expect(BAR(B_RED), 20480);
        mbar_expect(BAR(B_QIN), 20480);
        until(T_K1); loadK(1);
        until(T_S1); loadS(1);
        until(T_K2); loadK(2);
        until(T_Q);
        asm volatile("cp.async.bulk.tensor.5d.shared::cluster.global.mbarrier::complete_tx::bytes [%0], [%1, {%4, %4, %3, %4, %4}], [%2];" ::"r"(sb + O_REG), "l"(&p.m_q),
                     "r"(BAR(B_QIN)), "r"(b * 4), "r"(0) : "memory");
        TSTAMP(78);
        until(T_S2); loadS(2);
        until(T_K3); loadK(3);
        until(T_WM0); loadM(0, 2 * SLOT + 24576, 3 * SLOT + 24576);
        until(T_S3); loadS(3);
        until(T_K4); loadK(4);
        until(T_S4); loadS(4);
        until(T_W0); pfW(0, 2);
        until(T_WM1); loadM(1, SLOT + 16384, SLOT + 24576);
        until(T_REST);
        pfW(2, 4);
        mbar_wait(BAR(B_QST), 0);
        loadM(2, O_REG, O_REG + 8192);
        pfW(4, 10);
#pragma unroll 1
        for (int i = 0; i < 4; i++) bulk_pf(p.w2 + (b * 4 + i) * 1920, 3840);
        TSTAMP(61);
      }
      EPOCH;
      if (lane == 0) poll_ge(g_sync + Y_MOD + (vr >> 1) * 32, ep * 100);
      __syncwarp();
      {
        float4 s = gather4<5>(g_mod + 4 * D_ + vr * 128 + lane * 4, 6 * D_, ep);
        const uint32_t a = sb + O_CS + (lane >> 1) * 32 + (lane & 1) * 8;
        sts64(a, pack2(1.f + rbf(s.x), 1.f + rbf(s.y)), pack2(1.f + rbf(s.z), 1.f + rbf(s.w)));
        s = gather4<5>(g_mod + 3 * D_ + vr * 128 + lane * 4, 6 * D_, ep);
        sts64(a + 16, pack2(s.x, s.y), pack2(s.z, s.w));
        fence_async_smem();
        __syncwarp();
        if (lane == 0) { mbar_arrive(BAR(B_CS)); TSTAMP(11); poll_ge(g_sync + Y_MOD + 64, ep * 100); }
        __syncwarp();
      }
#pragma unroll 1
      for (int i = 0; i < 2; i++) {
        if (i == 0 || lane < 8) {
          const float4 s = gather4<5>(g_mod + 5 * D_ + cg * 160 + (i ? (~cg & 1) * 128 : (cg & 1) * 32) + lane * 4, 6 * D_, ep);
          sts128(sb + O_GB + i * 512 + lane * 16, __float_as_uint(rbf(s.x)), __float_as_uint(rbf(s.y)), __float_as_uint(rbf(s.z)), __float_as_uint(rbf(s.w)));
        }
      }
      __syncwarp();
      if (lane == 0) poll_ge(g_sync + Y_VV + fs * 32, ep * 32);
      __syncwarp();
#pragma unroll 1
      for (int i = 0; i < 3; i++) {
        uint32_t v[20], bad;
        int it = 0;
        const uint32_t* g = g_vv + fs * 1920 + i * 128 + lane;
        do {
          bad = 0;
#pragma unroll
          for (int k = 0; k < 20; k++) v[k] = ldr(g + ((k % 5) * 384 + (k / 5) * 32));
#pragma unroll
          for (int k = 0; k < 20; k++) bad |= v[k] ^ ep;
        } while ((bad & 1) && ++it < 100000);
#pragma unroll
        for (int k = 0; k < 4; k++) sts128(sb + O_BP + (i * 128 + k * 32 + lane) * 16, v[5 * k], v[5 * k + 1], v[5 * k + 2], hadd2(v[5 * k + 3], v[5 * k + 4]));
      }
      fence_async_smem();
      __syncwarp();
      if (lane == 0) { mbar_arrive(BAR(B_VV)); TSTAMP(37); }
      asm volatile("barrier.cluster.wait.aligned;" ::: "memory");
    } else if (warp == 0) {
      if (lane < 14) asm volatile("prefetch.tensormap [%0];" ::"l"(&p.m_k + lane) : "memory");
      bar_sync(1, 384);
      asm volatile("barrier.cluster.arrive.relaxed.aligned;" ::: "memory");
      EPOCH;
      {
        const uint32_t* f = g_sync + (lane < 5 ? Y_KV + (lane * 4 + (b >> 5)) * 32 : Y_Q);
        const uint32_t target = ep * (lane < 5 ? 32 : 128);
        uint32_t pend = 63;
        int it = 0;
        do {
          uint32_t v = target;
          HINT(if ((pend >> lane) & 1) v = ldr(f));
          uint32_t m = __ballot_sync(0xffffffffu, (int)(v - target) >= 0 || ++it > 100000) & pend;
          pend &= ~m;
          for (; m; m &= m - 1) {
            const int j = __ffs(m) - 1;
            if (lane == 0) {
              if (j < 5) {
                TSTAMP(2 + j);
                mbar_expect(BAR(B_KV + j), 4096);
                bulk_ld(sb + bnd(j) + U_KV, g_kvT + (size_t)(j * 128 + b) * S_, 4096, BAR(B_KV + j));
              } else { TSTAMP(0); loadQ(0); loadQ(1); }
            }
          }
        } while (pend);
      }
      if (lane == 0) {
        uint32_t m = 0;
        int slot = 2, ph = 0;
#pragma unroll 1
        for (int s = 0; s < 20; s++) {
          const int rd = (ord >> (s & 28)) & 7, k0 = rd * 128 + (s & 3) * 32;
          mbar_wait(BAR(B_EMPTY + slot), ph);
          loadW(slot, k0);
          if (s == 0) TSTAMP(10);
          if (!(s & 3)) m = 0;
          if (!((m >> (s & 3)) & 1)) m = poll4(g_sync + Y_X1 + rd * 64 + (rb >> 3) * 32, ep * 32, 1u << (s & 3));
          if (s == 0) TSTAMP(19);
          if (s == 16) TSTAMP(1);
          tma3d(sb + slot * SLOT + 24576, &p.m_xa, 0, k0, (rb >> 3) * 32 + 16 + (rb & 7) * 2, BAR(B_FULL + slot));
          if (++slot == 6) { slot = s == 3 ? 2 : 0; ph ^= 1; }
        }
#pragma unroll 1
        for (int s = 0; s < 12; s++) {
          const int e = s % 5;
          if (s >= 5) mbar_wait(BAR(B_W2E + e), s >= 10);
          else if (s != 3) mbar_wait(BAR(B_EMPTY + s + 1), 0);
          const uint32_t d = sb + w2entry(e), st = e == 3 ? SLOT : 8192;
          const int k0 = kh * 768 + (s < 3 ? cg * 192 + s * 64 : ((cg + 1 + s % 3) & 3) * 192 + (s / 3 - 1) * 64), c0 = cg * 160 + (cg & 1) * 32;
          mbar_expect(BAR(B_W2F + e), 24576);
          tma2d(d, &p.m_w2a, c0, k0, BAR(B_W2F + e));
          tma2d(d + st, &p.m_w2a, c0 + 64, k0, BAR(B_W2F + e));
          tma3d(d + 2 * st, &p.m_w2b, 0, k0, cg * 5 + (~cg & 1) * 4, BAR(B_W2F + e));
        }
        mbar_wait(BAR(B_W2E + 2), 1);
      }
      __syncwarp();
      asm volatile("barrier.cluster.wait.aligned;" ::: "memory");
      if (lane == 0)
        asm volatile("{ .reg .b32 r; mapa.shared::cluster.u32 r, %0, %1; mbarrier.arrive.shared::cluster.b64 _, [r]; }" ::"r"(BAR(B_RDY)), "r"(kh ^ 1) : "memory");
    } else {
      const uint32_t dv = __ldg((const uint16_t*)p.ssmD + min(lane, 4) * 128 + b);
      const uint32_t cv = __ldg((const uint32_t*)p.c + (b % 5) * 64 + (tid & 63));
#pragma unroll
      for (int j = 0; j < 5; j++) {
        if (tid < 83) sts128(sb + bnd(j) + (lane < 17 ? U_KV + 4096 + lane * 16 : lane == 17 ? U_RAW - 16 : U_ODD - 16), 0, 0, 0, 0);
      }
      bar_sync(1, 384);
      asm volatile("barrier.cluster.arrive.relaxed.aligned;" ::: "memory");
      sts32(sb + O_SILU + (tid & 63) * 4, pack2(__fdividef(blo(cv), 1.f + __expf(-blo(cv))), __fdividef(bhi(cv), 1.f + __expf(-bhi(cv)))));
      fence_async_smem();
#pragma unroll 1
      for (int j = 0; j < 5; j++) {
        const uint32_t ra = sb + bnd(j) + U_RAW + hw * 2048 + lane * 16;
        const float dj = blo(__shfl_sync(0xffffffffu, dv, j));
        mbar_wait(BAR(B_SSM + j), 0);
        if (tid == 64 && j == 0) TSTAMP(77);
#pragma unroll
        for (int i = 0; i < 4; i++) {
          uint4 w = lds128(ra + i * 512);
          const uint32_t pv = lds32(ra + i * 512 - 4);
          if (i == 0 && tid == 64) { w.x = prmt(pack2(blo(w.x) + dj, 0.f), w.x, 0x7610); sts32(ra, w.x); }
          sts128(ra + (U_ODD - U_RAW) + i * 512, prmt(pv, w.x, 0x5432), prmt(w.x, w.y, 0x5432), prmt(w.y, w.z, 0x5432), prmt(w.z, w.w, 0x5432));
        }
        __syncwarp();
        if (lane == 0) mbar_arrive(BAR(B_PL + j));
        if (tid == 64) TSTAMP(32 + j);
      }
      EPOCH;
      uint32_t yy = 0;
#pragma unroll 1
      for (int j = 0; j < 5; j++) {
        if (!(j & 1)) {
          if (lane == 0) poll_ge(g_sync + Y_MOD + j * 16, ep * 100);
          __syncwarp();
          const int sg = lane & 3;
          const float x = rbf(gather1(g_mod + (sg + (sg == 3)) * D_ + min(j + ((lane >> 2) & 1), 4) * 128 + b, ep));
          const float ga = __shfl_sync(0xffffffffu, x, (lane & 28) + 2);
          const float y = sg == 0 ? ga * x : sg == 1 ? ga * rbf(1.f + x) : 1.f + x;
          yy = pack2(y, y);
          if (tid == 64 && j < 4) TSTAMP(7 + (j >> 1));
        }
        const uint32_t ma = __shfl_sync(0xffffffffu, yy, (j & 1) * 4 + 1), mb = __shfl_sync(0xffffffffu, yy, (j & 1) * 4), mc = __shfl_sync(0xffffffffu, yy, (j & 1) * 4 + 3);
        uint32_t pa = sb + bnd(j) + hw * 8192 + lane * 16, qa = sb + qreg(j) + hw * 4096 + lane * 32 + (lane & 4) * 4;
        __nv_bfloat16* gx = g_x1T + (size_t)(j * 128 + b) * 4096 + hw * 2048 + lane * 8;
        mbar_wait(BAR(B_QF + j), 0);
        mbar_wait(BAR(B_Y + j), 0);
#pragma unroll 1
        for (int i = 0; i < 4; i++) {
          const uint4 p0 = lds128(pa), p1 = lds128(pa + 2048), p2 = lds128(pa + 4096), p3 = lds128(pa + 6144);
          const uint32_t y0 = hadd2(hadd2(p0.x, p1.x), hadd2(p2.x, p3.x)), y1 = hadd2(hadd2(p0.y, p1.y), hadd2(p2.y, p3.y));
          const uint32_t y2 = hadd2(hadd2(p0.z, p1.z), hadd2(p2.z, p3.z)), y3 = hadd2(hadd2(p0.w, p1.w), hadd2(p2.w, p3.w));
          uint4 n = lds128(qa ^ 16), u = lds128(qa);
          if ((n.w ^ ep) & 1) {
            refetch(g_qT + (gx - g_x1T) + i * 256 + lane * 8, 28 - (lane & 4) * 4, qa & ~16u, ep);
            u = lds128(qa); n = lds128(qa ^ 16);
          }
          const uint32_t x0 = hfma2(hfma2(u.z, ma, mb), y0, u.x), x1 = hfma2(hfma2(u.w, ma, mb), y1, u.y);
          const uint32_t x2 = hfma2(hfma2(n.z, ma, mb), y2, n.x), x3 = hfma2(hfma2(n.w, ma, mb), y3, n.y);
          uint32_t s0 = hmul2(x0, mc), s1 = hmul2(x1, mc), s2 = hmul2(x2, mc), s3 = hmul2(x3, mc);
          const uint32_t od = lane & 1;
          if ((rb & 3) == 0) s0 = settag(s0, od, ep);
          if ((rb & 3) == 1) s1 = settag(s1, od, ep);
          if ((rb & 3) == 2) s2 = settag(s2, od, ep);
          if ((rb & 3) == 3) s3 = settag(s3, od, ep);
          __syncwarp();
          stg128(gx + 1024, s0, s1, s2, s3);
          stg128(gx, x0, x1, x2, settag(x3, od, ep));
          pa += 512; qa += 1024; gx += 256;
        }
        __syncwarp();
        if (lane == 0) {
          hint_add(g_sync + Y_X1 + j * 64 + hw * 32 + (b >> 5));
          if (j != 2) mbar_arrive(BAR(B_EMPTY + (j < 2 ? j + 4 : j - 3)));
        }
        if (tid == 64) TSTAMP(12 + j);
      }
      {
        bar_sync(4, 64);
        if (lane < 5) poll_ge(g_sync + Y_X1 + ((cg * 5 + lane) >> 2) * 64 + (rb >> 3) * 32 + ((cg * 5 + lane) & 3), ep * 32);
        __syncwarp();
        float s1a, s2a, s1b, s2b;
        uint32_t bad, ph = 0;
        do {
          if (lane == 0) {
            mbar_expect(BAR(B_X1 + hw), 10240);
            tma2d(sb + O_REG + hw * 10240, &p.m_xr, (rb >> 3) * 2048 + (rb & 7) * 128 + (kh ^ 1) * 64, cg * 160 + hw * 80, BAR(B_X1 + hw));
          }
          s1a = s2a = s1b = s2b = 0.f;
          bad = 0;
          mbar_wait(BAR(B_X1 + hw), ph & 1);
          if (tid == 64) TSTAMP(58);
#pragma unroll 1
          for (int k = 0; k < 8; k++) {
            const uint32_t a = ((sb + O_REG + hw * 10240 + lane * 4) ^ (k << 4)) + k * 128;
            uint32_t v[10];
#pragma unroll
            for (int i = 0; i < 10; i++) v[i] = lds32(a + i * 1024);
#pragma unroll
            for (int i = 0; i < 10; i++) { const float x = blo(v[i]), y = bhi(v[i]); s1a += x; s2a = fmaf(x, x, s2a); s1b += y; s2b = fmaf(y, y, s2b); bad |= v[i] ^ ep; }
          }
        } while ((__ballot_sync(0xffffffffu, bad & 1) & 0x80808080u) && ++ph < 1000);
        if (hw) sts128(sb + O_TMP + lane * 16, __float_as_uint(s1a), __float_as_uint(s2a), __float_as_uint(s1b), __float_as_uint(s2b));
        bar_sync(4, 64);
        if (!hw) {
          const float4 o = lds128f(sb + O_TMP + lane * 16);
          asm volatile("st.relaxed.gpu.global.v4.u32 [%0], {%1,%2,%3,%4};" ::"l"(g_st + ((rb * 2 + (kh ^ 1)) * 4 + cg) * 128 + lane * 4), "r"(tagf(s1a + o.x, ep)),
                       "r"(tagf(s2a + o.y, ep)), "r"(tagf(s1b + o.z, ep)), "r"(tagf(s2b + o.w, ep)) : "memory");
        }
        const float4 s = gather4<4>(g_st + (rb * 2 + hw) * 512 + lane * 4, 128, ep);
        const float ma = s.x * (1.f / D_), mb = s.z * (1.f / D_);
        const uint32_t pa = pack2(-ma, sqrtf(fmaxf(s.y * (1.f / D_) - ma * ma, 0.f) + 1e-5f)), pb = pack2(-mb, sqrtf(fmaxf(s.w * (1.f / D_) - mb * mb, 0.f) + 1e-5f));
        sts128(sb + O_ST + hw * 512 + lane * 16, pa, __float_as_uint(__fdividef(1.f, bhi(pa) * bhi(pa))), pb, __float_as_uint(__fdividef(1.f, bhi(pb) * bhi(pb))));
        __syncwarp();
        if (lane == 0) mbar_arrive(BAR(B_ST + hw));
        if (tid == 64) TSTAMP(52);
      }
      if (lane == 0) {
        const uint32_t reg = sb + (hw ? 0 : 4 * SLOT);
        const int row0 = rb * 128 + (hw ^ kh) * 64;
        uint32_t* flags = g_sync + Y_H + (rb * 4 + kh * 2 + hw) * 32;
#pragma unroll 1
        for (int i = 0; i < 3; i++) {
          mbar_wait(BAR(B_STAGED + hw * 3 + i), 0);
          tma2d_store(&p.m_h, reg + i * 8192, fs * 192 + i * 64, row0);
          bulk_commit();
          if (i) { bulk_wait<1>(); str(flags + cg, ep * 4 + i - 1); }
        }
        bulk_wait<0>();
        str(flags + cg, ep * 4 + 2);
        TSTAMP(17 + hw);
        uint32_t m = 0;
#pragma unroll 1
        for (int i = 0; i < 9; i++) {
          const int oc = (cg + 1 + i % 3) & 3, e = (i + 3) & 3;
          if (i % 3 == 0) m = 0;
          HINT(if (!(m & (1u << oc))) m = poll4(flags, ep * 4 + i / 3, 1u << oc));
          if (i >= 4) mbar_wait(BAR(B_HE + hw * 4 + e), ((i >> 2) - 1) & 1);
          mbar_expect(BAR(B_HF + hw * 4 + e), 8192);
          tma2d(reg + e * 8192, &p.m_h, kh * 768 + oc * 192 + (i / 3) * 64, row0, BAR(B_HF + hw * 4 + e));
        }
      }
      __syncwarp();
      asm volatile("barrier.cluster.wait.aligned;" ::: "memory");
    }
  } else {
    const int isE = warp >= 8 ? 1 : 0;
    const int w = warp & 3, r = lane >> 2, c = lane & 3;
    const bool lead = (tid & 127) == 0;
    const int tb = b >> 2;
    if (isE) {
      const int u = tid & 127, t = tb * 64 + r * 8 + w, th = t - (w == 3 ? 0 : 3);
      const uint32_t d = sb + kreg(0) + (u >> 2) * 64 + ((c ^ (r >> 1)) << 4);
      const int o = t * D_ + (b & 3) * 32 + c * 8;
      cpa16(d, p.k + o, 16); cpa16(d + SLOT, p.v + o, 16);
      cpa16(d + 2048, p.k + o + 4 * D_, 16); cpa16(d + SLOT + 2048, p.v + o + 4 * D_, 16);
      if (u < 112) cpa16(w == 3 ? sb + kreg(0) + 5632 + lane * 16 : d + 4096, w == 3 ? p.shift + (b & 3) * 128 + lane * 8 : p.k + (th < 0 ? o : o - 3 * D_), th < 0 ? 0 : 16);
      if (lead) TSTAMP(74);
    } else {
      if (lane == 0) {
#pragma unroll
        for (int i = 0; i < 21; i++) mbar_init(BAR(w + 4 * i), i < 4 ? 2 : i < 7 ? 4 : 1);
        asm volatile("fence.mbarrier_init.release.cluster;" ::: "memory");
      }
      __syncwarp();
      if (lead) TSTAMP(76);
    }
    bar_sync(1, 384);
    if (tid == 256) TSTAMP(75);
    asm volatile("setmaxnreg.inc.sync.aligned.u32 232;");
    asm volatile("barrier.cluster.arrive.relaxed.aligned;" ::: "memory");
    EPOCH;
    if (isE) {
      asm volatile("cp.async.wait_all;" ::: "memory");
      bar_sync(6, 128);
    }
#define STEP(i, ln, kv, gv, cv) ((uint64_t)(ln | (kv + 1) << 1 | (gv + 1) << 4 | (cv + 1) << 6) << (10 * i))
#pragma unroll 1
    for (uint64_t todo = isE ? SCHED_E : SCHED_L; todo; todo >>= 10) {
      if (todo & 1) {
        uint32_t x[40];
        mbar_wait(BAR(B_QIN), 0);
        if (lead) TSTAMP(9);
        const uint32_t qa = sb + O_REG + (lane & 15) * 128 + (((2 * w + (lane >> 4)) ^ (lane & 7)) << 4);
#pragma unroll
        for (int i = 0; i < 10; i++) ldsm4t(qa + i * 2048, x[4 * i], x[4 * i + 1], x[4 * i + 2], x[4 * i + 3]);
        float z[8] = {0.f, 0.f, 0.f, 0.f, 0.f, 0.f, 0.f, 0.f};
#pragma unroll
        for (int i = 0; i < 40; i++) {
          const float f = blo(x[i]), g = bhi(x[i]);
          float* y = z + (i & 1) * 4;
          y[0] += f; y[1] = fmaf(f, f, y[1]); y[2] += g; y[3] = fmaf(g, g, y[3]);
        }
        if (lane == 0) mbar_arrive(BAR(B_QST));
        halve<8>(z, lane, 16); halve<4>(z, lane, 8); halve<2>(z, lane, 4);
        sts32(sb + O_TMP + lane * 16 + w * 4, __float_as_uint(z[0]));
        bar_sync(5 + isE, 128);
        const float4 t = lds128f(sb + O_TMP + lane * 16);
        const float sm = (t.x + t.y + t.z + t.w) * (1.f / D_), so = __shfl_xor_sync(0xffffffffu, sm, 4);
        const float mean = (lane & 4) ? so : sm, rs = rsqrtf(fmaxf(((lane & 4) ? sm : so) - mean * mean, 0.f) + 1e-5f), u = (lane & 4) ? -mean * rs : rs;
#pragma unroll
        for (int i = 0; i < 8; i++) z[i] = __shfl_sync(0xffffffffu, u, i * 4 + c);
        __nv_bfloat16* g = g_qT + (w * 16 + r) * 4096 + b * 32 + ((c ^ (b >> 1)) & 1) * 8 + (c & 2) * 8;
#pragma unroll
        for (int i = 0; i < 20; i++)
          stg128(g + ((i >> 1) * 64 + (i & 1) * 8) * 4096, x[2 * i], x[2 * i + 1], pack2(fmaf(blo(x[2 * i]), z[0], z[1]), fmaf(bhi(x[2 * i]), z[2], z[3])),
                 settag(pack2(fmaf(blo(x[2 * i + 1]), z[4], z[5]), fmaf(bhi(x[2 * i + 1]), z[6], z[7])), c & 1, ep));
        bar_sync(5 + isE, 128);
        if (lead) { hint_add(g_sync + Y_Q); TSTAMP(59); }
      }
      if (todo & 14) {
        const int n = ((todo >> 1) & 7) - 1, tg = lane & 7;
        const uint32_t a = sb + kreg(n) + tg * 64 + ((w ^ (tg >> 1)) << 4) + (lane >> 3) * 4;
        if (n) mbar_wait(BAR(B_KIN + n), 0);
        if (lead) TSTAMP(69 + n);
        uint32_t kk[11], x[8];
        const uint4 sw = lds128(sb + kreg(n) + 5632 + w * 64 + (lane & 24) * 2);
#pragma unroll
        for (int i = 0; i < 11; i++) kk[i] = lds32(a + (i < 3 ? 4096 + i * 512 : (i - 3) * 512));
#pragma unroll
        for (int i = 0; i < 8; i++) x[7 - i] = lds32(a + SLOT + i * 512);
        const uint32_t w0 = prmt(sw.x, sw.z, 0x5410), w1 = prmt(sw.x, sw.z, 0x7632), w2 = prmt(sw.y, sw.w, 0x5410), w3 = prmt(sw.y, sw.w, 0x7632);
#pragma unroll
        for (int i = 0; i < 8; i++) x[7 - i] = hmul2(hfma2(kk[i + 3], w0, hfma2(kk[i + 2], w1, hfma2(kk[i + 1], w2, hmul2(kk[i], w3)))), x[7 - i]);
        const int tw = (~tb & 7) ^ ((~lane & 1) << 2);
#pragma unroll
        for (int i = 0; i < 4; i++) x[2 * i] = settag(x[2 * i], tw == i ? 0x00010001u : 0u, -(ep & 1));
        __nv_bfloat16* g = g_kvT + (n * 128 + (b & 3) * 32 + w * 8 + (lane >> 3) * 2) * S_ + 2040 - tb * 64 - tg * 8;
        stg128(g, prmt(x[0], x[1], 0x5410), prmt(x[2], x[3], 0x5410), prmt(x[4], x[5], 0x5410), prmt(x[6], x[7], 0x5410));
        stg128(g + S_, prmt(x[0], x[1], 0x7632), prmt(x[2], x[3], 0x7632), prmt(x[4], x[5], 0x7632), prmt(x[6], x[7], 0x7632));
        bar_sync(5 + isE, 128);
        if (lead) {
          hint_add(g_sync + Y_KV + (n * 4 + (b & 3)) * 32);
          if (n > 2) { mbar_arrive(BAR(B_EMPTY + 2)); mbar_arrive(BAR(B_EMPTY + 3)); }
          TSTAMP(64 + n);
        }
      }
      if (todo & 48) {
        const int pc = ((todo >> 4) & 3) - 1;
        if (b < 100) {
          const uint32_t a0 = sb + (pc == 0 ? 2 * SLOT + 24576 : pc == 1 ? SLOT + 16384 : O_REG);
          mbar_wait(BAR(B_PL), 0);
          mbar_wait(BAR(B_WM + pc), 0);
          if (lead) TSTAMP(81 + pc);
          gemv_tile(a0, a0 + (pc == 0 ? SLOT : 8192), sb + O_SILU, g_mod + (b % 5) * 6 * D_ + w * 16 + r + wmcol(pc), ep, lane);
        }
        bar_sync(5 + isE, 128);
        if (lead) {
          if (b < 100) hint_add(g_sync + Y_MOD + pc * 32);
          TSTAMP(pc == 2 ? 60 : 20 + pc);
          if (pc) {
            mbar_wait(BAR(B_QF), 0);
            if (pc == 1) loadQ(2); else mbar_wait(BAR(B_QST), 0);
            loadQ(pc + 2);
          }
        }
        __syncwarp();
      }
      if (todo & 448) {
        const int j = ((todo >> 6) & 7) - 1;
        const uint32_t ub = sb + bnd(j), sa = ub + ((r & 1) ? U_RAW : U_ODD) + 4 * (8 * w + (r >> 1) - 3 + c);
        uint32_t A[64];
        float d[128];
        mbar_wait(BAR(B_PL + j), 0);
#pragma unroll
        for (int g = 0; g < 16; g++) { A[4 * g] = lds32(sa + g * 256); A[4 * g + 1] = lds32(sa + g * 256 + 128); A[4 * g + 2] = lds32(sa + g * 256 + 16); A[4 * g + 3] = lds32(sa + g * 256 + 144); }
        mbar_wait(BAR(B_KV + j), 0);
        if ((lds32(ub + U_KV + (tid & 127) * 32 + r * 4) ^ ep) & 1) refetch(g_kvT + (j * 128 + b) * S_ + (tid & 127) * 16, r * 4, ub + U_KV + (tid & 127) * 32, ep);
        __syncwarp();
        bar_sync(5 + isE, 128);
        if (lead) TSTAMP(53 + j);
        const uint64_t db = mkdesc(ub + U_KV, 16, 128, 0);
        wg_fence();
        wgmma_rs_32_0(d + 0, A[0], A[1], A[2], A[3], db + 0, 0);
        wgmma_rs_32_0(d + 16, A[0], A[1], A[2], A[3], db + 32, 0);
        wgmma_rs_32_0(d + 32, A[0], A[1], A[2], A[3], db + 64, 0);
        wgmma_rs_32_0(d + 48, A[0], A[1], A[2], A[3], db + 96, 0);
        wgmma_rs_32_0(d + 0, A[4], A[5], A[6], A[7], db + 16, 1);
        wgmma_rs_32_0(d + 16, A[4], A[5], A[6], A[7], db + 48, 1);
        wgmma_rs_32_0(d + 32, A[4], A[5], A[6], A[7], db + 80, 1);
        wgmma_rs_32_0(d + 48, A[4], A[5], A[6], A[7], db + 112, 1);
        wgmma_rs_32_0(d + 0, A[8], A[9], A[10], A[11], db + 32, 1);
        wgmma_rs_32_0(d + 16, A[8], A[9], A[10], A[11], db + 64, 1);
        wgmma_rs_32_0(d + 32, A[8], A[9], A[10], A[11], db + 96, 1);
        wgmma_rs_32_0(d + 64, A[0], A[1], A[2], A[3], db + 128, 0);
        wgmma_rs_32_0(d + 0, A[12], A[13], A[14], A[15], db + 48, 1);
        wgmma_rs_32_0(d + 16, A[12], A[13], A[14], A[15], db + 80, 1);
        wgmma_rs_32_0(d + 32, A[12], A[13], A[14], A[15], db + 112, 1);
        wgmma_rs_32_0(d + 48, A[8], A[9], A[10], A[11], db + 128, 1);
        wgmma_rs_32_0(d + 0, A[16], A[17], A[18], A[19], db + 64, 1);
        wgmma_rs_32_0(d + 16, A[16], A[17], A[18], A[19], db + 96, 1);
        wgmma_rs_32_0(d + 32, A[16], A[17], A[18], A[19], db + 128, 1);
        wgmma_rs_32_0(d + 64, A[4], A[5], A[6], A[7], db + 144, 1);
        wgmma_rs_32_0(d + 0, A[20], A[21], A[22], A[23], db + 80, 1);
        wgmma_rs_32_0(d + 16, A[20], A[21], A[22], A[23], db + 112, 1);
        wgmma_rs_32_0(d + 48, A[12], A[13], A[14], A[15], db + 144, 1);
        wgmma_rs_32_0(d + 32, A[20], A[21], A[22], A[23], db + 144, 1);
        wgmma_rs_32_0(d + 0, A[24], A[25], A[26], A[27], db + 96, 1);
        wgmma_rs_32_0(d + 16, A[24], A[25], A[26], A[27], db + 128, 1);
        wgmma_rs_32_0(d + 80, A[0], A[1], A[2], A[3], db + 160, 0);
        wgmma_rs_32_0(d + 64, A[8], A[9], A[10], A[11], db + 160, 1);
        wgmma_rs_32_0(d + 0, A[28], A[29], A[30], A[31], db + 112, 1);
        wgmma_rs_32_0(d + 16, A[28], A[29], A[30], A[31], db + 144, 1);
        wgmma_rs_32_0(d + 48, A[16], A[17], A[18], A[19], db + 160, 1);
        wgmma_rs_32_0(d + 32, A[24], A[25], A[26], A[27], db + 160, 1);
        wgmma_rs_32_0(d + 0, A[32], A[33], A[34], A[35], db + 128, 1);
        wgmma_rs_32_0(d + 16, A[32], A[33], A[34], A[35], db + 160, 1);
        wgmma_rs_32_0(d + 80, A[4], A[5], A[6], A[7], db + 176, 1);
        wgmma_rs_32_0(d + 64, A[12], A[13], A[14], A[15], db + 176, 1);
        wgmma_rs_32_0(d + 0, A[36], A[37], A[38], A[39], db + 144, 1);
        wgmma_rs_32_0(d + 48, A[20], A[21], A[22], A[23], db + 176, 1);
        wgmma_rs_32_0(d + 32, A[28], A[29], A[30], A[31], db + 176, 1);
        wgmma_rs_32_0(d + 16, A[36], A[37], A[38], A[39], db + 176, 1);
        wgmma_rs_32_0(d + 0, A[40], A[41], A[42], A[43], db + 160, 1);
        wgmma_rs_32_0(d + 96, A[0], A[1], A[2], A[3], db + 192, 0);
        wgmma_rs_32_0(d + 80, A[8], A[9], A[10], A[11], db + 192, 1);
        wgmma_rs_32_0(d + 64, A[16], A[17], A[18], A[19], db + 192, 1);
        wgmma_rs_32_0(d + 0, A[44], A[45], A[46], A[47], db + 176, 1);
        wgmma_rs_32_0(d + 48, A[24], A[25], A[26], A[27], db + 192, 1);
        wgmma_rs_32_0(d + 32, A[32], A[33], A[34], A[35], db + 192, 1);
        wgmma_rs_32_0(d + 16, A[40], A[41], A[42], A[43], db + 192, 1);
        wgmma_rs_32_0(d + 0, A[48], A[49], A[50], A[51], db + 192, 1);
        wgmma_rs_32_0(d + 96, A[4], A[5], A[6], A[7], db + 208, 1);
        wgmma_rs_32_0(d + 80, A[12], A[13], A[14], A[15], db + 208, 1);
        wgmma_rs_32_0(d + 64, A[20], A[21], A[22], A[23], db + 208, 1);
        wgmma_rs_32_0(d + 48, A[28], A[29], A[30], A[31], db + 208, 1);
        wgmma_rs_32_0(d + 32, A[36], A[37], A[38], A[39], db + 208, 1);
        wgmma_rs_32_0(d + 16, A[44], A[45], A[46], A[47], db + 208, 1);
        wgmma_rs_32_0(d + 0, A[52], A[53], A[54], A[55], db + 208, 1);
        wgmma_rs_32_0(d + 112, A[0], A[1], A[2], A[3], db + 224, 0);
        wgmma_rs_32_0(d + 96, A[8], A[9], A[10], A[11], db + 224, 1);
        wgmma_rs_32_0(d + 80, A[16], A[17], A[18], A[19], db + 224, 1);
        wgmma_rs_32_0(d + 64, A[24], A[25], A[26], A[27], db + 224, 1);
        wgmma_rs_32_0(d + 48, A[32], A[33], A[34], A[35], db + 224, 1);
        wgmma_rs_32_0(d + 32, A[40], A[41], A[42], A[43], db + 224, 1);
        wgmma_rs_32_0(d + 16, A[48], A[49], A[50], A[51], db + 224, 1);
        wgmma_rs_32_0(d + 0, A[56], A[57], A[58], A[59], db + 224, 1);
        wgmma_rs_32_0(d + 112, A[4], A[5], A[6], A[7], db + 240, 1);
        wgmma_rs_32_0(d + 96, A[12], A[13], A[14], A[15], db + 240, 1);
        wgmma_rs_32_0(d + 80, A[20], A[21], A[22], A[23], db + 240, 1);
        wgmma_rs_32_0(d + 64, A[28], A[29], A[30], A[31], db + 240, 1);
        wgmma_rs_32_0(d + 48, A[36], A[37], A[38], A[39], db + 240, 1);
        wgmma_rs_32_0(d + 32, A[44], A[45], A[46], A[47], db + 240, 1);
        wgmma_rs_32_0(d + 16, A[52], A[53], A[54], A[55], db + 240, 1);
        wgmma_rs_32_0(d + 0, A[60], A[61], A[62], A[63], db + 240, 1);
        wg_commit();
        const uint32_t yoff = ub + w * 2048 + (127 + 2 * w - lane) * 16;
        const uint32_t yoff0 = yoff + (lane < 2 * w ? -2048 : 8192), yoff4 = yoff + (lane < 2 * w ? 6144 : 0);
        wg_wait<0>();
        regfence<128>(d);
        if (lead) TSTAMP(42 + j);
        bar_sync(5 + isE, 128);
#pragma unroll
        for (int z = 0; z < 8; z++) {
          uint32_t e[4];
#pragma unroll
          for (int i = 0; i < 4; i++) {
            const int u = 4 * z + i;
            e[i] = u < 31 ? pack2(d[4 * u] + d[4 * u + 6], d[4 * u + 1] + d[4 * u + 7]) : pack2(d[4 * u], d[4 * u + 1]);
          }
          if (z == 0 && c < w) e[0] = 0;
          stsm4t(z == 0 ? yoff0 : z == 4 ? yoff4 : z < 4 ? yoff + 8192 - 512 * z : yoff - 512 * (z - 4), e[0], e[1], e[2], e[3]);
        }
        __syncwarp();
        if (lane == 0) mbar_arrive(BAR(B_Y + j));
        if (lead) TSTAMP(j < 3 ? 47 + j : 76 + j);
      }
    }
    const int rh = isE ^ kh;
    const uint32_t hreg = sb + (isE ? 0 : 4 * SLOT);
    uint32_t hA[48];
    {
      float ag[96], au[96];
      int slot = 2, prev = 0, ph = 0, s = 0;
      const int v0 = min(vr, 2) * 4;
      const uint64_t dbase = mkdesc(sb, 4096, 1024, 1);
      const uint32_t ck = sb + 24576 + rh * 4096 + lane * 128 + (((2 * w + 1) ^ (lane & 7)) << 4) + (lane >> 3) * 4;
      auto stage = [&](float* vv) {
        const uint64_t dg = dbase + slot * (SLOT >> 4), da = dg + ((24576 + rh * 4096) >> 4);
        if (s == LH + LEAD * isE) { if (isE) bar_arrive(7, 256); else bar_sync(7, 256); }
        mbar_wait(BAR(B_FULL + slot), ph);
        if ((lds32(ck + slot * SLOT) ^ ep) & 1)
          refetch(g_x1T + (((ord >> (s & 28)) & 7) * 128 + (s & 3) * 32 + lane) * 4096 + (rb >> 3) * 2048 + 1024 + (rb & 7) * 128 + rh * 64 + w * 16, 16 + (lane >> 3) * 4,
                  ((ck + slot * SLOT) & ~15u) ^ 16, ep);
        __syncwarp();
        if (s == 0 && lead) TSTAMP(22 + isE);
        if (s && (s & 3) == 0 && tid == 128) TSTAMP(37 + (s >> 2));
        wg_fence();
        wgmma_ss_192_11(ag, da, dg, s);
        wgmma_ss_192_11(au, da, dg + 768, s);
        if (vv) wgmma_ss_8_10(vv, dg + (2 * vt + isE) * 256, mkdesc(sb + O_CS, 32, 128, 0) + (s & 3) * 8, s & 3);
        wgmma_ss_192_11(ag, da + 128, dg + 128, 1);
        wgmma_ss_192_11(au, da + 128, dg + 896, 1);
        if (vv) wgmma_ss_8_10(vv, dg + (2 * vt + isE) * 256 + 128, mkdesc(sb + O_CS, 32, 128, 0) + (s & 3) * 8 + 4, 1);
        wg_commit();
        wg_wait<1>();
        if (s > 0 && lead) mbar_arrive(BAR(B_EMPTY + prev));
        prev = slot;
        if (++slot == 6) { slot = s == 3 ? 2 : 0; ph ^= 1; }
        ++s;
      };
#pragma unroll 1
      while (s < v0) stage(nullptr);
      {
        float vv[4];
        mbar_wait(BAR(B_CS), 0);
#pragma unroll 1
        while (s < v0 + 4) stage(vv);
        wg_wait<0>();
        regfence<4>(vv);
        if (c == 0) {
          uint32_t* g = g_vv + (fs * 5 + vr) * 384 + (2 * vt + isE) * 64 + 16 * w + r;
          str(g, settag(pack2(vv[0], vv[1]), 1, ep));
          str(g + 8, settag(pack2(vv[2], vv[3]), 1, ep));
        }
        bar_sync(5 + isE, 128);
        if (lead) hint_add(g_sync + Y_VV + fs * 32);
      }
#pragma unroll 1
      while (s < 20) stage(nullptr);
      {
        mbar_wait(BAR(B_ST + rh), 0);
        const uint32_t a0 = lds32(sb + O_ST + rh * 512 + w * 128 + r * 8), a1 = lds32(sb + O_ST + rh * 512 + w * 128 + r * 8 + 64);
        mbar_wait(BAR(B_VV), 0);
        const uint64_t dp = mkdesc(sb + O_BP, 16, 128, 0);
        wg_fence();
        wgmma_rs_192_0(ag, a0, a1, 0, 0, dp, 1);
        wgmma_rs_192_0(au, a0, a1, 0, 0, dp + 192, 1);
        wg_commit();
        wg_wait<1>();
        if (lead) mbar_arrive(BAR(B_EMPTY + 5));
        mbar_wait(BAR(B_EMPTY + 4 - 4 * isE), 0);
        wg_wait<0>();
      }
      regfence<96>(ag); regfence<96>(au);
      if (lead) TSTAMP(24 + isE);
      const uint32_t stg = hreg + (16 * w + (lane & 15)) * 128;
#pragma unroll
      for (int kq = 0; kq < 12; kq++) {
#pragma unroll
        for (int i = 0; i < 4; i++) hA[4 * kq + i] = pack2(ag[8 * kq + 2 * i] * au[8 * kq + 2 * i], ag[8 * kq + 2 * i + 1] * au[8 * kq + 2 * i + 1]);
        hA[4 * kq + 2] = settag(hA[4 * kq + 2], c == 2 * (kq & 1), ep);
        hA[4 * kq + 3] = settag(hA[4 * kq + 3], c == 2 * (kq & 1) + 1, ep);
        stsm4(stg + (kq >> 2) * 8192 + (((2 * (kq & 3) + (lane >> 4)) ^ (lane & 7)) * 16), hA[4 * kq], hA[4 * kq + 1], hA[4 * kq + 2], hA[4 * kq + 3]);
        if ((kq & 3) == 3) {
          fence_async_smem();
          __syncwarp();
          if (lane == 0) mbar_arrive(BAR(B_STAGED + isE * 3 + (kq >> 2)));
        }
      }
      if (lead) TSTAMP(50 + isE);
    }
    float o[80];
    {
#pragma unroll
      for (int s = 0; s < 3; s++) {
        mbar_wait(BAR(B_W2F + s), 0);
        const uint64_t dw = mkdesc(sb + w2entry(s), 8192, 1024, 1);
        wg_fence();
#pragma unroll
        for (int kk = 0; kk < 4; kk++) wgmma_rs_160_1(o, hA[16 * s + 4 * kk], hA[16 * s + 4 * kk + 1], hA[16 * s + 4 * kk + 2], hA[16 * s + 4 * kk + 3], dw + kk * 128, (s | kk) ? 1 : 0);
        wg_commit();
        if (s > 0) { wg_wait<1>(); if (lead) mbar_arrive(BAR(B_W2E + s - 1)); }
      }
      const uint32_t wd = ((lane >> 3) & 1) * 4 + (lane >> 4) * 8;
      const uint32_t ck = hreg + (16 * w + (lane & 15)) * 128 + (((2 * (lane >> 4) + 1) ^ (lane & 7)) << 4) + wd;
      int e = 3, pe = 0;
#pragma unroll 1
      for (int i = 0; i < 9; i++) {
        const int he = (i + 3) & 3;
        mbar_wait(BAR(B_W2F + e), pe);
        mbar_wait(BAR(B_HF + isE * 4 + he), (i >> 2) & 1);
        const uint32_t c0 = lds32(ck + he * 8192), c1 = lds32((ck + he * 8192) ^ 64);
        if (((c0 ^ ep) | (c1 ^ ep)) & 1) {
          const __nv_bfloat16* g = g_h + (rb * 128 + rh * 64 + 16 * w + (lane & 15)) * F_ + kh * 768 + ((cg + 1 + i % 3) & 3) * 192 + (i / 3) * 64 + (lane & 16);
          const uint32_t a = ((ck + he * 8192) & ~15u) ^ 16;
          refetch(g, 16 + wd, a, ep);
          refetch(g + 32, 16 + wd, a ^ 64, ep);
        }
        __syncwarp();
        if (i == 0 && lead) TSTAMP(26 + isE);
        const uint64_t dw = mkdesc(sb + w2entry(e), e == 3 ? SLOT : 8192, 1024, 1);
        const uint64_t dh = mkdesc(hreg + he * 8192, 16, 1024, 1);
        wg_fence();
#pragma unroll
        for (int kk = 0; kk < 4; kk++) wgmma_ss_160_01(o, dh + kk * 2, dw + kk * 128, 1);
        wg_commit();
        wg_wait<1>();
        if (lead) {
          mbar_arrive(BAR(B_W2E + (e == 0 ? 4 : e - 1)));
          if (i > 0) mbar_arrive(BAR(B_HE + isE * 4 + ((he - 1) & 3)));
        }
        if (++e == 5) { e = 0; pe ^= 1; }
      }
      wg_wait<0>();
      regfence<80>(o);
      if (lead) TSTAMP(28 + isE);
    }
    const float ia = __uint_as_float(lds32(sb + O_ST + rh * 512 + w * 128 + r * 8 + 4)), ib = __uint_as_float(lds32(sb + O_ST + rh * 512 + w * 128 + r * 8 + 68));
    asm volatile("barrier.cluster.wait.aligned;" ::: "memory");
    const uint32_t red = sb + w2entry(2) + (tid & 127) * 16;
    auto fin = [&](int u, uint32_t& x0, uint32_t& x1, uint32_t& x2, uint32_t& x3) {
      const float2 g0 = lds64f(sb + O_GB + (16 * u + 2 * c) * 4), g1 = lds64f(sb + O_GB + (16 * u + 8 + 2 * c) * 4);
      x0 = pack2(fmaf(g0.x, o[8 * u] * ia, blo(x0)), fmaf(g0.y, o[8 * u + 1] * ia, bhi(x0)));
      x1 = pack2(fmaf(g0.x, o[8 * u + 2] * ib, blo(x1)), fmaf(g0.y, o[8 * u + 3] * ib, bhi(x1)));
      x2 = pack2(fmaf(g1.x, o[8 * u + 4] * ia, blo(x2)), fmaf(g1.y, o[8 * u + 5] * ia, bhi(x2)));
      x3 = pack2(fmaf(g1.x, o[8 * u + 6] * ib, blo(x3)), fmaf(g1.y, o[8 * u + 7] * ib, bhi(x3)));
    };
    if (isE) {
      mbar_wait_cluster(BAR(B_RDY), 0);
      uint32_t rred, rbar;
      asm volatile("mapa.shared::cluster.u32 %0, %1, %2;" : "=r"(rred) : "r"(red), "r"(kh ^ 1));
      asm volatile("mapa.shared::cluster.u32 %0, %1, %2;" : "=r"(rbar) : "r"(BAR(B_RED)), "r"(kh ^ 1));
      const uint32_t xa = sb + O_REG + ((lane & 7) + 8 * (lane >> 4)) * 128 + (((2 * w + ((lane >> 3) & 1)) ^ (lane & 7)) * 16);
#pragma unroll
      for (int u = 0; u < 10; u++) {
        uint32_t x0, x1, x2, x3;
        ldsm4t(xa + u * 2048 + (cg & 1) * (u < 8 ? 4096 : -16384), x0, x1, x2, x3);
        fin(u, x0, x1, x2, x3);
        asm volatile("st.async.weak.shared::cluster.mbarrier::complete_tx::bytes.v4.b32 [%0], {%1,%2,%3,%4}, [%5];" ::"r"(rred + u * 2048), "r"(x0), "r"(x1), "r"(x2), "r"(x3), "r"(rbar) : "memory");
      }
    } else {
      mbar_wait_cluster(BAR(B_RED), 0);
      if (lead) TSTAMP(30);
      const uint32_t stg = hreg + (16 * w + (lane & 15)) * 128;
      const int row = rb * 128 + kh * 64 + 16 * w, c0 = cg * 160 + (cg & 1) * 32;
#pragma unroll
      for (int u = 0; u < 10; u++) {
        uint4 x = lds128(red + u * 2048);
        fin(u, x.x, x.y, x.z, x.w);
        stsm4(stg + (u >> 2) * 8192 + (((2 * (u & 3) + (lane >> 4)) ^ (lane & 7)) * 16), x.x, x.y, x.z, x.w);
        if ((u & 3) == 3 || u == 9) {
          fence_async_smem();
          __syncwarp();
          if (lane == 0) {
            if (u < 9) tma2d_store(&p.m_outa, hreg + (u >> 2) * 8192 + w * 2048, c0 + (u >> 2) * 64, row);
            else tma3d_store(&p.m_outb, hreg + 16384 + w * 2048, 0, row, cg * 5 + (~cg & 1) * 4);
          }
        }
      }
      if (lane == 0) { bulk_commit(); bulk_wait0_read(); }
      if (lead) { str(g_sync + Y_EP + b * 32, ep); TSTAMP(31); }
    }
  }
}

#define L2PROMO CU_TENSOR_MAP_L2_PROMOTION_L2_128B
typedef CUresult (*EncodeFn)(CUtensorMap*, CUtensorMapDataType, cuuint32_t, void*, const cuuint64_t*, const cuuint64_t*, const cuuint32_t*,
                             const cuuint32_t*, CUtensorMapInterleave, CUtensorMapSwizzle, CUtensorMapL2promotion, CUtensorMapFloatOOBfill);

void make_map(EncodeFn enc, CUtensorMap* m, const void* ptr, uint64_t inner, uint64_t outer, uint32_t bi, uint32_t bo, CUtensorMapSwizzle sw) {
  cuuint64_t d[2] = {inner, outer};
  cuuint64_t s[1] = {inner * 2};
  cuuint32_t bx[2] = {bi, bo};
  cuuint32_t e[2] = {1, 1};
  enc(m, CU_TENSOR_MAP_DATA_TYPE_BFLOAT16, 2, const_cast<void*>(ptr), d, s, bx, e, CU_TENSOR_MAP_INTERLEAVE_NONE, sw, L2PROMO,
      CU_TENSOR_MAP_FLOAT_OOB_FILL_NONE);
}

void make_map3(EncodeFn enc, CUtensorMap* m, const void* ptr, uint64_t d0, uint64_t d1, uint64_t d2, uint64_t s1, uint64_t s2, uint32_t b0, uint32_t b1, uint32_t b2,
               CUtensorMapSwizzle sw) {
  cuuint64_t d[3] = {d0, d1, d2};
  cuuint64_t s[2] = {s1, s2};
  cuuint32_t bx[3] = {b0, b1, b2};
  cuuint32_t e[3] = {1, 1, 1};
  enc(m, CU_TENSOR_MAP_DATA_TYPE_BFLOAT16, 3, const_cast<void*>(ptr), d, s, bx, e, CU_TENSOR_MAP_INTERLEAVE_NONE, sw, L2PROMO,
      CU_TENSOR_MAP_FLOAT_OOB_FILL_NONE);
}

}

extern "C" void kernel_launch(void* const* d_in, const int* in_sizes, int n_in, void* d_out, int out_size) {
  (void)in_sizes; (void)n_in; (void)out_size;
  void* f = nullptr;
  cudaDriverEntryPointQueryResult qr;
  cudaGetDriverEntryPoint("cuTensorMapEncodeTiled", &f, cudaEnableDefault, &qr);
  EncodeFn enc = (EncodeFn)f;
  void *x1T, *h;
  cudaGetSymbolAddress(&x1T, g_x1T);
  cudaGetSymbolAddress(&h, g_h);
  Params p;
  make_map3(enc, &p.m_k, d_in[1], D_, S_ / 8, 8, 8 * D_ * 2, D_ * 2, 32, 8, 8, CU_TENSOR_MAP_SWIZZLE_64B);
  make_map3(enc, &p.m_kh, d_in[1], D_, S_ / 8, 8, 8 * D_ * 2, D_ * 2, 32, 8, 3, CU_TENSOR_MAP_SWIZZLE_64B);
  make_map3(enc, &p.m_v, d_in[2], D_, S_ / 8, 8, 8 * D_ * 2, D_ * 2, 32, 8, 8, CU_TENSOR_MAP_SWIZZLE_64B);
  {
    cuuint64_t d[5] = {64, 2, S_ / 4, 2, D_ / 64}, s[4] = {D_ * 2, 4 * D_ * 2, 2 * D_ * 2, 128};
    cuuint32_t bx[5] = {64, 2, 4, 2, D_ / 64}, e[5] = {1, 1, 1, 1, 1};
    enc(&p.m_q, CU_TENSOR_MAP_DATA_TYPE_BFLOAT16, 5, d_in[0], d, s, bx, e, CU_TENSOR_MAP_INTERLEAVE_NONE, CU_TENSOR_MAP_SWIZZLE_128B, L2PROMO, CU_TENSOR_MAP_FLOAT_OOB_FILL_NONE);
  }
  make_map(enc, &p.m_wm, d_in[11], 6 * D_, D_, 64, 64, CU_TENSOR_MAP_SWIZZLE_128B);
  make_map3(enc, &p.m_wg, d_in[7], 64, D_, F_ / 64, F_ * 2, 128, 64, 32, 3, CU_TENSOR_MAP_SWIZZLE_128B);
  make_map3(enc, &p.m_wu, d_in[8], 64, D_, F_ / 64, F_ * 2, 128, 64, 32, 3, CU_TENSOR_MAP_SWIZZLE_128B);
  make_map3(enc, &p.m_xa, x1T, 64, D_, 64, S_ * 4, 128, 64, 32, 2, CU_TENSOR_MAP_SWIZZLE_128B);
  make_map(enc, &p.m_xr, x1T, 2 * S_, D_, 64, 80, CU_TENSOR_MAP_SWIZZLE_128B);
  make_map(enc, &p.m_w2a, d_in[9], D_, F_, 64, 64, CU_TENSOR_MAP_SWIZZLE_128B);
  make_map3(enc, &p.m_w2b, d_in[9], 32, F_, D_ / 32, D_ * 2, 64, 64, 64, 1, CU_TENSOR_MAP_SWIZZLE_128B);
  make_map(enc, &p.m_h, h, F_, S_, 64, 64, CU_TENSOR_MAP_SWIZZLE_128B);
  make_map(enc, &p.m_outa, d_out, D_, S_, 64, 16, CU_TENSOR_MAP_SWIZZLE_128B);
  make_map3(enc, &p.m_outb, d_out, 32, S_, D_ / 32, D_ * 2, 64, 64, 16, 1, CU_TENSOR_MAP_SWIZZLE_128B);
  p.zero = 0;
  p.k = (const __nv_bfloat16*)d_in[1];
  p.v = (const __nv_bfloat16*)d_in[2];
  p.shift = (const __nv_bfloat16*)d_in[3];
  p.ssm = (const __nv_bfloat16*)d_in[4];
  p.ssmD = (const __nv_bfloat16*)d_in[5];
  p.c = (const __nv_bfloat16*)d_in[10];
  p.wg = (const __nv_bfloat16*)d_in[7];
  p.wu = (const __nv_bfloat16*)d_in[8];
  p.w2 = (const __nv_bfloat16*)d_in[9];
  cudaFuncSetAttribute(fused_kernel, cudaFuncAttributeMaxDynamicSharedMemorySize, SMEM_BYTES);
  fused_kernel<<<128, 384, SMEM_BYTES, cudaStreamPerThread>>>(p);
}
```

```cpp
#include <cuda_runtime.h>
#include <cuda.h>
#include <cuda_bf16.h>
#include <cstdint>

namespace {

constexpr int S_ = 2048, D_ = 640, F_ = 1536;

__device__ __align__(1024) uint8_t g_s[18 << 20];
#define g_sync ((uint32_t*)(ps + (28 << 16)))
#define g_mod ((uint32_t*)(ps + (29 << 16)))
#define g_vv ((uint32_t*)(ps + (30 << 16)))
enum { Y_KV = 0, Y_Y = 20 * 32, Y_MOD = 25 * 32, Y_VV = 31 * 32, Y_CLS = 40 * 32 + 8, Y_EP = 7 };
enum { G_KV = 0, G_Y = 5, G_X = 10, G_H = 15, G_M = 27 };
enum { M_X = 0, M_H = 256, M_ST = 512 };
#define TSTAMP(i) do { } while (0)
#define T_K1 900
#define T_S0 500
#define T_Q 4400
#define T_K2 1500
#define T_S1 2100
#define T_K3 2400
#define T_WM0 3000
#define T_S2 3500
#define T_K4 3800
#define T_S3 5900
#define T_WM1 6500
#define T_S4 6200
#define T_W0 6900
#define T_WM2 7300
#define STEP(ln, kv, gv, cv) (ln | (kv + 1) << 1 | (gv + 1) << 4 | (cv + 1) << 6)
#define SCH 1
#define SCHED_E STEP(0, 0, -1, -1), STEP(0, 2, -1, -1), STEP(0, 3, 0, -1), STEP(0, 4, -1, 1), STEP(1, -1, -1, 3), STEP(0, -1, 1, -1), STEP(0, -1, 2, -1)
#define SCHED_L STEP(0, 1, -1, 0), STEP(0, -1, -1, 2), STEP(0, -1, -1, 4)
#define LH 10
#define LEAD 3

struct Params {
  CUtensorMap m_k, m_kh, m_v, m_q, m_wm, m_wg, m_wu, m_s, m_w2a, m_w2b, m_outa, m_outb;
  const __nv_bfloat16 *c, *wg, *wu, *w2;
};
constexpr int NLD = 14;
__host__ __device__ constexpr uint32_t nth_load(int n) {
  const uint32_t when[NLD] = {T_K1 << 8 | 1, T_K2 << 8 | 2, T_K3 << 8 | 3, T_K4 << 8 | 4, T_S0 << 8 | 16, T_S1 << 8 | 17, T_S2 << 8 | 18, T_S3 << 8 | 19, T_S4 << 8 | 20,
                              T_Q << 8 | 21, T_WM0 << 8 | 32, T_WM1 << 8 | 33, T_WM2 << 8 | 34, T_W0 << 8 | 48};
  for (int i = 0; i < NLD; i++) {
    int rank = 0;
    for (int k = 0; k < NLD; k++) rank += when[k] < when[i];
    if (rank == n) return when[i];
  }
  return 0;
}
__host__ __device__ constexpr uint64_t sched(int g) {
  const uint32_t t[2][8] = {{SCHED_L}, {SCHED_E}};
  uint64_t r = 0;
  for (int i = 0; i < 7; i++) r |= (uint64_t)t[g][i] << 9 * i;
  return r;
}
__host__ __device__ constexpr uint32_t release(int g) {
  uint32_t last[7] = {};
  for (int i = 0; i < 7; i++) {
    const uint32_t t = (sched(g) >> 9 * i) & 511, kv = (t >> 1) & 7, cv = (t >> 6) & 7;
    if (kv) last[kv == 5 ? 2 : kv + 1] = last[kv == 5 ? 3 : kv + 1] = i;
    if (t & 48) last[0] = last[1] = i;
    if (cv) last[cv == 5 ? 1 : cv + 1] = last[6] = i;
  }
  uint32_t r = g ? 7 << 18 : 0;
  for (int i = 0; i < 7; i++) r |= last[i] << 3 * i;
  return r;
}
template <int I> struct IC { static constexpr int v = I; };
template <int N, class F> __device__ __forceinline__ void unrolled(F f) {
  if constexpr (N > 0) { unrolled<N - 1>(f); f(IC<N - 1>()); }
}

constexpr uint32_t SLOT = 32768;
constexpr uint32_t U_RAW = 16, U_ODD = U_RAW + 4160, U_KV = 8448;
constexpr uint32_t O_SILU = SLOT + 8192;
constexpr uint32_t O_REG = 6 * SLOT;
constexpr uint32_t O_Y = O_REG + 20480;
constexpr uint32_t O_BP = O_Y + 4096;
constexpr uint32_t O_MA = O_BP + 6272;
constexpr uint32_t O_CS = O_MA + 768;
constexpr uint32_t O_GB = O_CS + 640;
constexpr uint32_t O_IC = O_GB + 640;
constexpr uint32_t O_LN = O_IC + 640;
constexpr uint32_t O_ROLE = O_LN + 128;
constexpr uint32_t O_ST = O_ROLE + 128;
constexpr uint32_t O_BAR = O_ST + 1024;
constexpr uint32_t O_SX = O_BAR + 768;
constexpr uint32_t SMEM_BYTES = O_BAR + 1024;
static_assert(SMEM_BYTES <= 232448, "smem");
enum { B_EMPTY = 0, B_W2E = 6, B_PL = 11, B_LN = 16, B_STAGED = 17, B_VV = 23, B_RED = 24, B_RDY = 25, B_FULL = 26, B_W2F = 32, B_HF = 37, B_HE = 45,
       B_KIN = 53, B_KV = 58, B_QIN = 63, B_WM = 64, B_CS = 65, B_X1 = 67, B_ST = 68, B_ROLE = 71, B_SSM = 72, B_PR = 66, B_YF = 77, B_YE = 80 };
__device__ __forceinline__ uint32_t kreg(int n) { return n < 4 ? (n + 2) * SLOT + 16384 : 2 * SLOT + 26624; }
__device__ __forceinline__ uint32_t voff(int n) { return n < 4 ? 6144 : SLOT; }
__device__ __forceinline__ uint32_t w2entry(int e) { return e == 3 ? SLOT + 24576 : (e + 1) * SLOT; }
__device__ __forceinline__ uint32_t bnd(int j) { return j < 4 ? (j + 2) * SLOT : SLOT + 16384; }
__device__ __forceinline__ uint32_t pgo(int rb, int p) { return (rb >> 1) << 21 | p << 13 | ((rb ^ p) & 1) << 12; }
__device__ __forceinline__ uint32_t cgrp(int g) { return g << 16 | ((0x99669966u >> g) & 1) << 12; }
__device__ __forceinline__ uint32_t tile(int rb, int g0, int x) { return pgo(rb, (x & 1) | (x & 2) << 1) ^ cgrp(g0 + (x >> 2)); }

__device__ __forceinline__ uint32_t smem_u32(const void* p) { return (uint32_t)__cvta_generic_to_shared(p); }
__device__ __forceinline__ void mbar_init(uint32_t bar, uint32_t cnt) { asm volatile("mbarrier.init.shared::cta.b64 [%0], %1;" ::"r"(bar), "r"(cnt) : "memory"); }
__device__ __forceinline__ void mbar_expect(uint32_t bar, uint32_t bytes) { asm volatile("mbarrier.arrive.expect_tx.shared::cta.b64 _, [%0], %1;" ::"r"(bar), "r"(bytes) : "memory"); }
__device__ __forceinline__ void mbar_arrive(uint32_t bar) { asm volatile("mbarrier.arrive.shared::cta.b64 _, [%0];" ::"r"(bar) : "memory"); }
__device__ __forceinline__ void mbar_wait(uint32_t bar, uint32_t parity) {
  asm volatile("{\n .reg .pred p;\n .reg .u32 c;\n mov.u32 c, 0;\n LOOP:\n mbarrier.try_wait.parity.shared::cta.b64 p, [%0], %1;\n @p bra DONE;\n add.u32 c, c, 1;\n setp.lt.u32 p, c, 200000;\n @p bra LOOP;\n DONE:\n }" ::"r"(bar), "r"(parity) : "memory");
}
__device__ __forceinline__ void mbar_wait_cluster(uint32_t bar, uint32_t parity) {
  asm volatile("{\n .reg .pred p;\n .reg .u32 c;\n mov.u32 c, 0;\n LOOP:\n mbarrier.try_wait.parity.acquire.cluster.shared::cta.b64 p, [%0], %1;\n @p bra DONE;\n add.u32 c, c, 1;\n setp.lt.u32 p, c, 200000;\n @p bra LOOP;\n DONE:\n }" ::"r"(bar), "r"(parity) : "memory");
}
__device__ __forceinline__ bool elect() { uint32_t p; asm volatile("{ .reg .pred q; elect.sync _|q, 0xffffffff; selp.u32 %0, 1, 0, q; }" : "=r"(p)); return p; }
__device__ __forceinline__ uint32_t clk() { uint32_t c; asm volatile("mov.u32 %0, %%clock;" : "=r"(c)); return c; }
__device__ __forceinline__ uint32_t ldr(const uint32_t* p) { uint32_t v; asm volatile("ld.relaxed.gpu.global.u32 %0, [%1];" : "=r"(v) : "l"(p) : "memory"); return v; }
__device__ __forceinline__ uint4 ldr4(const uint32_t* p) {
  uint4 v; asm volatile("ld.relaxed.gpu.global.v4.u32 {%0,%1,%2,%3}, [%4];" : "=r"(v.x), "=r"(v.y), "=r"(v.z), "=r"(v.w) : "l"(p) : "memory"); return v;
}
__device__ __forceinline__ void poll_ge(const uint32_t* p, uint32_t target) {
  asm volatile("{\n .reg .pred p;\n .reg .u32 c, v;\n mov.u32 c, 0;\n LOOP:\n ld.relaxed.gpu.global.u32 v, [%0];\n sub.u32 v, v, %1;\n setp.ge.s32 p, v, 0;\n @p bra DONE;\n add.u32 c, c, 1;\n setp.lt.u32 p, c, 100000;\n @p bra LOOP;\n DONE:\n }" ::"l"(p), "r"(target) : "memory");
}
__device__ __forceinline__ void poll_lane(uint32_t& v, const void* p, uint32_t target, int l) {
  for (int it = 0; !((__ballot_sync(0xffffffffu, (int)(v - target) >= 0) >> l) & 1) && it < 100000; it++) v = ldr((const uint32_t*)p);
}
__device__ __forceinline__ void hint_add(uint32_t* p) { asm volatile("red.relaxed.gpu.global.add.u32 [%0], 1;" ::"l"(p) : "memory"); }
__device__ __forceinline__ void refetch(const void* g, uint32_t off, uint32_t a, uint32_t tag) {
  asm volatile("{\n .reg .pred p;\n .reg .u32 c, v, x, y, z;\n .reg .u64 q;\n mov.u32 c, 0;\n cvt.u64.u32 q, %1;\n add.u64 q, q, %0;\n"
               " LOOP:\n ld.relaxed.gpu.global.u32 v, [q];\n xor.b32 v, v, %3;\n and.b32 v, v, 1;\n setp.eq.u32 p, v, 0;\n @p bra DONE;\n add.u32 c, c, 1;\n setp.lt.u32 p, c, 100000;\n @p bra LOOP;\n"
               " DONE:\n ld.relaxed.gpu.global.v4.u32 {v, x, y, z}, [%0];\n st.shared.v4.u32 [%2], {v, x, y, z};\n ld.relaxed.gpu.global.v4.u32 {v, x, y, z}, [%0+16];\n xor.b32 c, %2, 16;\n"
               " st.shared.v4.u32 [c], {v, x, y, z};\n fence.proxy.async.shared::cta;\n }" ::"l"(g), "r"(off), "r"(a), "r"(tag) : "memory");
}
__device__ __forceinline__ void refetch16(const void* g, uint32_t a, uint32_t tag) {
  asm volatile("{\n .reg .pred p;\n .reg .u32 c, t, v, x, y, z;\n mov.u32 c, 0;\n"
               " LOOP:\n ld.relaxed.gpu.global.v4.u32 {v, x, y, z}, [%0];\n xor.b32 t, v, %2;\n and.b32 t, t, 1;\n setp.eq.u32 p, t, 0;\n @p bra DONE;\n add.u32 c, c, 1;\n setp.lt.u32 p, c, 100000;\n @p bra LOOP;\n"
               " DONE:\n st.shared.v4.u32 [%1], {v, x, y, z};\n }" ::"l"(g), "r"(a), "r"(tag) : "memory");
}
__device__ __forceinline__ uint2 ldr2(const uint32_t* p) {
  uint2 v; asm volatile("ld.relaxed.gpu.global.v2.u32 {%0,%1}, [%2];" : "=r"(v.x), "=r"(v.y) : "l"(p) : "memory"); return v;
}
__device__ __forceinline__ uint32_t settag(uint32_t x, uint32_t m, uint32_t t) { return (x & ~m) | (t & m); }
__device__ __forceinline__ void stg128(void* p, uint32_t x, uint32_t y, uint32_t z, uint32_t w) {
  asm volatile("st.global.v4.u32 [%0], {%1,%2,%3,%4};" ::"l"(p), "r"(x), "r"(y), "r"(z), "r"(w) : "memory");
}
__device__ __forceinline__ void cpa16(uint32_t dst, const void* src, uint32_t n) { asm volatile("cp.async.cg.shared.global [%0], [%1], 16, %2;" ::"r"(dst), "l"(src), "r"(n) : "memory"); }
__device__ __forceinline__ void tma3d(uint32_t dst, const CUtensorMap* m, int x, int y, int z, uint32_t bar) {
  asm volatile("cp.async.bulk.tensor.3d.shared::cluster.global.mbarrier::complete_tx::bytes [%0], [%1, {%3, %4, %5}], [%2];" ::"r"(dst), "l"(m), "r"(bar), "r"(x), "r"(y), "r"(z) : "memory");
}
__device__ __forceinline__ void tma3d_store(const CUtensorMap* m, uint32_t src, int x, int y, int z) {
  asm volatile("cp.async.bulk.tensor.3d.global.shared::cta.bulk_group [%0, {%2, %3, %4}], [%1];" ::"l"(m), "r"(src), "r"(x), "r"(y), "r"(z) : "memory");
}
__device__ __forceinline__ void bulk_st(void* dst, uint32_t src, uint32_t bytes) {
  asm volatile("cp.async.bulk.global.shared::cta.bulk_group [%0], [%1], %2;" ::"l"(dst), "r"(src), "r"(bytes) : "memory");
}
__device__ __forceinline__ void bulk_pf(const void* src, uint32_t bytes) { asm volatile("cp.async.bulk.prefetch.L2.global [%0], %1;" ::"l"(src), "r"(bytes) : "memory"); }
__device__ __forceinline__ void tma2d(uint32_t dst, const CUtensorMap* m, int x, int y, uint32_t bar) {
  asm volatile("cp.async.bulk.tensor.2d.shared::cluster.global.mbarrier::complete_tx::bytes [%0], [%1, {%3, %4}], [%2];" ::"r"(dst), "l"(m), "r"(bar), "r"(x), "r"(y) : "memory");
}
__device__ __forceinline__ void tma2d_store(const CUtensorMap* m, uint32_t src, int x, int y) {
  asm volatile("cp.async.bulk.tensor.2d.global.shared::cta.bulk_group [%0, {%2, %3}], [%1];" ::"l"(m), "r"(src), "r"(x), "r"(y) : "memory");
}
__device__ __forceinline__ void bulk_ld(uint32_t dst, const void* src, uint32_t bytes, uint32_t bar) {
  asm volatile("cp.async.bulk.shared::cluster.global.mbarrier::complete_tx::bytes [%0], [%1], %2, [%3];" ::"r"(dst), "l"(src), "r"(bytes), "r"(bar) : "memory");
}
__device__ __forceinline__ void bulk_commit() { asm volatile("cp.async.bulk.commit_group;" ::: "memory"); }
template <int N> __device__ __forceinline__ void bulk_wait() { asm volatile("cp.async.bulk.wait_group %0;" ::"n"(N) : "memory"); }
__device__ __forceinline__ void bulk_wait0_read() { asm volatile("cp.async.bulk.wait_group.read 0;" ::: "memory"); }
__device__ __forceinline__ void fence_async_smem() { asm volatile("fence.proxy.async.shared::cta;" ::: "memory"); }
__device__ __forceinline__ void bar_sync(int id, int n) { asm volatile("bar.sync %0, %1;" ::"r"(id), "r"(n) : "memory"); }
__device__ __forceinline__ void bar_arrive(int id, int n) { asm volatile("bar.arrive %0, %1;" ::"r"(id), "r"(n) : "memory"); }
__device__ __forceinline__ void wg_fence() { asm volatile("wgmma.fence.sync.aligned;" ::: "memory"); }
__device__ __forceinline__ void wg_commit() { asm volatile("wgmma.commit_group.sync.aligned;" ::: "memory"); }
template <int N> __device__ __forceinline__ void wg_wait() { asm volatile("wgmma.wait_group.sync.aligned %0;" ::"n"(N) : "memory"); }
__device__ __forceinline__ void ldsm4(uint32_t a, uint32_t& r0, uint32_t& r1, uint32_t& r2, uint32_t& r3) {
  asm volatile("ldmatrix.sync.aligned.m8n8.x4.shared.b16 {%0,%1,%2,%3}, [%4];" : "=r"(r0), "=r"(r1), "=r"(r2), "=r"(r3) : "r"(a) : "memory");
}
__device__ __forceinline__ void ldsm4t(uint32_t a, uint32_t& r0, uint32_t& r1, uint32_t& r2, uint32_t& r3) {
  asm volatile("ldmatrix.sync.aligned.m8n8.x4.trans.shared.b16 {%0,%1,%2,%3}, [%4];" : "=r"(r0), "=r"(r1), "=r"(r2), "=r"(r3) : "r"(a) : "memory");
}
__device__ __forceinline__ void stsm4t(uint32_t a, uint32_t r0, uint32_t r1, uint32_t r2, uint32_t r3) {
  asm volatile("stmatrix.sync.aligned.m8n8.x4.trans.shared.b16 [%0], {%1,%2,%3,%4};" ::"r"(a), "r"(r0), "r"(r1), "r"(r2), "r"(r3) : "memory");
}
__device__ __forceinline__ void stsm4(uint32_t a, uint32_t r0, uint32_t r1, uint32_t r2, uint32_t r3) {
  asm volatile("stmatrix.sync.aligned.m8n8.x4.shared.b16 [%0], {%1,%2,%3,%4};" ::"r"(a), "r"(r0), "r"(r1), "r"(r2), "r"(r3) : "memory");
}
__device__ __forceinline__ uint32_t lds32(uint32_t a) { uint32_t v; asm volatile("ld.shared.u32 %0, [%1];" : "=r"(v) : "r"(a) : "memory"); return v; }
__device__ __forceinline__ uint4 lds128(uint32_t a) { uint4 v; asm volatile("ld.shared.v4.u32 {%0,%1,%2,%3}, [%4];" : "=r"(v.x), "=r"(v.y), "=r"(v.z), "=r"(v.w) : "r"(a) : "memory"); return v; }
__device__ __forceinline__ float4 lds128f(uint32_t a) { float4 v; asm volatile("ld.shared.v4.f32 {%0,%1,%2,%3}, [%4];" : "=f"(v.x), "=f"(v.y), "=f"(v.z), "=f"(v.w) : "r"(a) : "memory"); return v; }
__device__ __forceinline__ float2 lds64f(uint32_t a) { float2 v; asm volatile("ld.shared.v2.f32 {%0,%1}, [%2];" : "=f"(v.x), "=f"(v.y) : "r"(a) : "memory"); return v; }
__device__ __forceinline__ void sts32(uint32_t a, uint32_t v) { asm volatile("st.shared.u32 [%0], %1;" ::"r"(a), "r"(v) : "memory"); }
__device__ __forceinline__ void sts64(uint32_t a, uint32_t x, uint32_t y) { asm volatile("st.shared.v2.u32 [%0], {%1,%2};" ::"r"(a), "r"(x), "r"(y) : "memory"); }
__device__ __forceinline__ void sts128(uint32_t a, uint32_t x, uint32_t y, uint32_t z, uint32_t w) { asm volatile("st.shared.v4.u32 [%0], {%1,%2,%3,%4};" ::"r"(a), "r"(x), "r"(y), "r"(z), "r"(w) : "memory"); }
__device__ __forceinline__ void sts16(uint32_t a, uint16_t v) { asm volatile("st.shared.u16 [%0], %1;" ::"r"(a), "h"(v) : "memory"); }
__device__ __forceinline__ uint32_t prmt(uint32_t a, uint32_t b, uint32_t s) { uint32_t r; asm("prmt.b32 %0, %1, %2, %3;" : "=r"(r) : "r"(a), "r"(b), "r"(s)); return r; }
__device__ __forceinline__ uint32_t hfma2(uint32_t a, uint32_t b, uint32_t c) { uint32_t r; asm("fma.rn.bf16x2 %0, %1, %2, %3;" : "=r"(r) : "r"(a), "r"(b), "r"(c)); return r; }
__device__ __forceinline__ uint32_t hfma2lh(uint32_t a, uint32_t l) {
  uint32_t r;
  asm("{ .reg .b16 x, y; .reg .b32 u, v; mov.b32 {x, y}, %2; mov.b32 u, {x, x}; mov.b32 v, {y, y}; fma.rn.bf16x2 %0, %1, u, v; }" : "=r"(r) : "r"(a), "r"(l));
  return r;
}
__device__ __forceinline__ uint32_t addu(uint32_t a, uint32_t u) { uint32_t r; asm("add.u32 %0, %1, %2;" : "=r"(r) : "r"(a), "r"(u)); return r; }
__device__ __forceinline__ uint32_t tag0(uint32_t x, uint32_t t) { uint32_t r; asm("lop3.b32 %0, %1, 1, %2, 0xb8;" : "=r"(r) : "r"(x), "r"(t)); return r; }
__device__ __forceinline__ void keep(uint32_t& x) { x = __shfl_xor_sync(0xffffffffu, x, 0); }
__device__ __forceinline__ uint32_t hmul2(uint32_t a, uint32_t b) { uint32_t r; asm("mul.rn.bf16x2 %0, %1, %2;" : "=r"(r) : "r"(a), "r"(b)); return r; }
__device__ __forceinline__ uint32_t pack2(float lo, float hi) { uint32_t r; asm("cvt.rn.bf16x2.f32 %0, %1, %2;" : "=r"(r) : "f"(hi), "f"(lo)); return r; }
__device__ __forceinline__ float blo(uint32_t v) { return __uint_as_float(v << 16); }
__device__ __forceinline__ float bhi(uint32_t v) { return __uint_as_float(v & 0xffff0000u); }
__device__ __forceinline__ uint32_t hadd2(uint32_t a, uint32_t b) { uint32_t r; asm("add.rn.bf16x2 %0, %1, %2;" : "=r"(r) : "r"(a), "r"(b)); return r; }
__device__ __forceinline__ void str(uint32_t* p, uint32_t v) { asm volatile("st.relaxed.gpu.global.u32 [%0], %1;" ::"l"(p), "r"(v) : "memory"); }
__device__ __forceinline__ uint32_t tagf(float x, uint32_t tag) { return (__float_as_uint(x) & ~3u) | (tag & 3); }
template <int N> __device__ __forceinline__ float4 gather4(const uint32_t* p, int stride, uint32_t tag) {
  uint4 v[N];
  int it = 0;
  uint32_t bad;
  do {
#pragma unroll
    for (int i = 0; i < N; i++) v[i] = ldr4(p + i * stride);
    bad = 0;
#pragma unroll
    for (int i = 0; i < N; i++) bad |= (v[i].x ^ tag) | (v[i].y ^ tag) | (v[i].z ^ tag) | (v[i].w ^ tag);
  } while ((bad & 3) && ++it < 100000);
  float4 s = make_float4(__uint_as_float(v[0].x), __uint_as_float(v[0].y), __uint_as_float(v[0].z), __uint_as_float(v[0].w));
#pragma unroll
  for (int i = 1; i < N; i++) { s.x += __uint_as_float(v[i].x); s.y += __uint_as_float(v[i].y); s.z += __uint_as_float(v[i].z); s.w += __uint_as_float(v[i].w); }
  return s;
}
__device__ __forceinline__ float rbf(float x) { return blo(pack2(x, 0.f)); }
__device__ __forceinline__ uint64_t mkdesc(uint32_t addr, uint32_t lbo, uint32_t sbo, uint32_t swz) {
  return (uint64_t)((addr & 0x3FFFF) >> 4) | ((uint64_t)(lbo >> 4) << 16) | ((uint64_t)(sbo >> 4) << 32) | ((uint64_t)swz << 62);
}
template <int N> __device__ __forceinline__ void regfence(float* d) {
#pragma unroll
  for (int i = 0; i < N; i++) asm volatile("" : "+f"(d[i])::"memory");
}

__device__ __forceinline__ void wgmma_rs_32_0(float* d, uint32_t a0, uint32_t a1, uint32_t a2, uint32_t a3, uint64_t db, int sd) {
  asm volatile("{ .reg .pred p; setp.ne.b32 p, %21, 0; wgmma.mma_async.sync.aligned.m64n32k16.f32.bf16.bf16 {%0,%1,%2,%3,%4,%5,%6,%7,%8,%9,%10,%11,%12,%13,%14,%15}, {%16,%17,%18,%19}, %20, p, 1, 1, 0; }"
   : "+f"(d[0]), "+f"(d[1]), "+f"(d[2]), "+f"(d[3]), "+f"(d[4]), "+f"(d[5]), "+f"(d[6]), "+f"(d[7]), "+f"(d[8]), "+f"(d[9]), "+f"(d[10]), "+f"(d[11]), "+f"(d[12]), "+f"(d[13]), "+f"(d[14]), "+f"(d[15]) : "r"(a0), "r"(a1), "r"(a2), "r"(a3), "l"(db), "r"(sd));
}
__device__ __forceinline__ void wgmma_rs_160_1(float* d, uint32_t a0, uint32_t a1, uint32_t a2, uint32_t a3, uint64_t db, int sd) {
  asm volatile("{ .reg .pred p; setp.ne.b32 p, %85, 0; wgmma.mma_async.sync.aligned.m64n160k16.f32.bf16.bf16 {%0,%1,%2,%3,%4,%5,%6,%7,%8,%9,%10,%11,%12,%13,%14,%15,%16,%17,%18,%19,%20,%21,%22,%23,%24,%25,%26,%27,%28,%29,%30,%31,%32,%33,%34,%35,%36,%37,%38,%39,%40,%41,%42,%43,%44,%45,%46,%47,%48,%49,%50,%51,%52,%53,%54,%55,%56,%57,%58,%59,%60,%61,%62,%63,%64,%65,%66,%67,%68,%69,%70,%71,%72,%73,%74,%75,%76,%77,%78,%79}, {%80,%81,%82,%83}, %84, p, 1, 1, 1; }"
   : "+f"(d[0]), "+f"(d[1]), "+f"(d[2]), "+f"(d[3]), "+f"(d[4]), "+f"(d[5]), "+f"(d[6]), "+f"(d[7]), "+f"(d[8]), "+f"(d[9]), "+f"(d[10]), "+f"(d[11]), "+f"(d[12]), "+f"(d[13]), "+f"(d[14]), "+f"(d[15]), "+f"(d[16]), "+f"(d[17]), "+f"(d[18]), "+f"(d[19]), "+f"(d[20]), "+f"(d[21]), "+f"(d[22]), "+f"(d[23]), "+f"(d[24]), "+f"(d[25]), "+f"(d[26]), "+f"(d[27]), "+f"(d[28]), "+f"(d[29]), "+f"(d[30]), "+f"(d[31]), "+f"(d[32]), "+f"(d[33]), "+f"(d[34]), "+f"(d[35]), "+f"(d[36]), "+f"(d[37]), "+f"(d[38]), "+f"(d[39]), "+f"(d[40]), "+f"(d[41]), "+f"(d[42]), "+f"(d[43]), "+f"(d[44]), "+f"(d[45]), "+f"(d[46]), "+f"(d[47]), "+f"(d[48]), "+f"(d[49]), "+f"(d[50]), "+f"(d[51]), "+f"(d[52]), "+f"(d[53]), "+f"(d[54]), "+f"(d[55]), "+f"(d[56]), "+f"(d[57]), "+f"(d[58]), "+f"(d[59]), "+f"(d[60]), "+f"(d[61]), "+f"(d[62]), "+f"(d[63]), "+f"(d[64]), "+f"(d[65]), "+f"(d[66]), "+f"(d[67]), "+f"(d[68]), "+f"(d[69]), "+f"(d[70]), "+f"(d[71]), "+f"(d[72]), "+f"(d[73]), "+f"(d[74]), "+f"(d[75]), "+f"(d[76]), "+f"(d[77]), "+f"(d[78]), "+f"(d[79]) : "r"(a0), "r"(a1), "r"(a2), "r"(a3), "l"(db), "r"(sd));
}
__device__ __forceinline__ void wgmma_rs_192_0(float* d, uint32_t a0, uint32_t a1, uint32_t a2, uint32_t a3, uint64_t db, int sd) {
  asm volatile("{ .reg .pred p; setp.ne.b32 p, %101, 0; wgmma.mma_async.sync.aligned.m64n192k16.f32.bf16.bf16 {%0,%1,%2,%3,%4,%5,%6,%7,%8,%9,%10,%11,%12,%13,%14,%15,%16,%17,%18,%19,%20,%21,%22,%23,%24,%25,%26,%27,%28,%29,%30,%31,%32,%33,%34,%35,%36,%37,%38,%39,%40,%41,%42,%43,%44,%45,%46,%47,%48,%49,%50,%51,%52,%53,%54,%55,%56,%57,%58,%59,%60,%61,%62,%63,%64,%65,%66,%67,%68,%69,%70,%71,%72,%73,%74,%75,%76,%77,%78,%79,%80,%81,%82,%83,%84,%85,%86,%87,%88,%89,%90,%91,%92,%93,%94,%95}, {%96,%97,%98,%99}, %100, p, 1, 1, 0; }"
   : "+f"(d[0]), "+f"(d[1]), "+f"(d[2]), "+f"(d[3]), "+f"(d[4]), "+f"(d[5]), "+f"(d[6]), "+f"(d[7]), "+f"(d[8]), "+f"(d[9]), "+f"(d[10]), "+f"(d[11]), "+f"(d[12]), "+f"(d[13]), "+f"(d[14]), "+f"(d[15]), "+f"(d[16]), "+f"(d[17]), "+f"(d[18]), "+f"(d[19]), "+f"(d[20]), "+f"(d[21]), "+f"(d[22]), "+f"(d[23]), "+f"(d[24]), "+f"(d[25]), "+f"(d[26]), "+f"(d[27]), "+f"(d[28]), "+f"(d[29]), "+f"(d[30]), "+f"(d[31]), "+f"(d[32]), "+f"(d[33]), "+f"(d[34]), "+f"(d[35]), "+f"(d[36]), "+f"(d[37]), "+f"(d[38]), "+f"(d[39]), "+f"(d[40]), "+f"(d[41]), "+f"(d[42]), "+f"(d[43]), "+f"(d[44]), "+f"(d[45]), "+f"(d[46]), "+f"(d[47]), "+f"(d[48]), "+f"(d[49]), "+f"(d[50]), "+f"(d[51]), "+f"(d[52]), "+f"(d[53]), "+f"(d[54]), "+f"(d[55]), "+f"(d[56]), "+f"(d[57]), "+f"(d[58]), "+f"(d[59]), "+f"(d[60]), "+f"(d[61]), "+f"(d[62]), "+f"(d[63]), "+f"(d[64]), "+f"(d[65]), "+f"(d[66]), "+f"(d[67]), "+f"(d[68]), "+f"(d[69]), "+f"(d[70]), "+f"(d[71]), "+f"(d[72]), "+f"(d[73]), "+f"(d[74]), "+f"(d[75]), "+f"(d[76]), "+f"(d[77]), "+f"(d[78]), "+f"(d[79]), "+f"(d[80]), "+f"(d[81]), "+f"(d[82]), "+f"(d[83]), "+f"(d[84]), "+f"(d[85]), "+f"(d[86]), "+f"(d[87]), "+f"(d[88]), "+f"(d[89]), "+f"(d[90]), "+f"(d[91]), "+f"(d[92]), "+f"(d[93]), "+f"(d[94]), "+f"(d[95]) : "r"(a0), "r"(a1), "r"(a2), "r"(a3), "l"(db), "r"(sd));
}
__device__ __forceinline__ void wgmma_ss_8_10(float* d, uint64_t da, uint64_t db, int sd) {
  asm volatile("{ .reg .pred p; setp.ne.b32 p, %6, 0; wgmma.mma_async.sync.aligned.m64n8k16.f32.bf16.bf16 {%0,%1,%2,%3}, %4, %5, p, 1, 1, 1, 0; }"
   : "+f"(d[0]), "+f"(d[1]), "+f"(d[2]), "+f"(d[3]) : "l"(da), "l"(db), "r"(sd));
}
__device__ __forceinline__ void wgmma_ss_160_01(float* d, uint64_t da, uint64_t db, int sd) {
  asm volatile("{ .reg .pred p; setp.ne.b32 p, %82, 0; wgmma.mma_async.sync.aligned.m64n160k16.f32.bf16.bf16 {%0,%1,%2,%3,%4,%5,%6,%7,%8,%9,%10,%11,%12,%13,%14,%15,%16,%17,%18,%19,%20,%21,%22,%23,%24,%25,%26,%27,%28,%29,%30,%31,%32,%33,%34,%35,%36,%37,%38,%39,%40,%41,%42,%43,%44,%45,%46,%47,%48,%49,%50,%51,%52,%53,%54,%55,%56,%57,%58,%59,%60,%61,%62,%63,%64,%65,%66,%67,%68,%69,%70,%71,%72,%73,%74,%75,%76,%77,%78,%79}, %80, %81, p, 1, 1, 0, 1; }"
   : "+f"(d[0]), "+f"(d[1]), "+f"(d[2]), "+f"(d[3]), "+f"(d[4]), "+f"(d[5]), "+f"(d[6]), "+f"(d[7]), "+f"(d[8]), "+f"(d[9]), "+f"(d[10]), "+f"(d[11]), "+f"(d[12]), "+f"(d[13]), "+f"(d[14]), "+f"(d[15]), "+f"(d[16]), "+f"(d[17]), "+f"(d[18]), "+f"(d[19]), "+f"(d[20]), "+f"(d[21]), "+f"(d[22]), "+f"(d[23]), "+f"(d[24]), "+f"(d[25]), "+f"(d[26]), "+f"(d[27]), "+f"(d[28]), "+f"(d[29]), "+f"(d[30]), "+f"(d[31]), "+f"(d[32]), "+f"(d[33]), "+f"(d[34]), "+f"(d[35]), "+f"(d[36]), "+f"(d[37]), "+f"(d[38]), "+f"(d[39]), "+f"(d[40]), "+f"(d[41]), "+f"(d[42]), "+f"(d[43]), "+f"(d[44]), "+f"(d[45]), "+f"(d[46]), "+f"(d[47]), "+f"(d[48]), "+f"(d[49]), "+f"(d[50]), "+f"(d[51]), "+f"(d[52]), "+f"(d[53]), "+f"(d[54]), "+f"(d[55]), "+f"(d[56]), "+f"(d[57]), "+f"(d[58]), "+f"(d[59]), "+f"(d[60]), "+f"(d[61]), "+f"(d[62]), "+f"(d[63]), "+f"(d[64]), "+f"(d[65]), "+f"(d[66]), "+f"(d[67]), "+f"(d[68]), "+f"(d[69]), "+f"(d[70]), "+f"(d[71]), "+f"(d[72]), "+f"(d[73]), "+f"(d[74]), "+f"(d[75]), "+f"(d[76]), "+f"(d[77]), "+f"(d[78]), "+f"(d[79]) : "l"(da), "l"(db), "r"(sd));
}
__device__ __forceinline__ void wgmma_ss_192_01(float* d, uint64_t da, uint64_t db, int sd) {
  asm volatile("{ .reg .pred p; setp.ne.b32 p, %98, 0; wgmma.mma_async.sync.aligned.m64n192k16.f32.bf16.bf16 {%0,%1,%2,%3,%4,%5,%6,%7,%8,%9,%10,%11,%12,%13,%14,%15,%16,%17,%18,%19,%20,%21,%22,%23,%24,%25,%26,%27,%28,%29,%30,%31,%32,%33,%34,%35,%36,%37,%38,%39,%40,%41,%42,%43,%44,%45,%46,%47,%48,%49,%50,%51,%52,%53,%54,%55,%56,%57,%58,%59,%60,%61,%62,%63,%64,%65,%66,%67,%68,%69,%70,%71,%72,%73,%74,%75,%76,%77,%78,%79,%80,%81,%82,%83,%84,%85,%86,%87,%88,%89,%90,%91,%92,%93,%94,%95}, %96, %97, p, 1, 1, 0, 1; }"
   : "+f"(d[0]), "+f"(d[1]), "+f"(d[2]), "+f"(d[3]), "+f"(d[4]), "+f"(d[5]), "+f"(d[6]), "+f"(d[7]), "+f"(d[8]), "+f"(d[9]), "+f"(d[10]), "+f"(d[11]), "+f"(d[12]), "+f"(d[13]), "+f"(d[14]), "+f"(d[15]), "+f"(d[16]), "+f"(d[17]), "+f"(d[18]), "+f"(d[19]), "+f"(d[20]), "+f"(d[21]), "+f"(d[22]), "+f"(d[23]), "+f"(d[24]), "+f"(d[25]), "+f"(d[26]), "+f"(d[27]), "+f"(d[28]), "+f"(d[29]), "+f"(d[30]), "+f"(d[31]), "+f"(d[32]), "+f"(d[33]), "+f"(d[34]), "+f"(d[35]), "+f"(d[36]), "+f"(d[37]), "+f"(d[38]), "+f"(d[39]), "+f"(d[40]), "+f"(d[41]), "+f"(d[42]), "+f"(d[43]), "+f"(d[44]), "+f"(d[45]), "+f"(d[46]), "+f"(d[47]), "+f"(d[48]), "+f"(d[49]), "+f"(d[50]), "+f"(d[51]), "+f"(d[52]), "+f"(d[53]), "+f"(d[54]), "+f"(d[55]), "+f"(d[56]), "+f"(d[57]), "+f"(d[58]), "+f"(d[59]), "+f"(d[60]), "+f"(d[61]), "+f"(d[62]), "+f"(d[63]), "+f"(d[64]), "+f"(d[65]), "+f"(d[66]), "+f"(d[67]), "+f"(d[68]), "+f"(d[69]), "+f"(d[70]), "+f"(d[71]), "+f"(d[72]), "+f"(d[73]), "+f"(d[74]), "+f"(d[75]), "+f"(d[76]), "+f"(d[77]), "+f"(d[78]), "+f"(d[79]), "+f"(d[80]), "+f"(d[81]), "+f"(d[82]), "+f"(d[83]), "+f"(d[84]), "+f"(d[85]), "+f"(d[86]), "+f"(d[87]), "+f"(d[88]), "+f"(d[89]), "+f"(d[90]), "+f"(d[91]), "+f"(d[92]), "+f"(d[93]), "+f"(d[94]), "+f"(d[95]) : "l"(da), "l"(db), "r"(sd));
}

#define HINT(x) x

__global__ void __cluster_dims__(2, 1, 1) __launch_bounds__(384, 1) fused_kernel(const __nv_bfloat16* __restrict__ pk, const __nv_bfloat16* __restrict__ pv,
    const __nv_bfloat16* __restrict__ pshift, const __nv_bfloat16* __restrict__ pssm, const __nv_bfloat16* __restrict__ pD, uint8_t* ps, const __grid_constant__ Params p) {
  extern __shared__ __align__(1024) uint8_t smem_raw[];
  const uint32_t t_start = clk();
  const uint32_t sb = smem_u32(smem_raw);
  const uint32_t bars = sb + O_BAR;
  const int tid = threadIdx.x, lane = tid & 31;
  const int warp = __shfl_sync(0xffffffffu, tid >> 5, 0);
  const int b = blockIdx.x, kh = b & 1;
  const int part = b / 20;
  auto BAR = [&](int i) { return bars + 8 * i; };
#define ROLE ROLE_(lds32(sb + O_ROLE))
#define ROLEU ROLE_(__shfl_sync(0xffffffffu, lds32(sb + O_ROLE), 0))
#define ROLE_(x) const int ro = x, rb = ro >> 3, cg = (ro >> 1) & 3, fs = kh * 4 + cg, vr = min(rb, 14) / 3, vt = min(rb, 14) % 3; \
  const uint32_t ord = vr == 3 ? 0x42310 : vr == 4 ? 0x32410 : 0x43210; uint8_t* const misc = ps + (pgo(rb, 0) ^ cgrp(G_M)); \
  (void)fs; (void)vt; (void)ord; (void)misc
  if (tid == 0) TSTAMP(63);
#define EPLOAD const uint32_t e0 = ldr(g_sync + Y_EP + b * 32 + (lane & (uint32_t)(uintptr_t)ps))
#define EPOCH const uint32_t ep = __shfl_sync(0xffffffffu, e0, 0) + 1
#define EPOCHU const uint32_t ep = __shfl_sync(0xffffffffu, lds32(sb + O_ROLE + 4), 0)

  if (warp < 4) {
    asm volatile("setmaxnreg.dec.sync.aligned.u32 40;");
    const int hw = warp - 2;
    if (warp == 0) {
      EPLOAD;
      const int u = b >> 1, cls = u < 4 ? 4 + u : u < 36 ? (u - 4) >> 3 : 4 + (u - 36) / 7, pos = u < 4 ? 7 : u < 36 ? (u - 4) & 7 : (u - 36) % 7;
      const uint32_t pa = (pgo(2 * cls, 7) ^ cgrp(G_M)) + pos * 128;
      if (!kh && lane < 4) stg128(ps + (pa ^ (lane & 2) << 11) + (lane & 1) * 16, 0, 0, 0, 0);
      bar_sync(1, 384);
      asm volatile("barrier.cluster.arrive.relaxed.aligned;" ::: "memory");
      uint32_t far = 0;
      if (!kh && lane == 0) {
        uint32_t x, y;
        TSTAMP(113);
        asm volatile("atom.relaxed.gpu.global.exch.b32 %0, [%2], 0;\n atom.relaxed.gpu.global.exch.b32 %1, [%3], 0;" : "=r"(x), "=r"(y) : "l"(ps + pa), "l"(ps + (pa ^ 4096)) : "memory");
        asm volatile("{ .reg .pred p; setp.ne.u32 p, %0, 0; @p trap; mov.u32 %0, %%clock; }" : "+r"(x)::"memory");
        asm volatile("{ .reg .pred p; setp.ne.u32 p, %0, 0; @p trap; mov.u32 %0, %%clock; }" : "+r"(y)::"memory");
        far = y - x;
        TSTAMP(11);
      }
      EPOCH;
      if (lane == 0) TSTAMP(114);
      {
        uint32_t* f = g_sync + Y_CLS + cls * 32;
        if (!kh && lane == 0) str(f + pos, ep << 4 | (far < 100) << 3 | pos);
        uint32_t v;
        int it = 0;
        do v = ldr(f + (lane & 7)); while (__any_sync(0xffffffffu, (v ^ ep << 4) > 15) && ++it < 100000);
        const uint32_t rank = __popc(__ballot_sync(0xffffffffu, v < __shfl_sync(0xffffffffu, v, pos)) & 255);
        if (lane == 0) sts64(sb + O_ROLE, cls * 16 + rank * 2 + kh, ep);
        if (lane == 0) { mbar_arrive(BAR(B_ROLE)); TSTAMP(0); }
        __syncwarp();
      }
      ROLEU;
      {
        const uint32_t* f = g_sync + Y_KV + (min(lane, 4) * 4 + (b >> 5)) * 32;
        uint32_t pend = 31;
        int it = 0;
        do {
          uint32_t v = ep * 32;
          HINT(if ((pend >> lane) & 1) v = ldr(f));
          uint32_t m = __ballot_sync(0xffffffffu, (int)(v - ep * 32) >= 0 || ++it > 100000) & pend;
          pend &= ~m;
          for (; m; m &= m - 1) {
            const int j = __ffs(m) - 1;
            if (elect()) {
              TSTAMP(2 + j);
              mbar_expect(BAR(B_KV + j), 4096);
              bulk_ld(sb + bnd(j) + U_KV, ps + (pgo(b >> 3, b & 7) ^ cgrp(G_KV + j)), 4096, BAR(B_KV + j));
            }
          }
        } while (pend);
      }
      auto loadW = [&](int slot, int ph, int k0) {
        mbar_wait(BAR(B_EMPTY + slot), ph);
        if (elect()) {
          mbar_expect(BAR(B_FULL + slot), SLOT);
          tma3d(sb + slot * SLOT, &p.m_wg, 0, k0, fs * 3, BAR(B_FULL + slot));
          tma3d(sb + slot * SLOT + 12288, &p.m_wu, 0, k0, fs * 3, BAR(B_FULL + slot));
        }
      };
#pragma unroll 1
      for (int s = 0; s < 3; s++) loadW(s + 2, 0, s * 32);
      if (lane == 0) TSTAMP(10);
      int slot = 2, ph = 0;
      uint32_t xv = ep * 16 - 1;
#pragma unroll 1
      for (int s = 0; s < 20; s++) {
        const int rd = (ord >> (s & 28)) & 7;
        const uint32_t o = tile(rb, G_X, rd * 4 + (s & 3));
        if (s > 2) loadW(slot, ph, rd * 128 + (s & 3) * 32);
        HINT(poll_lane(xv, misc + M_X + lane * 4, ep * 16, rd * 2 + ((s >> 1) & 1)));
        if (elect()) {
          tma3d(sb + slot * SLOT + 24576, &p.m_s, 0, (o & 16383) >> 9, o >> 14, BAR(B_FULL + slot));
          if (s == 0) TSTAMP(19);
          if (s == 16) TSTAMP(1);
        }
        if (++slot == 6) { slot = s == 3 ? 2 : 0; ph ^= 1; }
      }
#pragma unroll 1
      for (int s = 0; s < 12; s++) {
        const int e = s % 5;
        const uint32_t d = sb + w2entry(e), st = e == 3 ? SLOT : 8192;
        const int k0 = kh * 768 + (s < 3 ? cg * 192 + s * 64 : ((cg + 1 + s % 3) & 3) * 192 + (s / 3 - 1) * 64), c0 = cg * 160 + (cg & 1) * 32;
        if (s >= 5) mbar_wait(BAR(B_W2E + e), s >= 10);
        else if (s != 3) mbar_wait(BAR(B_EMPTY + s + 1), 0);
        if (elect()) {
          mbar_expect(BAR(B_W2F + e), 24576);
          tma2d(d, &p.m_w2a, c0, k0, BAR(B_W2F + e));
          tma2d(d + st, &p.m_w2a, c0 + 64, k0, BAR(B_W2F + e));
          tma3d(d + 2 * st, &p.m_w2b, 0, k0, cg * 5 + (~cg & 1) * 4, BAR(B_W2F + e));
        }
      }
      mbar_wait(BAR(B_W2E + 2), 1);
      __syncwarp();
      asm volatile("barrier.cluster.wait.aligned;" ::: "memory");
      if (lane == 0)
        asm volatile("{ .reg .b32 r; mapa.shared::cluster.u32 r, %0, %1; mbarrier.arrive.shared::cluster.b64 _, [r]; }" ::"r"(BAR(B_RDY)), "r"(kh ^ 1) : "memory");
    } else {
      if (warp == 1) {
        bar_sync(1, 384);
        asm volatile("barrier.cluster.arrive.relaxed.aligned;" ::: "memory");
        if (lane == 0) TSTAMP(112);
        unrolled<NLD>([&](auto I) {
          constexpr uint32_t e = nth_load(I.v), n = e & 15, kind = (e >> 4) & 15;
          while (clk() - t_start < (e >> 8)) {}
          if (kind == 1 && n == 5) mbar_wait(BAR(B_ROLE), 0);
          if (elect()) {
            if constexpr (kind == 0) {
              const uint32_t d = sb + kreg(n), bar = BAR(B_KIN + n);
              const int ch = n * 128 + (b & 3) * 32, tg = (b >> 2) * 8;
              mbar_expect(bar, 9984);
              tma3d(d, &p.m_k, ch, tg, 0, bar);
              tma3d(d + voff(n), &p.m_v, ch, tg, 0, bar);
              tma3d(d + 4096, &p.m_kh, ch, tg - 1, 5, bar);
              bulk_ld(d + 5632, pshift + ch * 4, 256, bar);
            } else if constexpr (kind == 1 && n < 5) {
              mbar_expect(BAR(B_SSM + n), 4096);
              bulk_ld(sb + bnd(n) + U_RAW, pssm + (size_t)(n * 128 + b) * S_, 4096, BAR(B_SSM + n));
            } else if constexpr (kind == 1) {
              mbar_expect(BAR(B_RED), 20480);
              mbar_expect(BAR(B_QIN), 20480);
              tma3d(sb + O_REG, &p.m_q, 0, lds32(sb + O_ROLE) * 16, 0, BAR(B_QIN));
            } else if constexpr (kind == 2) {
              if (b < 120 && min(part, 2) == n) {
                const int x = (b >> 1) % 10, col = part < 5 ? (x >> 1) * D_ + part * 128 + (x & 1) * 64 : 5 * D_ + x * 64;
                mbar_expect(BAR(B_WM), 40960);
                tma2d(sb, &p.m_wm, col, kh * 320, BAR(B_WM));
                tma2d(sb + 20480, &p.m_wm, col, kh * 320 + 160, BAR(B_WM));
              }
            } else {
              bulk_pf((kh ? p.wu : p.wg) + (b >> 1) * 2 * F_, 6144);
            }
            TSTAMP(96 + I.v);
          }
        });
        ROLEU;
        EPOCHU;
#pragma unroll 1
        for (int jj = 0; jj < 5; jj++) {
          const int j = (ord >> (jj * 4)) & 7;
          const uint32_t ma = sb + (jj & 1 ? O_ST : O_MA);
          uint32_t pend = 3;
          auto watch = [&](uint32_t need) {
            int it = 0;
            while (pend & need) {
              const uint32_t target = ep * (lane ? 20 : 128);
              uint32_t v = target;
              HINT(if ((pend >> lane) & 1) v = ldr(g_sync + (lane ? Y_MOD : Y_Y) + j * 32));
              const uint32_t m = __ballot_sync(0xffffffffu, (int)(v - target) >= 0 || ++it > 100000) & pend;
              if ((m & 1) && elect()) {
                if (jj < 2) TSTAMP(47 + jj);
                mbar_expect(BAR(B_YF + (jj & 1)), 4096);
                bulk_ld(sb + (jj & 1 ? O_BP : O_Y), ps + (pgo(rb, ro & 7) ^ cgrp(G_Y + j)), 4096, BAR(B_YF + (jj & 1)));
              }
              pend &= ~m;
            }
          };
          if (jj >= 2) mbar_wait(BAR(B_YE + (jj & 1)), jj >> 2);
          watch(2);
#pragma unroll 1
          for (int i = 0; i < 64; i += 32) {
            const int t = i + lane;
            uint2 v[10];
            uint32_t bad;
            int it = 0;
            do {
              bad = 0;
#pragma unroll
              for (int k = 0; k < 10; k++) v[k] = ldr2(g_mod + j * 2 * D_ + k * 128 + t * 2);
#pragma unroll
              for (int k = 0; k < 10; k++) bad |= (v[k].x ^ ep) | (v[k].y ^ ep);
            } while (__any_sync(0xffffffffu, bad & 3) && ++it < 100000);
            auto vec = [&](int k) { return pack2(__uint_as_float(v[k].x) + __uint_as_float(v[k + 5].x), __uint_as_float(v[k].y) + __uint_as_float(v[k + 5].y)); };
            const uint32_t ga = vec(2);
            uint32_t cc = hadd2(vec(4), 0x3F803F80u);
            if (!(cc & 0x7FFF)) cc |= 0x2B80;
            if (!(cc & 0x7FFF0000)) cc |= 0x2B800000;
            sts32(ma + t * 4, hmul2(ga, hadd2(vec(1), 0x3F803F80u)));
            sts32(ma + 256 + t * 4, hmul2(ga, vec(0)));
            sts32(ma + 512 + t * 4, cc);
            const uint32_t d = j * 128 + t * 2 - cg * 160;
            if (d < 160) sts64(sb + O_IC + (!(cg & 1) ? d : d < 32 ? d + 128 : d - 32) * 4, __float_as_uint(__fdividef(1.f, blo(cc))), __float_as_uint(__fdividef(1.f, bhi(cc))));
            if (j == vr) {
              sts32(sb + O_CS + (t >> 2) * 32 + (t & 3) * 4, cc);
              sts32(sb + O_CS + (t >> 2) * 32 + (t & 3) * 4 + 16, vec(3));
              fence_async_smem();
            }
          }
          __syncwarp();
          if (lane == 0) {
            mbar_arrive(BAR(B_PR + 4 * (jj & 1)));
            if (j == vr) mbar_arrive(BAR(B_CS));
            if (jj < 3) TSTAMP(jj < 2 ? 7 + jj : 79);
          }
          watch(1);
          if (jj == 0 && elect()) {
            bulk_pf((kh ? p.wu : p.wg) + (128 + (b >> 1) * 2) * F_, 6144);
            bulk_pf((kh ? p.wu : p.wg) + (256 + (b >> 1) * 6) * F_, 18432);
            bulk_pf(p.w2 + b * 7680, 15360);
            TSTAMP(61);
          }
        }
        HINT(poll_ge(g_sync + Y_MOD + 160, ep * 20));
#pragma unroll 1
        for (int i = 0; i < 2; i++) {
          if (i == 0 || lane < 8) {
            const float4 s = gather4<2>(g_mod + 10 * D_ + cg * 160 + (i ? (~cg & 1) * 128 : (cg & 1) * 32) + lane * 4, D_, ep);
            sts128(sb + O_GB + i * 512 + lane * 16, __float_as_uint(rbf(s.x)), __float_as_uint(rbf(s.y)), __float_as_uint(rbf(s.z)), __float_as_uint(rbf(s.w)));
          }
        }
        if (lane == 0) { sts128(sb + O_BP + 6144, 0, 0, 0, 0); mbar_arrive(BAR(B_VV)); }
        mbar_wait(BAR(B_YE + 1), 1);
      } else {
        const int t0 = tid & 63;
#pragma unroll
        for (int j = 0; j < 5; j++) {
          if (tid < 83) sts128(sb + bnd(j) + (lane < 17 ? U_KV + 4096 + lane * 16 : lane == 17 ? U_RAW - 16 : U_ODD - 16), 0, 0, 0, 0);
        }
        bar_sync(1, 384);
        asm volatile("barrier.cluster.arrive.relaxed.aligned;" ::: "memory");
        fence_async_smem();
        uint32_t dv;
        asm volatile("ld.global.nc.u16 %0, [%1];" : "=r"(dv) : "l"(pD + min(lane, 4) * 128 + b) : "memory");
        if (elect()) {
#pragma unroll
          for (int i = 0; i < 6; i++) asm volatile("prefetch.tensormap [%0];" ::"l"(&p.m_k + hw * 6 + i) : "memory");
        }
        asm volatile("prefetch.global.L2 [%0];" ::"l"(p.c + kh * 320 + min(t0, 39) * 8) : "memory");
#pragma unroll 1
        for (int j = 0; j < 5; j++) {
          const uint32_t ra = sb + bnd(j) + U_RAW + hw * 2048 + lane * 16;
          const float dj = blo(__shfl_sync(0xffffffffu, dv, j));
          mbar_wait(BAR(B_SSM + j), 0);
          if (tid == 64 && j == 0) TSTAMP(77);
#pragma unroll
          for (int i = 0; i < 4; i++) {
            uint4 w = lds128(ra + i * 512);
            const uint32_t pv = lds32(ra + i * 512 - 4);
            if (i == 0 && tid == 64) { w.x = prmt(pack2(blo(w.x) + dj, 0.f), w.x, 0x7610); sts32(ra, w.x); }
            sts128(ra + (U_ODD - U_RAW) + i * 512, prmt(pv, w.x, 0x5432), prmt(w.x, w.y, 0x5432), prmt(w.y, w.z, 0x5432), prmt(w.z, w.w, 0x5432));
          }
          __syncwarp();
          if (lane == 0) mbar_arrive(BAR(B_PL + j));
          if (tid == 64) TSTAMP(32 + j);
          if (j == 0) {
            const uint4 cv = ldr4((const uint32_t*)p.c + kh * 160 + min(t0, 39) * 4);
            auto silu = [](uint32_t x) { return pack2(__fdividef(blo(x), 1.f + __expf(-blo(x))), __fdividef(bhi(x), 1.f + __expf(-bhi(x)))); };
            sts128(sb + O_SILU + t0 * 16, silu(cv.x), silu(cv.y), silu(cv.z), silu(cv.w));
            fence_async_smem();
          }
        }
        mbar_wait(BAR(B_LN), 0);
        ROLEU;
        uint32_t ya = lane * 32 + (lane & 4) * 4, xl = (lane ^ lane >> 3) * 16, pl = (lane & 3) * 16;
        const uint32_t tt = -(lds32(sb + O_ROLE + 4) & 1), ln[2] = {lds32(sb + O_LN + (lane & 28)), lds32(sb + O_LN + 32 + (lane & 28))};
        float sx[4] = {0.f, 0.f, 0.f, 0.f};
        keep(ya); keep(xl); keep(pl);
#pragma unroll 1
        for (int it = 0; it != 10;) {
          const int j = (ord >> (it * 2 & 28)) & 7, odd = (it >> 1) & 1, g = (it & 1) * 2 + hw;
          const uint32_t pm = sb + (odd ? O_ST : O_MA) + g * 64, yo = sb + (odd ? O_BP : O_Y) + g * 1024, qo = sb + O_REG + (j * 4 + g) * 1024;
          uint32_t q[8], m[8], y[8];
          mbar_wait(BAR(B_PR + 4 * odd), (it >> 2) & 1);
          {
            const uint4 q0 = lds128(addu(xl, qo)), a4 = lds128(addu(pl, pm)), b4 = lds128(addu(pl, pm) + 256), q1 = lds128(addu(xl, qo) + 512);
            const uint32_t ma[4] = {a4.x, a4.y, a4.z, a4.w}, mb[4] = {b4.x, b4.y, b4.z, b4.w};
            q[0] = q0.x; q[1] = q0.y; q[2] = q0.z; q[3] = q0.w; q[4] = q1.x; q[5] = q1.y; q[6] = q1.z; q[7] = q1.w;
#pragma unroll
            for (int i = 0; i < 8; i++) m[i] = hfma2(hfma2lh(q[i], ln[i >> 2]), ma[i & 3], mb[i & 3]);
          }
          mbar_wait(BAR(B_YF + odd), (it >> 2) & 1);
          if (!(xl | hw) && it < 6 && !(it & 1)) TSTAMP(it == 0 ? 49 : it == 2 ? 58 : 80);
          ldsm4t(addu(ya, yo), y[0], y[1], y[2], y[3]);
          ldsm4t(addu(ya, yo) ^ 16, y[4], y[5], y[6], y[7]);
#pragma unroll
          for (int i = 0; i < 8; i++) q[i] = hfma2(m[i], y[i], q[i]);
          if ((__ballot_sync(0xffffffffu, ((y[0] ^ tt) | (y[1] ^ tt) | (y[2] ^ tt) | (y[3] ^ tt) | (y[4] ^ tt) | (y[5] ^ tt) | (y[6] ^ tt) | (y[7] ^ tt)) & 0x00010001u) & 15) && it < 16) {
#pragma unroll 1
            for (int hf = 0; hf < 32; hf += 16) refetch16(ps + ((pgo(rb, ro & 7) ^ cgrp(G_Y + j)) + g * 1024 + (ya ^ hf)), (ya ^ hf) + yo, tt);
            __syncwarp();
            it += 16;
            continue;
          }
          const uint4 c4 = lds128(addu(pl, pm) + 512);
          uint8_t* const xg = ps + addu(xl, tile(rb, G_X, j * 4 + g) + (ro & 4) * 4096 + (ro & 3) * 1024);
          stg128(xg, tag0(hmul2(q[0], c4.x), tt), hmul2(q[1], c4.y), hmul2(q[2], c4.z), hmul2(q[3], c4.w));
          stg128(xg + 512, tag0(hmul2(q[4], c4.x), tt), hmul2(q[5], c4.y), hmul2(q[6], c4.z), hmul2(q[7], c4.w));
          asm volatile("{ .reg .pred p; elect.sync _|p, 0xffffffff; @p red.relaxed.gpu.global.add.u32 [%0], 1; @p mbarrier.arrive.shared::cta.b64 _, [%1]; }"
                       ::"l"(misc + M_X + j * 8 + (it & 1) * 4), "r"(BAR(B_YE + odd)) : "memory");
#pragma unroll
          for (int i = 0; i < 8; i++) {
            const float f = blo(q[i]), h = bhi(q[i]);
            float &s1 = sx[(i >> 2) * 2], &s2 = sx[(i >> 2) * 2 + 1];
            s1 += f; s2 = fmaf(f, f, s2); s1 += h; s2 = fmaf(h, h, s2);
          }
          if (!(xl | hw) && (it & 1)) TSTAMP(12 + ((it & 15) >> 1));
          if (!(xl | hw) && it == 0) TSTAMP(116);
          it = (it & 15) + 1;
        }
        const int lane = ya >> 5, t = hw * 32 + lane;
        EPOCHU;
#pragma unroll
        for (int i = 0; i < 8; i++) sx[i & 3] += __shfl_xor_sync(0xffffffffu, sx[i & 3], (i >> 2) + 1);
        if (!(lane & 3)) sts64(sb + O_SX + t * 2, __float_as_uint(hw ? sx[0] : sx[2]), __float_as_uint(hw ? sx[1] : sx[3]));
        bar_sync(4, 64);
        const float2 so = lds64f(sb + O_SX + (hw ^ 1) * 64 + (xl >> 6) * 8);
        const float mean = ((hw ? sx[2] : sx[0]) + so.x) * (1.f / D_);
        const uint32_t pa = pack2(-mean, sqrtf(fmaxf(((hw ? sx[3] : sx[1]) + so.y) * (1.f / D_) - mean * mean, 0.f) + 1e-5f));
        if (!(lane & 3))
          asm volatile("st.relaxed.gpu.global.v2.u32 [%0], {%1,%2};" ::"l"(misc + M_ST + (ro & 7) * 128 + t * 2), "r"(pa), "r"(tagf(__fdividef(1.f, bhi(pa) * bhi(pa)), ep)) : "memory");
        uint4 v;
        int it = 0;
        do v = ldr4((const uint32_t*)(misc + M_ST + t * 16)); while ((((v.y ^ ep) | (v.w ^ ep)) & 3) && ++it < 100000);
        sts128(sb + O_ST + t * 16, v.x, v.y, v.z, v.w);
        __syncwarp();
        if (lane == 0) mbar_arrive(BAR(B_ST + hw));
        if (t == 0) TSTAMP(52);
      }
      ROLEU;
      EPOCHU;
      int lane;
      asm volatile("mov.u32 %0, %%laneid;" : "=r"(lane));
      {
        HINT(poll_ge(g_sync + Y_VV + fs * 32, ep * 32));
        uint32_t v[20], bad;
        int it = 0;
        const uint32_t* g = g_vv + fs * 1920 + (hw + 1) * 128 + lane;
        do {
          bad = 0;
#pragma unroll
          for (int k = 0; k < 20; k++) v[k] = ldr(g + ((k % 5) * 384 + (k / 5) * 32));
#pragma unroll
          for (int k = 0; k < 20; k++) bad |= v[k] ^ ep;
        } while (__any_sync(0xffffffffu, bad & 1) && ++it < 100000);
#pragma unroll
        for (int k = 0; k < 4; k++) sts128(sb + O_BP + ((hw + 1) * 128 + k * 32 + lane) * 16, v[5 * k], v[5 * k + 1], v[5 * k + 2], hadd2(v[5 * k + 3], v[5 * k + 4]));
        fence_async_smem();
        __syncwarp();
      }
      if (lane == 0) mbar_arrive(BAR(B_VV));
      if (warp == 1) {
        if (lane == 0) TSTAMP(37);
        mbar_wait(BAR(B_STAGED + 3), 0);
        if (elect()) {
          mbar_expect(BAR(B_X1), 20480);
#pragma unroll 1
          for (int x = 0; x < 5; x++) bulk_ld(sb + O_REG + x * 4096, ps + tile(rb, G_X, cg * 5 + (x + (cg & 1)) % 5) + (kh ^ 1) * 16384, 4096, BAR(B_X1));
        }
      } else {
        const uint32_t reg = sb + (hw ? 0 : 4 * SLOT);
        const int t0 = (hw ^ kh) * 24 + kh * 12;
        uint32_t* flags = (uint32_t*)(misc + M_H + (kh * 2 + hw) * 64);
#pragma unroll 1
        for (int i = 0; i < 3; i++) {
          const uint32_t o = tile(rb, G_H, t0 + cg * 3 + i);
          mbar_wait(BAR(B_STAGED + hw * 3 + i), 0);
          if (elect()) {
            tma3d_store(&p.m_s, reg + i * 8192, 0, (o & 16383) >> 9, o >> 14);
            bulk_commit();
            if (i) { bulk_wait<1>(); str(flags + cg, ep * 4 + i - 1); }
            if (i == 2) { bulk_wait<0>(); str(flags + cg, ep * 4 + 2); TSTAMP(17 + hw); }
          }
        }
        uint32_t hv = ep * 4 - 1;
#pragma unroll 1
        for (int i = 0; i < 9; i++) {
          const int oc = (cg + 1 + i % 3) & 3, e = (i + 3) & 3;
          const uint32_t o = tile(rb, G_H, t0 + oc * 3 + i / 3);
          HINT(poll_lane(hv, flags + (lane & 3), ep * 4 + i / 3, oc));
          if (i >= 4) mbar_wait(BAR(B_HE + hw * 4 + e), ((i >> 2) - 1) & 1);
          if (elect()) {
            mbar_expect(BAR(B_HF + hw * 4 + e), 8192);
            tma3d(reg + e * 8192, &p.m_s, 0, (o & 16383) >> 9, o >> 14, BAR(B_HF + hw * 4 + e));
          }
        }
      }
      __syncwarp();
      asm volatile("barrier.cluster.wait.aligned;" ::: "memory");
    }
  } else {
    const int isE = warp >= 8 ? 1 : 0;
    const int w = warp & 3, r = lane >> 2, c = lane & 3;
    const bool lead = (tid & 127) == 0;
    const int tb = b >> 2;
    if (isE) {
      const int u = tid & 127, t = tb * 64 + r * 8 + w, th = t - (w == 3 ? 0 : 3);
      const uint32_t d = sb + kreg(0) + (u >> 2) * 64 + ((c ^ (r >> 1)) << 4);
      const int o = t * D_ + (b & 3) * 32 + c * 8;
      cpa16(d, pk + o, 16); cpa16(d + voff(0), pv + o, 16);
      cpa16(d + 2048, pk + o + 4 * D_, 16); cpa16(d + voff(0) + 2048, pv + o + 4 * D_, 16);
      if (u < 112) cpa16(w == 3 ? sb + kreg(0) + 5632 + lane * 16 : d + 4096, w == 3 ? pshift + (b & 3) * 128 + lane * 8 : pk + (th < 0 ? o : o - 3 * D_), th < 0 ? 0 : 16);
      if (lead) TSTAMP(74);
    } else {
      if (lane == 0) {
#pragma unroll
        for (int i = 0; i < 21; i++) mbar_init(BAR(w + 4 * i), i < 4 ? 2 : i < 6 || i == 20 ? 4 : 1);
        asm volatile("fence.mbarrier_init.release.cluster;" ::: "memory");
      }
      __syncwarp();
      if (lead) TSTAMP(76);
    }
    EPLOAD;
    bar_sync(1, 384);
    if (tid == 256) TSTAMP(75);
    asm volatile("setmaxnreg.inc.sync.aligned.u32 232;");
    asm volatile("barrier.cluster.arrive.relaxed.aligned;" ::: "memory");
    EPOCH;
    if (isE) {
      asm volatile("cp.async.wait_all;" ::: "memory");
      bar_sync(6, 128);
    }
    uint64_t steps = isE ? sched(1) : sched(0);
    const uint32_t rel = isE ? release(1) : release(0);
#pragma unroll 1
    for (int si = 0; steps; si++, steps >>= 9) {
      const uint32_t todo = (uint32_t)steps;
      if (todo & 1) {
        uint4 x[10];
        mbar_wait(BAR(B_QIN), 0);
        if (lead) TSTAMP(9);
#pragma unroll
        for (int i = 0; i < 10; i++) x[i] = lds128(sb + O_REG + (lane >> 4) * 1024 + w * 256 + (lane & 15) * 16 + i * 2048);
        float z[4] = {0.f, 0.f, 0.f, 0.f};
        auto acc = [&](uint32_t v) { const float f = blo(v), g = bhi(v); z[0] += f; z[1] = fmaf(f, f, z[1]); z[2] += g; z[3] = fmaf(g, g, z[3]); };
#pragma unroll
        for (int i = 0; i < 10; i++) { acc(x[i].x); acc(x[i].y); acc(x[i].z); acc(x[i].w); }
        z[0] += z[2]; z[1] += z[3];
#pragma unroll
        for (int i = 0; i < 3; i++) { z[0] += __shfl_xor_sync(0xffffffffu, z[0], i < 2 ? i + 1 : 16); z[1] += __shfl_xor_sync(0xffffffffu, z[1], i < 2 ? i + 1 : 16); }
        const float mean = z[0] * (1.f / D_), rs = rbf(rsqrtf(fmaxf(z[1] * (1.f / D_) - mean * mean, 0.f) + 1e-5f));
        if (!(lane & 19)) sts32(sb + O_LN + w * 16 + lane, pack2(rs, -mean * rs));
        __syncwarp();
        if (lane == 0) mbar_arrive(BAR(B_LN));
        if (lead) TSTAMP(59);
      }
      if (todo & 14) {
        const int n = ((todo >> 1) & 7) - 1, tg = lane & 7;
        const uint32_t a = sb + kreg(n) + tg * 64 + ((w ^ (tg >> 1)) << 4) + (lane >> 3) * 4;
        if (n) mbar_wait(BAR(B_KIN + n), 0);
        if (lead) TSTAMP(69 + n);
        uint32_t kk[11], x[8];
        const uint4 sw = lds128(sb + kreg(n) + 5632 + w * 64 + (lane & 24) * 2);
#pragma unroll
        for (int i = 0; i < 11; i++) kk[i] = lds32(a + (i < 3 ? 4096 + i * 512 : (i - 3) * 512));
#pragma unroll
        for (int i = 0; i < 8; i++) x[7 - i] = lds32(a + voff(n) + i * 512);
        const uint32_t w0 = prmt(sw.x, sw.z, 0x5410), w1 = prmt(sw.x, sw.z, 0x7632), w2 = prmt(sw.y, sw.w, 0x5410), w3 = prmt(sw.y, sw.w, 0x7632);
#pragma unroll
        for (int i = 0; i < 8; i++) x[7 - i] = hmul2(hfma2(kk[i + 3], w0, hfma2(kk[i + 2], w1, hfma2(kk[i + 1], w2, hmul2(kk[i], w3)))), x[7 - i]);
        const int tw = (~tb & 7) ^ ((~lane & 1) << 2);
#pragma unroll
        for (int i = 0; i < 4; i++) x[2 * i] = settag(x[2 * i], tw == i ? 0x00010001u : 0u, -(ep & 1));
        const uint32_t o = (pgo((b & 3) * 4 + w, (lane >> 3) * 2) ^ cgrp(G_KV + n)) + 4080 - tb * 128 - tg * 16;
        stg128(ps + o, prmt(x[0], x[1], 0x5410), prmt(x[2], x[3], 0x5410), prmt(x[4], x[5], 0x5410), prmt(x[6], x[7], 0x5410));
        stg128(ps + (o ^ 0x3000), prmt(x[0], x[1], 0x7632), prmt(x[2], x[3], 0x7632), prmt(x[4], x[5], 0x7632), prmt(x[6], x[7], 0x7632));
        bar_sync(5 + isE, 128);
        if (lead) { hint_add(g_sync + Y_KV + (n * 4 + (b & 3)) * 32); TSTAMP(64 + n); }
      }
      if (b < 120 && ((todo >> 4) & 3) == min(part, 2) + 1) {
        float d[4];
        const uint64_t db = mkdesc(sb + O_SILU, 16, 128, 0), da = mkdesc(sb, 4096, 1024, 1);
        mbar_wait(BAR(B_PL + 1), 0);
        mbar_wait(BAR(B_WM), 0);
        if (lead) TSTAMP(81 + min(part, 2));
        wg_fence();
#pragma unroll
        for (int kk = 0; kk < 20; kk++) wgmma_ss_8_10(d, da + kk * 128, db + kk * 2, kk);
        wg_commit();
        wg_wait<0>();
        regfence<4>(d);
        uint32_t* g = g_mod + (part * 2 + kh) * D_ + (b >> 1) % 10 * 64 + w * 16 + r;
        if (c == 0) { str(g, tagf(d[0], ep)); str(g + 8, tagf(d[2], ep)); }
        bar_sync(5 + isE, 128);
        if (lead) { hint_add(g_sync + Y_MOD + part * 32); TSTAMP(part >= 2 ? 60 : 20 + part); }
      }
      if (todo & 448) {
        const int j = ((todo >> 6) & 7) - 1, u = tid & 127;
        const uint32_t ub = sb + bnd(j), sa = ub + ((r & 1) ? U_RAW : U_ODD) + 4 * (8 * w + (r >> 1) - 3 + c);
        uint32_t A[64];
        float d[128];
        mbar_wait(BAR(B_PL + j), 0);
#pragma unroll
        for (int g = 0; g < 16; g++) { A[4 * g] = lds32(sa + g * 256); A[4 * g + 1] = lds32(sa + g * 256 + 128); A[4 * g + 2] = lds32(sa + g * 256 + 16); A[4 * g + 3] = lds32(sa + g * 256 + 144); }
        if (lead) TSTAMP(89 + j);
        mbar_wait(BAR(B_KV + j), 0);
        if ((lds32(ub + U_KV + u * 32 + r * 4) ^ ep) & 1) refetch(ps + (pgo(b >> 3, b & 7) ^ cgrp(G_KV + j)) + u * 32, r * 4, ub + U_KV + u * 32, ep);
        __syncwarp();
        bar_sync(5 + isE, 128);
        if (lead) TSTAMP(53 + j);
        const uint64_t db = mkdesc(ub + U_KV, 16, 128, 0);
        wg_fence();
        wgmma_rs_32_0(d + 0, A[0], A[1], A[2], A[3], db + 0, 0);
        wgmma_rs_32_0(d + 16, A[0], A[1], A[2], A[3], db + 32, 0);
        wgmma_rs_32_0(d + 32, A[0], A[1], A[2], A[3], db + 64, 0);
        wgmma_rs_32_0(d + 48, A[0], A[1], A[2], A[3], db + 96, 0);
        wgmma_rs_32_0(d + 0, A[4], A[5], A[6], A[7], db + 16, 1);
        wgmma_rs_32_0(d + 16, A[4], A[5], A[6], A[7], db + 48, 1);
        wgmma_rs_32_0(d + 32, A[4], A[5], A[6], A[7], db + 80, 1);
        wgmma_rs_32_0(d + 48, A[4], A[5], A[6], A[7], db + 112, 1);
        wgmma_rs_32_0(d + 0, A[8], A[9], A[10], A[11], db + 32, 1);
        wgmma_rs_32_0(d + 16, A[8], A[9], A[10], A[11], db + 64, 1);
        wgmma_rs_32_0(d + 32, A[8], A[9], A[10], A[11], db + 96, 1);
        wgmma_rs_32_0(d + 64, A[0], A[1], A[2], A[3], db + 128, 0);
        wgmma_rs_32_0(d + 0, A[12], A[13], A[14], A[15], db + 48, 1);
        wgmma_rs_32_0(d + 16, A[12], A[13], A[14], A[15], db + 80, 1);
        wgmma_rs_32_0(d + 32, A[12], A[13], A[14], A[15], db + 112, 1);
        wgmma_rs_32_0(d + 48, A[8], A[9], A[10], A[11], db + 128, 1);
        wgmma_rs_32_0(d + 0, A[16], A[17], A[18], A[19], db + 64, 1);
        wgmma_rs_32_0(d + 16, A[16], A[17], A[18], A[19], db + 96, 1);
        wgmma_rs_32_0(d + 32, A[16], A[17], A[18], A[19], db + 128, 1);
        wgmma_rs_32_0(d + 64, A[4], A[5], A[6], A[7], db + 144, 1);
        wgmma_rs_32_0(d + 0, A[20], A[21], A[22], A[23], db + 80, 1);
        wgmma_rs_32_0(d + 16, A[20], A[21], A[22], A[23], db + 112, 1);
        wgmma_rs_32_0(d + 48, A[12], A[13], A[14], A[15], db + 144, 1);
        wgmma_rs_32_0(d + 32, A[20], A[21], A[22], A[23], db + 144, 1);
        wgmma_rs_32_0(d + 0, A[24], A[25], A[26], A[27], db + 96, 1);
        wgmma_rs_32_0(d + 16, A[24], A[25], A[26], A[27], db + 128, 1);
        wgmma_rs_32_0(d + 80, A[0], A[1], A[2], A[3], db + 160, 0);
        wgmma_rs_32_0(d + 64, A[8], A[9], A[10], A[11], db + 160, 1);
        wgmma_rs_32_0(d + 0, A[28], A[29], A[30], A[31], db + 112, 1);
        wgmma_rs_32_0(d + 16, A[28], A[29], A[30], A[31], db + 144, 1);
        wgmma_rs_32_0(d + 48, A[16], A[17], A[18], A[19], db + 160, 1);
        wgmma_rs_32_0(d + 32, A[24], A[25], A[26], A[27], db + 160, 1);
        wgmma_rs_32_0(d + 0, A[32], A[33], A[34], A[35], db + 128, 1);
        wgmma_rs_32_0(d + 16, A[32], A[33], A[34], A[35], db + 160, 1);
        wgmma_rs_32_0(d + 80, A[4], A[5], A[6], A[7], db + 176, 1);
        wgmma_rs_32_0(d + 64, A[12], A[13], A[14], A[15], db + 176, 1);
        wgmma_rs_32_0(d + 0, A[36], A[37], A[38], A[39], db + 144, 1);
        wgmma_rs_32_0(d + 48, A[20], A[21], A[22], A[23], db + 176, 1);
        wgmma_rs_32_0(d + 32, A[28], A[29], A[30], A[31], db + 176, 1);
        wgmma_rs_32_0(d + 16, A[36], A[37], A[38], A[39], db + 176, 1);
        wgmma_rs_32_0(d + 0, A[40], A[41], A[42], A[43], db + 160, 1);
        wgmma_rs_32_0(d + 96, A[0], A[1], A[2], A[3], db + 192, 0);
        wgmma_rs_32_0(d + 80, A[8], A[9], A[10], A[11], db + 192, 1);
        wgmma_rs_32_0(d + 64, A[16], A[17], A[18], A[19], db + 192, 1);
        wgmma_rs_32_0(d + 0, A[44], A[45], A[46], A[47], db + 176, 1);
        wgmma_rs_32_0(d + 48, A[24], A[25], A[26], A[27], db + 192, 1);
        wgmma_rs_32_0(d + 32, A[32], A[33], A[34], A[35], db + 192, 1);
        wgmma_rs_32_0(d + 16, A[40], A[41], A[42], A[43], db + 192, 1);
        wgmma_rs_32_0(d + 0, A[48], A[49], A[50], A[51], db + 192, 1);
        wgmma_rs_32_0(d + 96, A[4], A[5], A[6], A[7], db + 208, 1);
        wgmma_rs_32_0(d + 80, A[12], A[13], A[14], A[15], db + 208, 1);
        wgmma_rs_32_0(d + 64, A[20], A[21], A[22], A[23], db + 208, 1);
        wgmma_rs_32_0(d + 48, A[28], A[29], A[30], A[31], db + 208, 1);
        wgmma_rs_32_0(d + 32, A[36], A[37], A[38], A[39], db + 208, 1);
        wgmma_rs_32_0(d + 16, A[44], A[45], A[46], A[47], db + 208, 1);
        wgmma_rs_32_0(d + 0, A[52], A[53], A[54], A[55], db + 208, 1);
        wgmma_rs_32_0(d + 112, A[0], A[1], A[2], A[3], db + 224, 0);
        wgmma_rs_32_0(d + 96, A[8], A[9], A[10], A[11], db + 224, 1);
        wgmma_rs_32_0(d + 80, A[16], A[17], A[18], A[19], db + 224, 1);
        wgmma_rs_32_0(d + 64, A[24], A[25], A[26], A[27], db + 224, 1);
        wgmma_rs_32_0(d + 48, A[32], A[33], A[34], A[35], db + 224, 1);
        wgmma_rs_32_0(d + 32, A[40], A[41], A[42], A[43], db + 224, 1);
        wgmma_rs_32_0(d + 16, A[48], A[49], A[50], A[51], db + 224, 1);
        wgmma_rs_32_0(d + 0, A[56], A[57], A[58], A[59], db + 224, 1);
        wgmma_rs_32_0(d + 112, A[4], A[5], A[6], A[7], db + 240, 1);
        wgmma_rs_32_0(d + 96, A[12], A[13], A[14], A[15], db + 240, 1);
        wgmma_rs_32_0(d + 80, A[20], A[21], A[22], A[23], db + 240, 1);
        wgmma_rs_32_0(d + 64, A[28], A[29], A[30], A[31], db + 240, 1);
        wgmma_rs_32_0(d + 48, A[36], A[37], A[38], A[39], db + 240, 1);
        wgmma_rs_32_0(d + 32, A[44], A[45], A[46], A[47], db + 240, 1);
        wgmma_rs_32_0(d + 16, A[52], A[53], A[54], A[55], db + 240, 1);
        wgmma_rs_32_0(d + 0, A[60], A[61], A[62], A[63], db + 240, 1);
        wg_commit();
        const uint32_t yoff = ub + w * 2048 + (127 + 2 * w - lane) * 16;
        const uint32_t yoff0 = yoff + (lane < 2 * w ? -2048 : 8192), yoff4 = yoff + (lane < 2 * w ? 6144 : 0);
        wg_wait<0>();
        regfence<128>(d);
        if (rel >> 18 == si) bar_arrive(8, 256);
        if (lead) TSTAMP(42 + j);
        bar_sync(5 + isE, 128);
#pragma unroll
        for (int z = 0; z < 8; z++) {
          uint32_t e[4];
#pragma unroll
          for (int i = 0; i < 4; i++) {
            const int x = 4 * z + i;
            e[i] = x < 31 ? pack2(d[4 * x] + d[4 * x + 6], d[4 * x + 1] + d[4 * x + 7]) : pack2(d[4 * x], d[4 * x + 1]);
          }
          if (z == 0 && c < w) e[0] = 0;
          stsm4t(z == 0 ? yoff0 : z == 4 ? yoff4 : z < 4 ? yoff + 8192 - 512 * z : yoff - 512 * (z - 4), e[0], e[1], e[2], e[3]);
        }
        uint8_t* g = ps + (pgo(u >> 4, (u >> 1) & 7) ^ cgrp(G_Y + j)) + ((b & 97) | (b & 6) << 2 | (b & 24) >> 2) * 32 + ((u ^ (b >> 4)) & 1) * 16;
        bar_sync(5 + isE, 128);
#pragma unroll
        for (int i = 0; i < 2; i++) {
          const uint32_t pa = ub + u * 16 + i * 8192;
          const uint4 p0 = lds128(pa), p1 = lds128(pa + 2048), p2 = lds128(pa + 4096), p3 = lds128(pa + 6144);
          stg128(g + (i << 23), settag(hadd2(hadd2(p0.x, p1.x), hadd2(p2.x, p3.x)), 1, ep), hadd2(hadd2(p0.y, p1.y), hadd2(p2.y, p3.y)),
                 hadd2(hadd2(p0.z, p1.z), hadd2(p2.z, p3.z)), hadd2(hadd2(p0.w, p1.w), hadd2(p2.w, p3.w)));
        }
        bar_sync(5 + isE, 128);
        if (lead) { hint_add(g_sync + Y_Y + j * 32); TSTAMP(84 + j); }
      }
      if (w == 0 && lane < 6 && ((rel >> 3 * lane) & 7) == si) mbar_arrive(BAR(B_EMPTY + lane));
      __syncwarp();
    }
    const int rh = isE ^ kh;
    const uint32_t hreg = sb + (isE ? 0 : 4 * SLOT);
    uint32_t hA[48];
    {
      float ag[96], au[96];
      int slot = 2, prev = 0, ph = 0, s = 0;
      int v0, vo;
      mbar_wait(BAR(B_ROLE), 0);
      { ROLE; v0 = min(vr, 2) * 4; vo = (2 * vt + isE) * 256; }
      const uint64_t dbase = mkdesc(sb, 4096, 1024, 1);
      const uint32_t ck = sb + 24576 + rh * 4096 + w * 1024 + lane * 32 + (r & 1) * 16;
      if (isE) bar_sync(8, 256);
      auto stage = [&](float* vv) {
        const uint64_t dg = dbase + slot * (SLOT >> 4), da = mkdesc(0, 0, 512, 2) | (uint32_t)(dg + ((24576 + rh * 4096) >> 4));
        if (s == LH + LEAD * isE) { if (isE) bar_arrive(7, 256); else bar_sync(7, 256); }
        mbar_wait(BAR(B_FULL + slot), ph);
        if ((lds32(ck + slot * SLOT) ^ ep) & 1) {
          ROLE;
          refetch(ps + tile(rb, G_X, ((ord >> (s & 28)) & 7) * 4 + (s & 3)) + rh * 16384 + w * 1024 + lane * 32, (r & 1) * 16, (ck + slot * SLOT) & ~31u, ep);
        }
        __syncwarp();
        if (s == 0 && lead) TSTAMP(22 + isE);
        if (s && (s & 3) == 0 && tid == 128) TSTAMP(37 + (s >> 2));
        wg_fence();
        wgmma_ss_192_01(ag, da, dg, s);
        wgmma_ss_192_01(au, da, dg + 768, s);
        if (vv) wgmma_ss_8_10(vv, dg + vo, mkdesc(sb + O_CS, 32, 128, 0) + (s & 3) * 8, s & 3);
        wgmma_ss_192_01(ag, da + 2, dg + 128, 1);
        wgmma_ss_192_01(au, da + 2, dg + 896, 1);
        if (vv) wgmma_ss_8_10(vv, dg + vo + 128, mkdesc(sb + O_CS, 32, 128, 0) + (s & 3) * 8 + 4, 1);
        wg_commit();
        wg_wait<1>();
        if (s > 0 && lead) mbar_arrive(BAR(B_EMPTY + prev));
        prev = slot;
        if (++slot == 6) { slot = s == 3 ? 2 : 0; ph ^= 1; }
        ++s;
      };
#pragma unroll 1
      while (s < v0) stage(nullptr);
      {
        float vv[4];
        mbar_wait(BAR(B_CS), 0);
#pragma unroll 1
        while (s < v0 + 4) stage(vv);
        wg_wait<0>();
        regfence<4>(vv);
        ROLE;
        if (c == 0) {
          uint32_t* g = g_vv + (fs * 5 + vr) * 384 + (2 * vt + isE) * 64 + 16 * w + r;
          str(g, settag(pack2(vv[0], vv[1]), 1, ep));
          str(g + 8, settag(pack2(vv[2], vv[3]), 1, ep));
        }
        bar_sync(5 + isE, 128);
        if (lead) hint_add(g_sync + Y_VV + fs * 32);
      }
#pragma unroll 1
      while (s < 20) stage(nullptr);
      {
        mbar_wait(BAR(B_ST + rh), 0);
        const uint32_t a0 = lds32(sb + O_ST + rh * 512 + w * 128 + r * 8), a1 = lds32(sb + O_ST + rh * 512 + w * 128 + r * 8 + 64);
        mbar_wait(BAR(B_VV), 0);
        const uint64_t dp = mkdesc(sb + O_BP, 16, 128, 0);
        wg_fence();
        wgmma_rs_192_0(ag, a0, a1, 0, 0, dp, 1);
        wgmma_rs_192_0(au, a0, a1, 0, 0, dp + 192, 1);
        wg_commit();
        wg_wait<1>();
        if (lead) mbar_arrive(BAR(B_EMPTY + 5));
        mbar_wait(BAR(B_EMPTY + 4 - 4 * isE), 0);
        wg_wait<0>();
      }
      regfence<96>(ag); regfence<96>(au);
      if (lead) TSTAMP(24 + isE);
      const uint32_t stg = hreg + (16 * w + (lane & 15)) * 128;
#pragma unroll
      for (int kq = 0; kq < 12; kq++) {
#pragma unroll
        for (int i = 0; i < 4; i++) hA[4 * kq + i] = pack2(ag[8 * kq + 2 * i] * au[8 * kq + 2 * i], ag[8 * kq + 2 * i + 1] * au[8 * kq + 2 * i + 1]);
        hA[4 * kq + 2] = settag(hA[4 * kq + 2], c == 2 * (kq & 1), ep);
        hA[4 * kq + 3] = settag(hA[4 * kq + 3], c == 2 * (kq & 1) + 1, ep);
        stsm4(stg + (kq >> 2) * 8192 + (((2 * (kq & 3) + (lane >> 4)) ^ (lane & 7)) * 16), hA[4 * kq], hA[4 * kq + 1], hA[4 * kq + 2], hA[4 * kq + 3]);
        if ((kq & 3) == 3) {
          fence_async_smem();
          __syncwarp();
          if (lane == 0) mbar_arrive(BAR(B_STAGED + isE * 3 + (kq >> 2)));
        }
      }
      if (lead) TSTAMP(50 + isE);
    }
    ROLE;
    float o[80];
    {
#pragma unroll
      for (int s = 0; s < 3; s++) {
        mbar_wait(BAR(B_W2F + s), 0);
        const uint64_t dw = mkdesc(sb + w2entry(s), 8192, 1024, 1);
        wg_fence();
#pragma unroll
        for (int kk = 0; kk < 4; kk++) wgmma_rs_160_1(o, hA[16 * s + 4 * kk], hA[16 * s + 4 * kk + 1], hA[16 * s + 4 * kk + 2], hA[16 * s + 4 * kk + 3], dw + kk * 128, (s | kk) ? 1 : 0);
        wg_commit();
        if (s > 0) { wg_wait<1>(); if (lead) mbar_arrive(BAR(B_W2E + s - 1)); }
      }
      const uint32_t co = (16 * w + (lane & 15)) * 128 + (((2 * (lane >> 4) + 1) ^ (lane & 7)) << 4) + ((lane >> 3) & 1) * 4 + (lane >> 4) * 8;
      int e = 3, pe = 0;
#pragma unroll 1
      for (int i = 0; i < 9; i++) {
        const int he = (i + 3) & 3;
        const uint32_t ck = hreg + he * 8192 + co;
        mbar_wait(BAR(B_W2F + e), pe);
        mbar_wait(BAR(B_HF + isE * 4 + he), (i >> 2) & 1);
        const uint32_t c0 = lds32(ck), c1 = lds32(ck ^ 64);
        if (((c0 ^ ep) | (c1 ^ ep)) & 1) {
          const uint32_t g = tile(rb, G_H, rh * 24 + kh * 12 + ((cg + 1 + i % 3) & 3) * 3 + i / 3) + (co & 4064) + (co >> 12) * 16384;
          refetch(ps + g, co & 31, ck & ~31u, ep);
          refetch(ps + (g ^ 64), co & 31, (ck & ~31u) ^ 64, ep);
        }
        __syncwarp();
        if (i == 0 && lead) TSTAMP(26 + isE);
        const uint64_t dw = mkdesc(sb + w2entry(e), e == 3 ? SLOT : 8192, 1024, 1);
        const uint64_t dh = mkdesc(hreg + he * 8192, 16, 1024, 1);
        wg_fence();
#pragma unroll
        for (int kk = 0; kk < 4; kk++) wgmma_ss_160_01(o, dh + kk * 2, dw + kk * 128, 1);
        wg_commit();
        wg_wait<1>();
        if (lead) {
          mbar_arrive(BAR(B_W2E + (e == 0 ? 4 : e - 1)));
          if (i > 0) mbar_arrive(BAR(B_HE + isE * 4 + ((he - 1) & 3)));
        }
        if (++e == 5) { e = 0; pe ^= 1; }
      }
      wg_wait<0>();
      regfence<80>(o);
      if (lead) TSTAMP(28 + isE);
    }
    const float ia = __uint_as_float(lds32(sb + O_ST + rh * 512 + w * 128 + r * 8 + 4)), ib = __uint_as_float(lds32(sb + O_ST + rh * 512 + w * 128 + r * 8 + 68));
    asm volatile("barrier.cluster.wait.aligned;" ::: "memory");
    const uint32_t red = sb + w2entry(2) + (tid & 127) * 16;
    auto fin = [&](int u, uint32_t& x0, uint32_t& x1, uint32_t& x2, uint32_t& x3, float2 f0, float2 f1) {
      const float2 g0 = lds64f(sb + O_GB + (16 * u + 2 * c) * 4), g1 = lds64f(sb + O_GB + (16 * u + 8 + 2 * c) * 4);
      x0 = pack2(fmaf(g0.x, o[8 * u] * ia, blo(x0) * f0.x), fmaf(g0.y, o[8 * u + 1] * ia, bhi(x0) * f0.y));
      x1 = pack2(fmaf(g0.x, o[8 * u + 2] * ib, blo(x1) * f0.x), fmaf(g0.y, o[8 * u + 3] * ib, bhi(x1) * f0.y));
      x2 = pack2(fmaf(g1.x, o[8 * u + 4] * ia, blo(x2) * f1.x), fmaf(g1.y, o[8 * u + 5] * ia, bhi(x2) * f1.y));
      x3 = pack2(fmaf(g1.x, o[8 * u + 6] * ib, blo(x3) * f1.x), fmaf(g1.y, o[8 * u + 7] * ib, bhi(x3) * f1.y));
    };
    if (isE) {
      mbar_wait(BAR(B_X1), 0);
      mbar_wait_cluster(BAR(B_RDY), 0);
      uint32_t rred, rbar;
      asm volatile("mapa.shared::cluster.u32 %0, %1, %2;" : "=r"(rred) : "r"(red), "r"(kh ^ 1));
      asm volatile("mapa.shared::cluster.u32 %0, %1, %2;" : "=r"(rbar) : "r"(BAR(B_RED)), "r"(kh ^ 1));
      const uint32_t xa = sb + O_REG + (16 * w + (lane & 15)) * 64 + (((lane >> 4) ^ ((lane >> 1) & 3)) << 4);
#pragma unroll
      for (int u = 0; u < 10; u++) {
        uint32_t x0, x1, x2, x3;
        ldsm4((xa ^ (u & 1) * 32) + (u >> 1) * 4096, x0, x1, x2, x3);
        fin(u, x0, x1, x2, x3, lds64f(sb + O_IC + (16 * u + 2 * c) * 4), lds64f(sb + O_IC + (16 * u + 8 + 2 * c) * 4));
        asm volatile("st.async.weak.shared::cluster.mbarrier::complete_tx::bytes.v4.b32 [%0], {%1,%2,%3,%4}, [%5];" ::"r"(rred + u * 2048), "r"(x0), "r"(x1), "r"(x2), "r"(x3), "r"(rbar) : "memory");
      }
    } else {
      mbar_wait_cluster(BAR(B_RED), 0);
      if (lead) TSTAMP(30);
      const uint32_t stg = hreg + (16 * w + (lane & 15)) * 128;
      const int row = rb * 128 + kh * 64 + 16 * w, c0 = cg * 160 + (cg & 1) * 32;
#pragma unroll
      for (int u = 0; u < 10; u++) {
        uint4 x = lds128(red + u * 2048);
        fin(u, x.x, x.y, x.z, x.w, make_float2(1.f, 1.f), make_float2(1.f, 1.f));
        stsm4(stg + (u >> 2) * 8192 + (((2 * (u & 3) + (lane >> 4)) ^ (lane & 7)) * 16), x.x, x.y, x.z, x.w);
        if ((u & 3) == 3 || u == 9) {
          fence_async_smem();
          __syncwarp();
          if (elect()) {
            if (u < 9) tma2d_store(&p.m_outa, hreg + (u >> 2) * 8192 + w * 2048, c0 + (u >> 2) * 64, row);
            else tma3d_store(&p.m_outb, hreg + 16384 + w * 2048, 0, row, cg * 5 + (~cg & 1) * 4);
          }
        }
      }
      if (elect()) { bulk_commit(); bulk_wait0_read(); }
      if (lead) { str(g_sync + Y_EP + b * 32, ep); TSTAMP(31); }
    }
  }
}

#define L2PROMO CU_TENSOR_MAP_L2_PROMOTION_L2_128B
typedef CUresult (*EncodeFn)(CUtensorMap*, CUtensorMapDataType, cuuint32_t, void*, const cuuint64_t*, const cuuint64_t*, const cuuint32_t*,
                             const cuuint32_t*, CUtensorMapInterleave, CUtensorMapSwizzle, CUtensorMapL2promotion, CUtensorMapFloatOOBfill);

void make_map(EncodeFn enc, CUtensorMap* m, const void* ptr, uint64_t inner, uint64_t outer, uint32_t bi, uint32_t bo, CUtensorMapSwizzle sw) {
  cuuint64_t d[2] = {inner, outer};
  cuuint64_t s[1] = {inner * 2};
  cuuint32_t bx[2] = {bi, bo};
  cuuint32_t e[2] = {1, 1};
  enc(m, CU_TENSOR_MAP_DATA_TYPE_BFLOAT16, 2, const_cast<void*>(ptr), d, s, bx, e, CU_TENSOR_MAP_INTERLEAVE_NONE, sw, L2PROMO,
      CU_TENSOR_MAP_FLOAT_OOB_FILL_NONE);
}

void make_map3(EncodeFn enc, CUtensorMap* m, const void* ptr, uint64_t d0, uint64_t d1, uint64_t d2, uint64_t s1, uint64_t s2, uint32_t b0, uint32_t b1, uint32_t b2,
               CUtensorMapSwizzle sw) {
  cuuint64_t d[3] = {d0, d1, d2};
  cuuint64_t s[2] = {s1, s2};
  cuuint32_t bx[3] = {b0, b1, b2};
  cuuint32_t e[3] = {1, 1, 1};
  enc(m, CU_TENSOR_MAP_DATA_TYPE_BFLOAT16, 3, const_cast<void*>(ptr), d, s, bx, e, CU_TENSOR_MAP_INTERLEAVE_NONE, sw, L2PROMO,
      CU_TENSOR_MAP_FLOAT_OOB_FILL_NONE);
}

}

extern "C" void kernel_launch(void* const* d_in, const int* in_sizes, int n_in, void* d_out, int out_size) {
  (void)in_sizes; (void)n_in; (void)out_size;
  void* f = nullptr;
  cudaDriverEntryPointQueryResult qr;
  cudaGetDriverEntryPoint("cuTensorMapEncodeTiled", &f, cudaEnableDefault, &qr);
  EncodeFn enc = (EncodeFn)f;
  void* s;
  cudaGetSymbolAddress(&s, g_s);
  Params p = {};
  uint8_t* ps = (uint8_t*)(((uintptr_t)s + (2 << 20) - 1) & ~(uintptr_t)((2 << 20) - 1));
  make_map3(enc, &p.m_k, d_in[1], D_, S_ / 8, 8, 8 * D_ * 2, D_ * 2, 32, 8, 8, CU_TENSOR_MAP_SWIZZLE_64B);
  make_map3(enc, &p.m_kh, d_in[1], D_, S_ / 8, 8, 8 * D_ * 2, D_ * 2, 32, 8, 3, CU_TENSOR_MAP_SWIZZLE_64B);
  make_map3(enc, &p.m_v, d_in[2], D_, S_ / 8, 8, 8 * D_ * 2, D_ * 2, 32, 8, 8, CU_TENSOR_MAP_SWIZZLE_64B);
  make_map3(enc, &p.m_q, d_in[0], 32, S_, D_ / 32, D_ * 2, 64, 32, 16, D_ / 32, CU_TENSOR_MAP_SWIZZLE_64B);
  make_map(enc, &p.m_wm, d_in[11], 6 * D_, D_, 64, 160, CU_TENSOR_MAP_SWIZZLE_128B);
  make_map3(enc, &p.m_wg, d_in[7], 64, D_, F_ / 64, F_ * 2, 128, 64, 32, 3, CU_TENSOR_MAP_SWIZZLE_128B);
  make_map3(enc, &p.m_wu, d_in[8], 64, D_, F_ / 64, F_ * 2, 128, 64, 32, 3, CU_TENSOR_MAP_SWIZZLE_128B);
  make_map3(enc, &p.m_s, ps, 256, 32, 1024, 512, 16384, 256, 8, 2, CU_TENSOR_MAP_SWIZZLE_NONE);
  make_map(enc, &p.m_w2a, d_in[9], D_, F_, 64, 64, CU_TENSOR_MAP_SWIZZLE_128B);
  make_map3(enc, &p.m_w2b, d_in[9], 32, F_, D_ / 32, D_ * 2, 64, 64, 64, 1, CU_TENSOR_MAP_SWIZZLE_128B);
  make_map(enc, &p.m_outa, d_out, D_, S_, 64, 16, CU_TENSOR_MAP_SWIZZLE_128B);
  make_map3(enc, &p.m_outb, d_out, 32, S_, D_ / 32, D_ * 2, 64, 64, 16, 1, CU_TENSOR_MAP_SWIZZLE_128B);
  p.c = (const __nv_bfloat16*)d_in[10];
  p.wg = (const __nv_bfloat16*)d_in[7];
  p.wu = (const __nv_bfloat16*)d_in[8];
  p.w2 = (const __nv_bfloat16*)d_in[9];
  cudaFuncSetAttribute(fused_kernel, cudaFuncAttributeMaxDynamicSharedMemorySize, SMEM_BYTES);
  fused_kernel<<<128, 384, SMEM_BYTES, cudaStreamPerThread>>>((const __nv_bfloat16*)d_in[1], (const __nv_bfloat16*)d_in[2], (const __nv_bfloat16*)d_in[3],
                                                              (const __nv_bfloat16*)d_in[4], (const __nv_bfloat16*)d_in[5], ps, p);
}
```

```cpp
#include <cuda_runtime.h>
#include <cuda.h>
#include <cuda_bf16.h>
#include <cstdint>

namespace {

constexpr int S_ = 2048, D_ = 640, F_ = 1536;

__device__ __align__(1024) uint8_t g_s[18 << 20];
#define g_sync ((uint32_t*)(ps + (28 << 16)))
#define g_mod ((uint32_t*)(ps + (29 << 16)))
#define g_vv ((uint32_t*)(ps + (30 << 16)))
enum { Y_KV = 0, Y_Y = 20 * 32, Y_MOD = 25 * 32, Y_VV = 31 * 32, Y_CLS = 40 * 32 + 8, Y_EP = 7 };
enum { G_KV = 0, G_Y = 5, G_X = 10, G_M = 15, G_H = 16 };
enum { M_X = 0, M_O = 40, M_H = 256, M_ST = 512 };
#define TSTAMP(i) do { } while (0)
#define T_K1 1900
#define T_S0 900
#define T_Q 6950
#define T_K2 2700
#define T_S1 1300
#define T_K3 3900
#define T_WM0 5500
#define T_S2 3500
#define T_K4 4700
#define T_S3 6600
#define D_Q 54
#define D_WM 27
#define NE 2
#define T_S4 8700
#define T_W0 9050
#define T_WM2 9600
#define STEP(ln, kv, gv, cv) (ln | (kv + 1) << 1 | (gv + 1) << 4 | (cv + 1) << 6)
#define SCH 5
#define SCHED_E STEP(0, 0, -1, -1), STEP(0, 1, -1, -1), STEP(0, 2, -1, 1), STEP(0, 4, -1, -1), STEP(1, -1, -1, 3), STEP(0, -1, 1, -1)
#define SCHED_L STEP(0, -1, -1, 0), STEP(0, 3, 0, 2), STEP(0, -1, -1, 4)
#define LH 10
#define LEAD 2

struct Params {
  CUtensorMap m_k, m_kh, m_v, m_q, m_wm, m_wg, m_wu, m_s, m_w2a, m_w2b, m_outa, m_outb;
  const __nv_bfloat16 *c, *wg, *wu, *w2;
  uint8_t* out;
};
constexpr int NLD = 10;
__host__ __device__ constexpr uint32_t nth_load(int n) {
  const uint32_t when[NLD] = {T_K1 << 8 | 1, T_K2 << 8 | 2, T_K3 << 8 | 3, T_K4 << 8 | 4, T_S0 << 8 | 16, T_S1 << 8 | 17, T_S2 << 8 | 18, T_S3 << 8 | 19, T_S4 << 8 | 20,
                              T_Q << 8 | 21};
  for (int i = 0; i < NLD; i++) {
    int rank = 0;
    for (int k = 0; k < NLD; k++) rank += when[k] < when[i];
    if (rank == n) return when[i];
  }
  return 0;
}
__host__ __device__ constexpr uint64_t sched(int g) {
  const uint32_t t[2][8] = {{SCHED_L}, {SCHED_E}};
  uint64_t r = 0;
  for (int i = 0; i < 7; i++) r |= (uint64_t)t[g][i] << 9 * i;
  return r;
}
__host__ __device__ constexpr uint32_t release(int g) {
  uint32_t last[7] = {};
  for (int i = 0; i < 7; i++) {
    const uint32_t t = (sched(g) >> 9 * i) & 511, kv = (t >> 1) & 7, cv = (t >> 6) & 7;
    if (kv) last[kv == 5 ? 2 : kv + 1] = last[kv == 5 ? 3 : kv + 1] = i;
    if (t & 48) last[0] = last[1] = i;
    if (cv) last[cv == 5 ? 1 : cv + 1] = last[6] = i;
  }
  uint32_t r = g ? 7 << 18 : 0;
  for (int i = 0; i < 7; i++) r |= last[i] << 3 * i;
  return r;
}
template <int I> struct IC { static constexpr int v = I; };
template <int N, class F> __device__ __forceinline__ void unrolled(F f) {
  if constexpr (N > 0) { unrolled<N - 1>(f); f(IC<N - 1>()); }
}

constexpr uint32_t SLOT = 32768;
constexpr uint32_t U_RAW = 16, U_ODD = U_RAW + 4160, U_KV = 8448;
constexpr uint32_t O_SILU = SLOT + 8192;
constexpr uint32_t O_REG = 6 * SLOT;
constexpr uint32_t O_Y = O_REG + 20480;
constexpr uint32_t O_BP = O_Y + 4096;
constexpr uint32_t O_MA = O_BP + 6272;
constexpr uint32_t O_CS = O_MA + 768;
constexpr uint32_t O_GB = O_CS + 640;
constexpr uint32_t O_LN = O_GB + 1280;
constexpr uint32_t O_ROLE = O_LN + 64;
constexpr uint32_t O_SX = O_ROLE + 64;
constexpr uint32_t O_ST = O_SX + 128;
constexpr uint32_t O_BAR = O_ST + 1024;
constexpr uint32_t SMEM_BYTES = O_BAR + 1024;
static_assert(SMEM_BYTES <= 232448, "smem");
enum { B_EMPTY = 0, B_W2E = 6, B_PL = 12, B_LN = 20, B_VV = 21, B_YE = 22, B_FULL = 24, B_W2F = 30, B_HF = 39,
       B_KIN = 45, B_KV = 50, B_QIN = 55, B_WM = 56, B_CS = 57, B_X1 = 58, B_ST = 59, B_ROLE = 61, B_SSM = 62, B_PR = 67, B_YF = 69 };
__device__ __forceinline__ uint32_t kreg(int n) { return n < 4 ? (n + 2) * SLOT + 16384 : 2 * SLOT + 26624; }
__device__ __forceinline__ uint32_t voff(int n) { return n < 4 ? 6144 : SLOT; }
__device__ __forceinline__ uint32_t w2entry(int e) { return (e & 3) == 3 ? (e >> 2) * 3 * SLOT + 24576 : (e - (e >> 2)) * SLOT; }
__device__ __forceinline__ uint32_t bnd(int j) { return j < 4 ? (j + 2) * SLOT : SLOT + 16384; }
__device__ __forceinline__ uint32_t pgo(int rb, int p) { return (rb >> 1) << 21 | p << 13 | ((rb ^ p) & 1) << 12; }
__device__ __forceinline__ uint32_t cgrp(int g) { return g << 16 | ((0x99669966u >> g) & 1) << 12; }
__device__ __forceinline__ uint32_t tile(int rb, int g0, int x) { return pgo(rb, (x & 1) | (x & 2) << 1) ^ cgrp(g0 + (x >> 2)); }

__device__ __forceinline__ uint32_t smem_u32(const void* p) { return (uint32_t)__cvta_generic_to_shared(p); }
__device__ __forceinline__ void mbar_init(uint32_t bar, uint32_t cnt) { asm volatile("mbarrier.init.shared::cta.b64 [%0], %1;" ::"r"(bar), "r"(cnt) : "memory"); }
__device__ __forceinline__ void mbar_expect(uint32_t bar, uint32_t bytes) { asm volatile("mbarrier.arrive.expect_tx.shared::cta.b64 _, [%0], %1;" ::"r"(bar), "r"(bytes) : "memory"); }
__device__ __forceinline__ void mbar_arrive(uint32_t bar) { asm volatile("mbarrier.arrive.shared::cta.b64 _, [%0];" ::"r"(bar) : "memory"); }
__device__ __forceinline__ void mbar_wait(uint32_t bar, uint32_t parity) {
  asm volatile("{\n .reg .pred p;\n .reg .u32 c;\n mov.u32 c, 0;\n LOOP:\n mbarrier.try_wait.parity.shared::cta.b64 p, [%0], %1;\n @p bra DONE;\n add.u32 c, c, 1;\n setp.lt.u32 p, c, 200000;\n @p bra LOOP;\n DONE:\n }" ::"r"(bar), "r"(parity) : "memory");
}
__device__ __forceinline__ void mbar_wait_cluster(uint32_t bar, uint32_t parity) {
  asm volatile("{\n .reg .pred p;\n .reg .u32 c;\n mov.u32 c, 0;\n LOOP:\n mbarrier.try_wait.parity.acquire.cluster.shared::cta.b64 p, [%0], %1;\n @p bra DONE;\n add.u32 c, c, 1;\n setp.lt.u32 p, c, 200000;\n @p bra LOOP;\n DONE:\n }" ::"r"(bar), "r"(parity) : "memory");
}
__device__ __forceinline__ bool elect() { uint32_t p; asm volatile("{ .reg .pred q; elect.sync _|q, 0xffffffff; selp.u32 %0, 1, 0, q; }" : "=r"(p)); return p; }
__device__ __forceinline__ uint32_t clk() { uint32_t c; asm volatile("mov.u32 %0, %%clock;" : "=r"(c)); return c; }
__device__ __forceinline__ uint32_t ldr(const uint32_t* p) { uint32_t v; asm volatile("ld.relaxed.gpu.global.u32 %0, [%1];" : "=r"(v) : "l"(p) : "memory"); return v; }
__device__ __forceinline__ uint4 ldr4(const uint32_t* p) {
  uint4 v; asm volatile("ld.relaxed.gpu.global.v4.u32 {%0,%1,%2,%3}, [%4];" : "=r"(v.x), "=r"(v.y), "=r"(v.z), "=r"(v.w) : "l"(p) : "memory"); return v;
}
__device__ __forceinline__ void poll_ge(const uint32_t* p, uint32_t target) {
  asm volatile("{\n .reg .pred p;\n .reg .u32 c, v;\n mov.u32 c, 0;\n LOOP:\n ld.relaxed.gpu.global.u32 v, [%0];\n sub.u32 v, v, %1;\n setp.ge.s32 p, v, 0;\n @p bra DONE;\n add.u32 c, c, 1;\n setp.lt.u32 p, c, 100000;\n @p bra LOOP;\n DONE:\n }" ::"l"(p), "r"(target) : "memory");
}
__device__ __forceinline__ void poll_lane(uint32_t& v, const void* p, uint32_t target, int l) {
  for (int it = 0; !((__ballot_sync(0xffffffffu, (int)(v - target) >= 0) >> l) & 1) && it < 100000; it++) v = ldr((const uint32_t*)p);
}
__device__ __forceinline__ void hint_add(uint32_t* p) { asm volatile("red.relaxed.gpu.global.add.u32 [%0], 1;" ::"l"(p) : "memory"); }
__device__ __forceinline__ void refetch(const void* g, uint32_t off, uint32_t a, uint32_t tag) {
  asm volatile("{\n .reg .pred p;\n .reg .u32 c, v, x, y, z;\n .reg .u64 q;\n mov.u32 c, 0;\n cvt.u64.u32 q, %1;\n add.u64 q, q, %0;\n"
               " LOOP:\n ld.relaxed.gpu.global.u32 v, [q];\n xor.b32 v, v, %3;\n and.b32 v, v, 1;\n setp.eq.u32 p, v, 0;\n @p bra DONE;\n add.u32 c, c, 1;\n setp.lt.u32 p, c, 100000;\n @p bra LOOP;\n"
               " DONE:\n ld.relaxed.gpu.global.v4.u32 {v, x, y, z}, [%0];\n st.shared.v4.u32 [%2], {v, x, y, z};\n ld.relaxed.gpu.global.v4.u32 {v, x, y, z}, [%0+16];\n xor.b32 c, %2, 16;\n"
               " st.shared.v4.u32 [c], {v, x, y, z};\n fence.proxy.async.shared::cta;\n }" ::"l"(g), "r"(off), "r"(a), "r"(tag) : "memory");
}
__device__ __forceinline__ void refetch16(const void* g, uint32_t a, uint32_t tag) {
  asm volatile("{\n .reg .pred p;\n .reg .u32 c, t, v, x, y, z;\n mov.u32 c, 0;\n"
               " LOOP:\n ld.relaxed.gpu.global.v4.u32 {v, x, y, z}, [%0];\n xor.b32 t, v, %2;\n and.b32 t, t, 1;\n setp.eq.u32 p, t, 0;\n @p bra DONE;\n add.u32 c, c, 1;\n setp.lt.u32 p, c, 100000;\n @p bra LOOP;\n"
               " DONE:\n st.shared.v4.u32 [%1], {v, x, y, z};\n }" ::"l"(g), "r"(a), "r"(tag) : "memory");
}
__device__ __forceinline__ uint2 ldr2(const uint32_t* p) {
  uint2 v; asm volatile("ld.relaxed.gpu.global.v2.u32 {%0,%1}, [%2];" : "=r"(v.x), "=r"(v.y) : "l"(p) : "memory"); return v;
}
__device__ __forceinline__ uint32_t settag(uint32_t x, uint32_t m, uint32_t t) { return (x & ~m) | (t & m); }
__device__ __forceinline__ void stg128(void* p, uint32_t x, uint32_t y, uint32_t z, uint32_t w) {
  asm volatile("st.global.v4.u32 [%0], {%1,%2,%3,%4};" ::"l"(p), "r"(x), "r"(y), "r"(z), "r"(w) : "memory");
}
__device__ __forceinline__ void cpa16(uint32_t dst, const void* src, uint32_t n) { asm volatile("cp.async.cg.shared.global [%0], [%1], 16, %2;" ::"r"(dst), "l"(src), "r"(n) : "memory"); }
__device__ __forceinline__ void tma3d(uint32_t dst, const CUtensorMap* m, int x, int y, int z, uint32_t bar) {
  asm volatile("cp.async.bulk.tensor.3d.shared::cluster.global.mbarrier::complete_tx::bytes [%0], [%1, {%3, %4, %5}], [%2];" ::"r"(dst), "l"(m), "r"(bar), "r"(x), "r"(y), "r"(z) : "memory");
}
__device__ __forceinline__ void bulk_st(void* dst, uint32_t src, uint32_t bytes) {
  asm volatile("cp.async.bulk.global.shared::cta.bulk_group [%0], [%1], %2;" ::"l"(dst), "r"(src), "r"(bytes) : "memory");
}
__device__ __forceinline__ void bulk_pf(const void* src, uint32_t bytes) { asm volatile("cp.async.bulk.prefetch.L2.global [%0], %1;" ::"l"(src), "r"(bytes) : "memory"); }
__device__ __forceinline__ void tma2d(uint32_t dst, const CUtensorMap* m, int x, int y, uint32_t bar) {
  asm volatile("cp.async.bulk.tensor.2d.shared::cluster.global.mbarrier::complete_tx::bytes [%0], [%1, {%3, %4}], [%2];" ::"r"(dst), "l"(m), "r"(bar), "r"(x), "r"(y) : "memory");
}
__device__ __forceinline__ void tma2d_add(const CUtensorMap* m, uint32_t src, int x, int y) {
  asm volatile("cp.reduce.async.bulk.tensor.2d.global.shared::cta.add.tile.bulk_group [%0, {%2, %3}], [%1];" ::"l"(m), "r"(src), "r"(x), "r"(y) : "memory");
}
__device__ __forceinline__ void bulk_ld(uint32_t dst, const void* src, uint32_t bytes, uint32_t bar) {
  asm volatile("cp.async.bulk.shared::cluster.global.mbarrier::complete_tx::bytes [%0], [%1], %2, [%3];" ::"r"(dst), "l"(src), "r"(bytes), "r"(bar) : "memory");
}
__device__ __forceinline__ void bulk_commit() { asm volatile("cp.async.bulk.commit_group;" ::: "memory"); }
template <int N> __device__ __forceinline__ void bulk_wait() { asm volatile("cp.async.bulk.wait_group %0;" ::"n"(N) : "memory"); }
__device__ __forceinline__ void bulk_wait0_read() { asm volatile("cp.async.bulk.wait_group.read 0;" ::: "memory"); }
__device__ __forceinline__ void fence_async_smem() { asm volatile("fence.proxy.async.shared::cta;" ::: "memory"); }
__device__ __forceinline__ void bar_sync(int id, int n) { asm volatile("bar.sync %0, %1;" ::"r"(id), "r"(n) : "memory"); }
__device__ __forceinline__ void bar_arrive(int id, int n) { asm volatile("bar.arrive %0, %1;" ::"r"(id), "r"(n) : "memory"); }
__device__ __forceinline__ void wg_fence() { asm volatile("wgmma.fence.sync.aligned;" ::: "memory"); }
__device__ __forceinline__ void wg_commit() { asm volatile("wgmma.commit_group.sync.aligned;" ::: "memory"); }
template <int N> __device__ __forceinline__ void wg_wait() { asm volatile("wgmma.wait_group.sync.aligned %0;" ::"n"(N) : "memory"); }
__device__ __forceinline__ void ldsm4(uint32_t a, uint32_t& r0, uint32_t& r1, uint32_t& r2, uint32_t& r3) {
  asm volatile("ldmatrix.sync.aligned.m8n8.x4.shared.b16 {%0,%1,%2,%3}, [%4];" : "=r"(r0), "=r"(r1), "=r"(r2), "=r"(r3) : "r"(a) : "memory");
}
__device__ __forceinline__ void ldsm4t(uint32_t a, uint32_t& r0, uint32_t& r1, uint32_t& r2, uint32_t& r3) {
  asm volatile("ldmatrix.sync.aligned.m8n8.x4.trans.shared.b16 {%0,%1,%2,%3}, [%4];" : "=r"(r0), "=r"(r1), "=r"(r2), "=r"(r3) : "r"(a) : "memory");
}
__device__ __forceinline__ void stsm4t(uint32_t a, uint32_t r0, uint32_t r1, uint32_t r2, uint32_t r3) {
  asm volatile("stmatrix.sync.aligned.m8n8.x4.trans.shared.b16 [%0], {%1,%2,%3,%4};" ::"r"(a), "r"(r0), "r"(r1), "r"(r2), "r"(r3) : "memory");
}
__device__ __forceinline__ void stsm4(uint32_t a, uint32_t r0, uint32_t r1, uint32_t r2, uint32_t r3) {
  asm volatile("stmatrix.sync.aligned.m8n8.x4.shared.b16 [%0], {%1,%2,%3,%4};" ::"r"(a), "r"(r0), "r"(r1), "r"(r2), "r"(r3) : "memory");
}
__device__ __forceinline__ uint32_t lds32(uint32_t a) { uint32_t v; asm volatile("ld.shared.u32 %0, [%1];" : "=r"(v) : "r"(a) : "memory"); return v; }
__device__ __forceinline__ uint4 lds128(uint32_t a) { uint4 v; asm volatile("ld.shared.v4.u32 {%0,%1,%2,%3}, [%4];" : "=r"(v.x), "=r"(v.y), "=r"(v.z), "=r"(v.w) : "r"(a) : "memory"); return v; }
__device__ __forceinline__ float4 lds128f(uint32_t a) { float4 v; asm volatile("ld.shared.v4.f32 {%0,%1,%2,%3}, [%4];" : "=f"(v.x), "=f"(v.y), "=f"(v.z), "=f"(v.w) : "r"(a) : "memory"); return v; }
__device__ __forceinline__ float2 lds64f(uint32_t a) { float2 v; asm volatile("ld.shared.v2.f32 {%0,%1}, [%2];" : "=f"(v.x), "=f"(v.y) : "r"(a) : "memory"); return v; }
__device__ __forceinline__ void sts32(uint32_t a, uint32_t v) { asm volatile("st.shared.u32 [%0], %1;" ::"r"(a), "r"(v) : "memory"); }
__device__ __forceinline__ void sts64(uint32_t a, uint32_t x, uint32_t y) { asm volatile("st.shared.v2.u32 [%0], {%1,%2};" ::"r"(a), "r"(x), "r"(y) : "memory"); }
__device__ __forceinline__ void sts128(uint32_t a, uint32_t x, uint32_t y, uint32_t z, uint32_t w) { asm volatile("st.shared.v4.u32 [%0], {%1,%2,%3,%4};" ::"r"(a), "r"(x), "r"(y), "r"(z), "r"(w) : "memory"); }
__device__ __forceinline__ void sts16(uint32_t a, uint16_t v) { asm volatile("st.shared.u16 [%0], %1;" ::"r"(a), "h"(v) : "memory"); }
__device__ __forceinline__ uint32_t prmt(uint32_t a, uint32_t b, uint32_t s) { uint32_t r; asm("prmt.b32 %0, %1, %2, %3;" : "=r"(r) : "r"(a), "r"(b), "r"(s)); return r; }
__device__ __forceinline__ uint32_t hfma2(uint32_t a, uint32_t b, uint32_t c) { uint32_t r; asm("fma.rn.bf16x2 %0, %1, %2, %3;" : "=r"(r) : "r"(a), "r"(b), "r"(c)); return r; }
__device__ __forceinline__ uint32_t hfma2lh(uint32_t a, uint32_t l) {
  uint32_t r;
  asm("{ .reg .b16 x, y; .reg .b32 u, v; mov.b32 {x, y}, %2; mov.b32 u, {x, x}; mov.b32 v, {y, y}; fma.rn.bf16x2 %0, %1, u, v; }" : "=r"(r) : "r"(a), "r"(l));
  return r;
}
__device__ __forceinline__ uint32_t addu(uint32_t a, uint32_t u) { uint32_t r; asm("add.u32 %0, %1, %2;" : "=r"(r) : "r"(a), "r"(u)); return r; }
__device__ __forceinline__ uint32_t tag0(uint32_t x, uint32_t t) { uint32_t r; asm("lop3.b32 %0, %1, 1, %2, 0xb8;" : "=r"(r) : "r"(x), "r"(t)); return r; }
__device__ __forceinline__ void keep(uint32_t& x) { x = __shfl_xor_sync(0xffffffffu, x, 0); }
__device__ __forceinline__ uint32_t hmul2(uint32_t a, uint32_t b) { uint32_t r; asm("mul.rn.bf16x2 %0, %1, %2;" : "=r"(r) : "r"(a), "r"(b)); return r; }
__device__ __forceinline__ uint32_t pack2(float lo, float hi) { uint32_t r; asm("cvt.rn.bf16x2.f32 %0, %1, %2;" : "=r"(r) : "f"(hi), "f"(lo)); return r; }
__device__ __forceinline__ float blo(uint32_t v) { return __uint_as_float(v << 16); }
__device__ __forceinline__ float bhi(uint32_t v) { return __uint_as_float(v & 0xffff0000u); }
__device__ __forceinline__ uint32_t hadd2(uint32_t a, uint32_t b) { uint32_t r; asm("add.rn.bf16x2 %0, %1, %2;" : "=r"(r) : "r"(a), "r"(b)); return r; }
__device__ __forceinline__ void str(uint32_t* p, uint32_t v) { asm volatile("st.relaxed.gpu.global.u32 [%0], %1;" ::"l"(p), "r"(v) : "memory"); }
__device__ __forceinline__ uint32_t tagf(float x, uint32_t tag) { return (__float_as_uint(x) & ~3u) | (tag & 3); }
template <int N> __device__ __forceinline__ float4 gather4(const uint32_t* p, int stride, uint32_t tag) {
  uint4 v[N];
  int it = 0;
  uint32_t bad;
  do {
#pragma unroll
    for (int i = 0; i < N; i++) v[i] = ldr4(p + i * stride);
    bad = 0;
#pragma unroll
    for (int i = 0; i < N; i++) bad |= (v[i].x ^ tag) | (v[i].y ^ tag) | (v[i].z ^ tag) | (v[i].w ^ tag);
  } while ((bad & 3) && ++it < 100000);
  float4 s = make_float4(__uint_as_float(v[0].x), __uint_as_float(v[0].y), __uint_as_float(v[0].z), __uint_as_float(v[0].w));
#pragma unroll
  for (int i = 1; i < N; i++) { s.x += __uint_as_float(v[i].x); s.y += __uint_as_float(v[i].y); s.z += __uint_as_float(v[i].z); s.w += __uint_as_float(v[i].w); }
  return s;
}
__device__ __forceinline__ float rbf(float x) { return blo(pack2(x, 0.f)); }
__device__ __forceinline__ uint64_t mkdesc(uint32_t addr, uint32_t lbo, uint32_t sbo, uint32_t swz) {
  return (uint64_t)((addr & 0x3FFFF) >> 4) | ((uint64_t)(lbo >> 4) << 16) | ((uint64_t)(sbo >> 4) << 32) | ((uint64_t)swz << 62);
}
template <int N> __device__ __forceinline__ void regfence(float* d) {
#pragma unroll
  for (int i = 0; i < N; i++) asm volatile("" : "+f"(d[i])::"memory");
}

__device__ __forceinline__ void wgmma_rs_32_0(float* d, uint32_t a0, uint32_t a1, uint32_t a2, uint32_t a3, uint64_t db, int sd) {
  asm volatile("{ .reg .pred p; setp.ne.b32 p, %21, 0; wgmma.mma_async.sync.aligned.m64n32k16.f32.bf16.bf16 {%0,%1,%2,%3,%4,%5,%6,%7,%8,%9,%10,%11,%12,%13,%14,%15}, {%16,%17,%18,%19}, %20, p, 1, 1, 0; }"
   : "+f"(d[0]), "+f"(d[1]), "+f"(d[2]), "+f"(d[3]), "+f"(d[4]), "+f"(d[5]), "+f"(d[6]), "+f"(d[7]), "+f"(d[8]), "+f"(d[9]), "+f"(d[10]), "+f"(d[11]), "+f"(d[12]), "+f"(d[13]), "+f"(d[14]), "+f"(d[15]) : "r"(a0), "r"(a1), "r"(a2), "r"(a3), "l"(db), "r"(sd));
}
__device__ __forceinline__ void wgmma_rs_160_1(float* d, uint32_t a0, uint32_t a1, uint32_t a2, uint32_t a3, uint64_t db, int sd) {
  asm volatile("{ .reg .pred p; setp.ne.b32 p, %85, 0; wgmma.mma_async.sync.aligned.m64n160k16.f32.bf16.bf16 {%0,%1,%2,%3,%4,%5,%6,%7,%8,%9,%10,%11,%12,%13,%14,%15,%16,%17,%18,%19,%20,%21,%22,%23,%24,%25,%26,%27,%28,%29,%30,%31,%32,%33,%34,%35,%36,%37,%38,%39,%40,%41,%42,%43,%44,%45,%46,%47,%48,%49,%50,%51,%52,%53,%54,%55,%56,%57,%58,%59,%60,%61,%62,%63,%64,%65,%66,%67,%68,%69,%70,%71,%72,%73,%74,%75,%76,%77,%78,%79}, {%80,%81,%82,%83}, %84, p, 1, 1, 1; }"
   : "+f"(d[0]), "+f"(d[1]), "+f"(d[2]), "+f"(d[3]), "+f"(d[4]), "+f"(d[5]), "+f"(d[6]), "+f"(d[7]), "+f"(d[8]), "+f"(d[9]), "+f"(d[10]), "+f"(d[11]), "+f"(d[12]), "+f"(d[13]), "+f"(d[14]), "+f"(d[15]), "+f"(d[16]), "+f"(d[17]), "+f"(d[18]), "+f"(d[19]), "+f"(d[20]), "+f"(d[21]), "+f"(d[22]), "+f"(d[23]), "+f"(d[24]), "+f"(d[25]), "+f"(d[26]), "+f"(d[27]), "+f"(d[28]), "+f"(d[29]), "+f"(d[30]), "+f"(d[31]), "+f"(d[32]), "+f"(d[33]), "+f"(d[34]), "+f"(d[35]), "+f"(d[36]), "+f"(d[37]), "+f"(d[38]), "+f"(d[39]), "+f"(d[40]), "+f"(d[41]), "+f"(d[42]), "+f"(d[43]), "+f"(d[44]), "+f"(d[45]), "+f"(d[46]), "+f"(d[47]), "+f"(d[48]), "+f"(d[49]), "+f"(d[50]), "+f"(d[51]), "+f"(d[52]), "+f"(d[53]), "+f"(d[54]), "+f"(d[55]), "+f"(d[56]), "+f"(d[57]), "+f"(d[58]), "+f"(d[59]), "+f"(d[60]), "+f"(d[61]), "+f"(d[62]), "+f"(d[63]), "+f"(d[64]), "+f"(d[65]), "+f"(d[66]), "+f"(d[67]), "+f"(d[68]), "+f"(d[69]), "+f"(d[70]), "+f"(d[71]), "+f"(d[72]), "+f"(d[73]), "+f"(d[74]), "+f"(d[75]), "+f"(d[76]), "+f"(d[77]), "+f"(d[78]), "+f"(d[79]) : "r"(a0), "r"(a1), "r"(a2), "r"(a3), "l"(db), "r"(sd));
}
__device__ __forceinline__ void wgmma_rs_192_0(float* d, uint32_t a0, uint32_t a1, uint32_t a2, uint32_t a3, uint64_t db, int sd) {
  asm volatile("{ .reg .pred p; setp.ne.b32 p, %101, 0; wgmma.mma_async.sync.aligned.m64n192k16.f32.bf16.bf16 {%0,%1,%2,%3,%4,%5,%6,%7,%8,%9,%10,%11,%12,%13,%14,%15,%16,%17,%18,%19,%20,%21,%22,%23,%24,%25,%26,%27,%28,%29,%30,%31,%32,%33,%34,%35,%36,%37,%38,%39,%40,%41,%42,%43,%44,%45,%46,%47,%48,%49,%50,%51,%52,%53,%54,%55,%56,%57,%58,%59,%60,%61,%62,%63,%64,%65,%66,%67,%68,%69,%70,%71,%72,%73,%74,%75,%76,%77,%78,%79,%80,%81,%82,%83,%84,%85,%86,%87,%88,%89,%90,%91,%92,%93,%94,%95}, {%96,%97,%98,%99}, %100, p, 1, 1, 0; }"
   : "+f"(d[0]), "+f"(d[1]), "+f"(d[2]), "+f"(d[3]), "+f"(d[4]), "+f"(d[5]), "+f"(d[6]), "+f"(d[7]), "+f"(d[8]), "+f"(d[9]), "+f"(d[10]), "+f"(d[11]), "+f"(d[12]), "+f"(d[13]), "+f"(d[14]), "+f"(d[15]), "+f"(d[16]), "+f"(d[17]), "+f"(d[18]), "+f"(d[19]), "+f"(d[20]), "+f"(d[21]), "+f"(d[22]), "+f"(d[23]), "+f"(d[24]), "+f"(d[25]), "+f"(d[26]), "+f"(d[27]), "+f"(d[28]), "+f"(d[29]), "+f"(d[30]), "+f"(d[31]), "+f"(d[32]), "+f"(d[33]), "+f"(d[34]), "+f"(d[35]), "+f"(d[36]), "+f"(d[37]), "+f"(d[38]), "+f"(d[39]), "+f"(d[40]), "+f"(d[41]), "+f"(d[42]), "+f"(d[43]), "+f"(d[44]), "+f"(d[45]), "+f"(d[46]), "+f"(d[47]), "+f"(d[48]), "+f"(d[49]), "+f"(d[50]), "+f"(d[51]), "+f"(d[52]), "+f"(d[53]), "+f"(d[54]), "+f"(d[55]), "+f"(d[56]), "+f"(d[57]), "+f"(d[58]), "+f"(d[59]), "+f"(d[60]), "+f"(d[61]), "+f"(d[62]), "+f"(d[63]), "+f"(d[64]), "+f"(d[65]), "+f"(d[66]), "+f"(d[67]), "+f"(d[68]), "+f"(d[69]), "+f"(d[70]), "+f"(d[71]), "+f"(d[72]), "+f"(d[73]), "+f"(d[74]), "+f"(d[75]), "+f"(d[76]), "+f"(d[77]), "+f"(d[78]), "+f"(d[79]), "+f"(d[80]), "+f"(d[81]), "+f"(d[82]), "+f"(d[83]), "+f"(d[84]), "+f"(d[85]), "+f"(d[86]), "+f"(d[87]), "+f"(d[88]), "+f"(d[89]), "+f"(d[90]), "+f"(d[91]), "+f"(d[92]), "+f"(d[93]), "+f"(d[94]), "+f"(d[95]) : "r"(a0), "r"(a1), "r"(a2), "r"(a3), "l"(db), "r"(sd));
}
__device__ __forceinline__ void wgmma_ss_8_10(float* d, uint64_t da, uint64_t db, int sd) {
  asm volatile("{ .reg .pred p; setp.ne.b32 p, %6, 0; wgmma.mma_async.sync.aligned.m64n8k16.f32.bf16.bf16 {%0,%1,%2,%3}, %4, %5, p, 1, 1, 1, 0; }"
   : "+f"(d[0]), "+f"(d[1]), "+f"(d[2]), "+f"(d[3]) : "l"(da), "l"(db), "r"(sd));
}
__device__ __forceinline__ void wgmma_ss_192_01(float* d, uint64_t da, uint64_t db, int sd) {
  asm volatile("{ .reg .pred p; setp.ne.b32 p, %98, 0; wgmma.mma_async.sync.aligned.m64n192k16.f32.bf16.bf16 {%0,%1,%2,%3,%4,%5,%6,%7,%8,%9,%10,%11,%12,%13,%14,%15,%16,%17,%18,%19,%20,%21,%22,%23,%24,%25,%26,%27,%28,%29,%30,%31,%32,%33,%34,%35,%36,%37,%38,%39,%40,%41,%42,%43,%44,%45,%46,%47,%48,%49,%50,%51,%52,%53,%54,%55,%56,%57,%58,%59,%60,%61,%62,%63,%64,%65,%66,%67,%68,%69,%70,%71,%72,%73,%74,%75,%76,%77,%78,%79,%80,%81,%82,%83,%84,%85,%86,%87,%88,%89,%90,%91,%92,%93,%94,%95}, %96, %97, p, 1, 1, 0, 1; }"
   : "+f"(d[0]), "+f"(d[1]), "+f"(d[2]), "+f"(d[3]), "+f"(d[4]), "+f"(d[5]), "+f"(d[6]), "+f"(d[7]), "+f"(d[8]), "+f"(d[9]), "+f"(d[10]), "+f"(d[11]), "+f"(d[12]), "+f"(d[13]), "+f"(d[14]), "+f"(d[15]), "+f"(d[16]), "+f"(d[17]), "+f"(d[18]), "+f"(d[19]), "+f"(d[20]), "+f"(d[21]), "+f"(d[22]), "+f"(d[23]), "+f"(d[24]), "+f"(d[25]), "+f"(d[26]), "+f"(d[27]), "+f"(d[28]), "+f"(d[29]), "+f"(d[30]), "+f"(d[31]), "+f"(d[32]), "+f"(d[33]), "+f"(d[34]), "+f"(d[35]), "+f"(d[36]), "+f"(d[37]), "+f"(d[38]), "+f"(d[39]), "+f"(d[40]), "+f"(d[41]), "+f"(d[42]), "+f"(d[43]), "+f"(d[44]), "+f"(d[45]), "+f"(d[46]), "+f"(d[47]), "+f"(d[48]), "+f"(d[49]), "+f"(d[50]), "+f"(d[51]), "+f"(d[52]), "+f"(d[53]), "+f"(d[54]), "+f"(d[55]), "+f"(d[56]), "+f"(d[57]), "+f"(d[58]), "+f"(d[59]), "+f"(d[60]), "+f"(d[61]), "+f"(d[62]), "+f"(d[63]), "+f"(d[64]), "+f"(d[65]), "+f"(d[66]), "+f"(d[67]), "+f"(d[68]), "+f"(d[69]), "+f"(d[70]), "+f"(d[71]), "+f"(d[72]), "+f"(d[73]), "+f"(d[74]), "+f"(d[75]), "+f"(d[76]), "+f"(d[77]), "+f"(d[78]), "+f"(d[79]), "+f"(d[80]), "+f"(d[81]), "+f"(d[82]), "+f"(d[83]), "+f"(d[84]), "+f"(d[85]), "+f"(d[86]), "+f"(d[87]), "+f"(d[88]), "+f"(d[89]), "+f"(d[90]), "+f"(d[91]), "+f"(d[92]), "+f"(d[93]), "+f"(d[94]), "+f"(d[95]) : "l"(da), "l"(db), "r"(sd));
}

#define HINT(x) x

__global__ void __cluster_dims__(2, 1, 1) __launch_bounds__(384, 1) fused_kernel(const __nv_bfloat16* __restrict__ pk, const __nv_bfloat16* __restrict__ pv,
    const __nv_bfloat16* __restrict__ pshift, const __nv_bfloat16* __restrict__ pssm, const __nv_bfloat16* __restrict__ pD, uint8_t* ps, const __grid_constant__ Params p) {
  extern __shared__ __align__(1024) uint8_t smem_raw[];
  const uint32_t t_start = clk();
  const uint32_t sb = smem_u32(smem_raw);
  const uint32_t bars = sb + O_BAR;
  const int tid = threadIdx.x, lane = tid & 31;
  const int warp = __shfl_sync(0xffffffffu, tid >> 5, 0);
  const int b = blockIdx.x, kh = b & 1;
  const int part = b / 20;
  auto BAR = [&](int i) { return bars + 8 * i; };
#define ROLE ROLE_(lds32(sb + O_ROLE))
#define ROLEU ROLE_(__shfl_sync(0xffffffffu, lds32(sb + O_ROLE), 0))
#define ROLE_(x) const int ro = x, rb = ro >> 3, cg = (ro >> 1) & 3, fs = kh * 4 + cg, vr = min(rb, 14) / 3, vt = min(rb, 14) % 3; \
  const uint32_t ord = vr == 3 ? 0x42310 : vr == 4 ? 0x32410 : 0x43210; uint8_t* const misc = ps + (pgo(rb, 0) ^ cgrp(G_M)); \
  (void)fs; (void)vt; (void)ord; (void)misc
  if (tid == 0) TSTAMP(63);
#define EPLOAD const uint32_t e0 = ldr(g_sync + Y_EP + b * 32 + (lane & (uint32_t)(uintptr_t)ps))
#define EPOCH const uint32_t ep = __shfl_sync(0xffffffffu, e0, 0) + 1
#define EPOCHU const uint32_t ep = __shfl_sync(0xffffffffu, lds32(sb + O_ROLE + 4), 0)

  if (warp < 4) {
    asm volatile("setmaxnreg.dec.sync.aligned.u32 40;");
    const int hw = warp - 2;
    if (warp == 0) {
      EPLOAD;
      const int u = b >> 1, cls = u < 4 ? 4 + u : u < 36 ? (u - 4) >> 3 : 4 + (u - 36) / 7, pos = u < 4 ? 7 : u < 36 ? (u - 4) & 7 : (u - 36) % 7;
      const uint32_t pa = (pgo(2 * cls, 7) ^ cgrp(G_M)) + pos * 128;
      if (!kh && lane < 4) stg128(ps + (pa ^ (lane & 2) << 11) + (lane & 1) * 16, 0, 0, 0, 0);
      bar_sync(1, 384);
      asm volatile("barrier.cluster.arrive.relaxed.aligned;" ::: "memory");
      uint32_t far = 0;
      if (!kh && lane == 0) {
        uint32_t x, y;
        TSTAMP(113);
        asm volatile("atom.relaxed.gpu.global.exch.b32 %0, [%2], 0;\n atom.relaxed.gpu.global.exch.b32 %1, [%3], 0;" : "=r"(x), "=r"(y) : "l"(ps + pa), "l"(ps + (pa ^ 4096)) : "memory");
        asm volatile("{ .reg .pred p; setp.ne.u32 p, %0, 0; @p trap; mov.u32 %0, %%clock; }" : "+r"(x)::"memory");
        asm volatile("{ .reg .pred p; setp.ne.u32 p, %0, 0; @p trap; mov.u32 %0, %%clock; }" : "+r"(y)::"memory");
        far = y - x;
        TSTAMP(11);
      }
      EPOCH;
      if (lane == 0) TSTAMP(114);
      {
        uint32_t* f = g_sync + Y_CLS + cls * 32;
        if (!kh && lane == 0) str(f + pos, ep << 4 | (far < 100) << 3 | pos);
        uint32_t v;
        int it = 0;
        do v = ldr(f + (lane & 7)); while (__any_sync(0xffffffffu, (v ^ ep << 4) > 15) && ++it < 100000);
        const uint32_t rank = __popc(__ballot_sync(0xffffffffu, v < __shfl_sync(0xffffffffu, v, pos)) & 255);
        if (lane == 0) sts64(sb + O_ROLE, cls * 16 + rank * 2 + kh, ep);
        if (lane == 0) { mbar_arrive(BAR(B_ROLE)); TSTAMP(0); }
        __syncwarp();
      }
      ROLEU;
      {
        const uint32_t* f = g_sync + Y_KV + (min(lane, 4) * 4 + (b >> 5)) * 32;
        const uint32_t tw = lane != 5 ? T_W0 : b * D_WM + (part < NE ? T_WM0 : T_WM2 - 20 * NE * D_WM);
        uint32_t pend = b < 120 ? 127 : 95;
        int it = 0;
        do {
          uint32_t v = ep * 32;
          HINT(if (lane < 5) v = ldr(f));
          uint32_t m = __ballot_sync(0xffffffffu, (lane < 5 ? (int)(v - ep * 32) >= 0 : clk() - t_start >= tw) || ++it > 100000) & pend;
          pend &= ~m;
          for (; m; m &= m - 1) {
            const int j = __ffs(m) - 1;
            if (elect()) {
              if (j < 5) {
                TSTAMP(2 + j);
                mbar_expect(BAR(B_KV + j), 4096);
                bulk_ld(sb + bnd(j) + U_KV, ps + (pgo(b >> 3, b & 7) ^ cgrp(G_KV + j)), 4096, BAR(B_KV + j));
              } else if (j == 5) {
                const int x = (b >> 1) % 10, col = part < 5 ? (x >> 1) * D_ + part * 128 + (x & 1) * 64 : 5 * D_ + x * 64;
                mbar_expect(BAR(B_WM), 40960);
                tma2d(sb, &p.m_wm, col, kh * 320, BAR(B_WM));
                tma2d(sb + 20480, &p.m_wm, col, kh * 320 + 160, BAR(B_WM));
                TSTAMP(106 + (part >= NE));
              } else {
                bulk_pf((kh ? p.wu : p.wg) + (b >> 1) * 2 * F_, 6144);
                TSTAMP(108);
              }
            }
          }
        } while (pend);
      }
      auto loadW = [&](int slot, int ph, int k0) {
        mbar_wait(BAR(B_EMPTY + slot), ph);
        if (elect()) {
          mbar_expect(BAR(B_FULL + slot), SLOT);
          tma3d(sb + slot * SLOT, &p.m_wg, 0, k0, fs * 3, BAR(B_FULL + slot));
          tma3d(sb + slot * SLOT + 12288, &p.m_wu, 0, k0, fs * 3, BAR(B_FULL + slot));
        }
      };
#pragma unroll 1
      for (int s = 0; s < 3; s++) loadW(s + 2, 0, s * 32);
      if (lane == 0) TSTAMP(10);
      int slot = 2, ph = 0;
      uint32_t xv = ep * 16 - 1;
#pragma unroll 1
      for (int s = 0; s < 20; s++) {
        const int rd = (ord >> (s & 28)) & 7;
        const uint32_t o = tile(rb, G_X, rd * 4 + (s & 3));
        if (s > 2) loadW(slot, ph, rd * 128 + (s & 3) * 32);
        HINT(poll_lane(xv, misc + M_X + lane * 4, ep * 16, rd * 2 + ((s >> 1) & 1)));
        if (elect()) {
          tma3d(sb + slot * SLOT + 24576, &p.m_s, 0, (o & 16383) >> 9, o >> 14, BAR(B_FULL + slot));
          if ((0x71 >> s) & 1) bulk_pf((kh ? p.wu : p.wg) + (max(s - 2, 1) * 128 + (b >> 1) * 2) * F_, 6144);
          if ((0xc80 >> s) & 1) bulk_pf(p.w2 + b * 7680 + max(s - 9, 0) * 2560, 5120);
          if (s == 0) TSTAMP(19);
          if (s == 16) TSTAMP(1);
        }
        if (++slot == 6) { slot = s == 3 ? 2 : 0; ph ^= 1; }
      }
      __syncwarp();
      asm volatile("barrier.cluster.wait.aligned;" ::: "memory");
#pragma unroll 1
      for (int s = 0; s < 12; s++) {
        const int e = s & 7;
        const uint32_t d = sb + w2entry(e), st = (e & 3) == 3 ? SLOT : 8192;
        const int k0 = kh * 768 + (s < 3 ? cg * 192 + s * 64 : (cg ^ (1 + s % 3)) * 192 + (s / 3 - 1) * 64), c0 = cg * 160 + (cg & 1) * 32;
        mbar_wait(BAR(s >= 8 ? B_W2E + e : B_EMPTY + s - ((s + 1) >> 2)), 0);
        if (elect()) {
          mbar_expect(BAR(B_W2F + e), 24576);
          tma2d(d, &p.m_w2a, c0, k0, BAR(B_W2F + e));
          tma2d(d + st, &p.m_w2a, c0 + 64, k0, BAR(B_W2F + e));
          tma3d(d + 2 * st, &p.m_w2b, 0, k0, cg * 5 + (~cg & 1) * 4, BAR(B_W2F + e));
        }
      }
    } else {
      if (warp == 1) {
        bar_sync(1, 384);
        asm volatile("barrier.cluster.arrive.relaxed.aligned;" ::: "memory");
        if (lane == 0) TSTAMP(112);
        unrolled<NLD>([&](auto I) {
          constexpr uint32_t e = nth_load(I.v), n = e & 15, kind = (e >> 4) & 15;
          while (clk() - t_start < (e >> 8) + (n == 5 ? (b >> 2) * D_Q : 0)) {}
          if (kind == 1 && n == 5) mbar_wait(BAR(B_ROLE), 0);
          if (elect()) {
            if constexpr (kind == 0) {
              const uint32_t d = sb + kreg(n), bar = BAR(B_KIN + n);
              const int ch = n * 128 + (b & 3) * 32, tg = (b >> 2) * 8;
              mbar_expect(bar, 9984);
              tma3d(d, &p.m_k, ch, tg, 0, bar);
              tma3d(d + voff(n), &p.m_v, ch, tg, 0, bar);
              tma3d(d + 4096, &p.m_kh, ch, tg - 1, 5, bar);
              bulk_ld(d + 5632, pshift + ch * 4, 256, bar);
            } else if constexpr (kind == 1 && n < 5) {
              mbar_expect(BAR(B_SSM + n), 4096);
              bulk_ld(sb + bnd(n) + U_RAW, pssm + (size_t)(n * 128 + b) * S_, 4096, BAR(B_SSM + n));
            } else {
              mbar_expect(BAR(B_QIN), 20480);
              tma3d(sb + O_REG, &p.m_q, 0, lds32(sb + O_ROLE) * 16, 0, BAR(B_QIN));
            }
            TSTAMP(96 + I.v);
          }
        });
        ROLEU;
        EPOCHU;
#pragma unroll 1
        for (int jj = 0; jj < 5; jj++) {
          const int j = (ord >> (jj * 4)) & 7;
          const uint32_t ma = sb + (jj & 1 ? O_ST : O_MA);
          uint32_t pend = 3;
          auto watch = [&](uint32_t need) {
            int it = 0;
            while (pend & need) {
              const uint32_t target = ep * (lane ? 20 : 128);
              uint32_t v = target;
              HINT(if ((pend >> lane) & 1) v = ldr(g_sync + (lane ? Y_MOD : Y_Y) + j * 32));
              const uint32_t m = __ballot_sync(0xffffffffu, (int)(v - target) >= 0 || ++it > 100000) & pend;
              if ((m & 1) && elect()) {
                if (jj < 2) TSTAMP(47 + jj);
                mbar_expect(BAR(B_YF + (jj & 1)), 4096);
                bulk_ld(sb + (jj & 1 ? O_BP : O_Y), ps + (pgo(rb, ro & 7) ^ cgrp(G_Y + j)), 4096, BAR(B_YF + (jj & 1)));
              }
              pend &= ~m;
            }
          };
          if (jj >= 2) mbar_wait(BAR(B_YE + (jj & 1)), jj >> 2);
          watch(2);
#pragma unroll 1
          for (int i = 0; i < 64; i += 32) {
            const int t = i + lane;
            uint2 v[10];
            uint32_t bad;
            int it = 0;
            do {
              bad = 0;
#pragma unroll
              for (int k = 0; k < 10; k++) v[k] = ldr2(g_mod + j * 2 * D_ + k * 128 + t * 2);
#pragma unroll
              for (int k = 0; k < 10; k++) bad |= (v[k].x ^ ep) | (v[k].y ^ ep);
            } while (__any_sync(0xffffffffu, bad & 3) && ++it < 100000);
            auto vec = [&](int k) { return pack2(__uint_as_float(v[k].x) + __uint_as_float(v[k + 5].x), __uint_as_float(v[k].y) + __uint_as_float(v[k + 5].y)); };
            const uint32_t ga = vec(2);
            const uint32_t cc = hadd2(vec(4), 0x3F803F80u);
            sts32(ma + t * 4, hmul2(ga, hadd2(vec(1), 0x3F803F80u)));
            sts32(ma + 256 + t * 4, hmul2(ga, vec(0)));
            sts32(ma + 512 + t * 4, cc);
            if (j == vr) {
              sts32(sb + O_CS + (t >> 2) * 32 + (t & 3) * 4, cc);
              sts32(sb + O_CS + (t >> 2) * 32 + (t & 3) * 4 + 16, vec(3));
              fence_async_smem();
            }
          }
          __syncwarp();
          if (lane == 0) {
            mbar_arrive(BAR(B_PR + (jj & 1)));
            if (j == vr) mbar_arrive(BAR(B_CS));
            if (jj < 3) TSTAMP(jj < 2 ? 7 + jj : 79);
          }
          watch(1);
        }
        HINT(poll_ge(g_sync + Y_MOD + 160, ep * 20));
#pragma unroll 1
        for (int i = 0; i < 2; i++) {
          if (i == 0 || lane < 8) {
            const float4 s = gather4<2>(g_mod + 10 * D_ + cg * 160 + (i ? (~cg & 1) * 128 : (cg & 1) * 32) + lane * 4, D_, ep);
            sts128(sb + O_GB + i * 512 + lane * 16, __float_as_uint(rbf(s.x)), __float_as_uint(rbf(s.y)), __float_as_uint(rbf(s.z)), __float_as_uint(rbf(s.w)));
          }
        }
        if (lane == 0) { sts128(sb + O_BP + 6144, 0, 0, 0, 0); mbar_arrive(BAR(B_VV)); }
        mbar_wait(BAR(B_YE + 1), 1);
      } else {
        const int t0 = tid & 63;
#pragma unroll
        for (int j = 0; j < 5; j++) {
          if (tid < 83) sts128(sb + bnd(j) + (lane < 17 ? U_KV + 4096 + lane * 16 : lane == 17 ? U_RAW - 16 : U_ODD - 16), 0, 0, 0, 0);
        }
        bar_sync(1, 384);
        asm volatile("barrier.cluster.arrive.relaxed.aligned;" ::: "memory");
        fence_async_smem();
        uint32_t dv;
        asm volatile("ld.global.nc.u16 %0, [%1];" : "=r"(dv) : "l"(pD + min(lane, 4) * 128 + b) : "memory");
        if (elect()) {
#pragma unroll
          for (int i = 0; i < 6; i++) asm volatile("prefetch.tensormap [%0];" ::"l"(&p.m_k + hw * 6 + i) : "memory");
        }
        asm volatile("prefetch.global.L2 [%0];" ::"l"(p.c + kh * 320 + min(t0, 39) * 8) : "memory");
#pragma unroll 1
        for (int j = 0; j < 5; j++) {
          const uint32_t ra = sb + bnd(j) + U_RAW + hw * 2048 + lane * 16;
          const float dj = blo(__shfl_sync(0xffffffffu, dv, j));
          mbar_wait(BAR(B_SSM + j), 0);
          if (tid == 64 && j == 0) TSTAMP(77);
#pragma unroll
          for (int i = 0; i < 4; i++) {
            uint4 w = lds128(ra + i * 512);
            const uint32_t pv = lds32(ra + i * 512 - 4);
            if (i == 0 && tid == 64) { w.x = prmt(pack2(blo(w.x) + dj, 0.f), w.x, 0x7610); sts32(ra, w.x); }
            sts128(ra + (U_ODD - U_RAW) + i * 512, prmt(pv, w.x, 0x5432), prmt(w.x, w.y, 0x5432), prmt(w.y, w.z, 0x5432), prmt(w.z, w.w, 0x5432));
          }
          __syncwarp();
          if (lane == 0) mbar_arrive(BAR(B_PL + j));
          if (tid == 64) TSTAMP(32 + j);
          if (j == 0) {
            const uint4 cv = ldr4((const uint32_t*)p.c + kh * 160 + min(t0, 39) * 4);
            auto silu = [](uint32_t x) { return pack2(__fdividef(blo(x), 1.f + __expf(-blo(x))), __fdividef(bhi(x), 1.f + __expf(-bhi(x)))); };
            sts128(sb + O_SILU + t0 * 16, silu(cv.x), silu(cv.y), silu(cv.z), silu(cv.w));
            fence_async_smem();
          }
        }
        mbar_wait(BAR(B_LN), 0);
        ROLEU;
        uint32_t ya = lane * 32 + (lane & 4) * 4, xl = (lane ^ lane >> 3) * 16, pl = (lane & 3) * 16;
        const uint32_t tt = -(lds32(sb + O_ROLE + 4) & 1), ln[2] = {lds32(sb + O_LN + (lane & 28)), lds32(sb + O_LN + 32 + (lane & 28))};
        float sx[4] = {0.f, 0.f, 0.f, 0.f};
        keep(ya); keep(xl); keep(pl);
#pragma unroll 1
        for (int it = 0; it != 10;) {
          const int j = (ord >> (it * 2 & 28)) & 7, odd = (it >> 1) & 1, g = (it & 1) * 2 + hw;
          const uint32_t pm = sb + (odd ? O_ST : O_MA) + g * 64, yo = sb + (odd ? O_BP : O_Y) + g * 1024, qo = sb + O_REG + (j * 4 + g) * 1024;
          uint32_t q[8], m[8], y[8];
          mbar_wait(BAR(B_PR + odd), (it >> 2) & 1);
          {
            const uint4 q0 = lds128(addu(xl, qo)), a4 = lds128(addu(pl, pm)), b4 = lds128(addu(pl, pm) + 256), q1 = lds128(addu(xl, qo) + 512);
            const uint32_t ma[4] = {a4.x, a4.y, a4.z, a4.w}, mb[4] = {b4.x, b4.y, b4.z, b4.w};
            q[0] = q0.x; q[1] = q0.y; q[2] = q0.z; q[3] = q0.w; q[4] = q1.x; q[5] = q1.y; q[6] = q1.z; q[7] = q1.w;
#pragma unroll
            for (int i = 0; i < 8; i++) m[i] = hfma2(hfma2lh(q[i], ln[i >> 2]), ma[i & 3], mb[i & 3]);
          }
          mbar_wait(BAR(B_YF + odd), (it >> 2) & 1);
          if (!(xl | hw) && it < 6 && !(it & 1)) TSTAMP(it == 0 ? 49 : it == 2 ? 58 : 80);
          ldsm4t(addu(ya, yo), y[0], y[1], y[2], y[3]);
          ldsm4t(addu(ya, yo) ^ 16, y[4], y[5], y[6], y[7]);
#pragma unroll
          for (int i = 0; i < 8; i++) q[i] = hfma2(m[i], y[i], q[i]);
          if ((__ballot_sync(0xffffffffu, ((y[0] ^ tt) | (y[1] ^ tt) | (y[2] ^ tt) | (y[3] ^ tt) | (y[4] ^ tt) | (y[5] ^ tt) | (y[6] ^ tt) | (y[7] ^ tt)) & 0x00010001u) & 15) && it < 16) {
#pragma unroll 1
            for (int hf = 0; hf < 32; hf += 16) refetch16(ps + ((pgo(rb, ro & 7) ^ cgrp(G_Y + j)) + g * 1024 + (ya ^ hf)), (ya ^ hf) + yo, tt);
            __syncwarp();
            it += 16;
            continue;
          }
          const uint4 c4 = lds128(addu(pl, pm) + 512);
          uint8_t* const xg = ps + addu(xl, tile(rb, G_X, j * 4 + g) + (ro & 4) * 4096 + (ro & 3) * 1024);
          stg128(xg, tag0(hmul2(q[0], c4.x), tt), hmul2(q[1], c4.y), hmul2(q[2], c4.z), hmul2(q[3], c4.w));
          stg128(xg + 512, tag0(hmul2(q[4], c4.x), tt), hmul2(q[5], c4.y), hmul2(q[6], c4.z), hmul2(q[7], c4.w));
          asm volatile("{ .reg .pred p; elect.sync _|p, 0xffffffff; @p red.relaxed.gpu.global.add.u32 [%0], 1; @p mbarrier.arrive.shared::cta.b64 _, [%1]; }"
                       ::"l"(misc + M_X + j * 8 + (it & 1) * 4), "r"(BAR(B_YE + odd)) : "memory");
          uint8_t* const og = p.out + addu((xl >> 6) * 1280 + pl, ro * 20480 + (j * 4 + g) * 64);
          stg128(og, q[0], q[1], q[2], q[3]);
          stg128(og + 10240, q[4], q[5], q[6], q[7]);
#pragma unroll
          for (int i = 0; i < 8; i++) {
            const float f = blo(q[i]), h = bhi(q[i]);
            float &s1 = sx[(i >> 2) * 2], &s2 = sx[(i >> 2) * 2 + 1];
            s1 += f; s2 = fmaf(f, f, s2); s1 += h; s2 = fmaf(h, h, s2);
          }
          if (!(xl | hw) && (it & 1)) TSTAMP(12 + ((it & 15) >> 1));
          if (!(xl | hw) && it == 0) TSTAMP(116);
          it = (it & 15) + 1;
        }
        const int lane = ya >> 5, t = hw * 32 + lane;
        EPOCHU;
#pragma unroll
        for (int i = 0; i < 8; i++) sx[i & 3] += __shfl_xor_sync(0xffffffffu, sx[i & 3], (i >> 2) + 1);
        if (!(lane & 3)) sts64(sb + O_SX + t * 2, __float_as_uint(hw ? sx[0] : sx[2]), __float_as_uint(hw ? sx[1] : sx[3]));
        bar_sync(4, 64);
        const float2 so = lds64f(sb + O_SX + (hw ^ 1) * 64 + (xl >> 6) * 8);
        const float mean = ((hw ? sx[2] : sx[0]) + so.x) * (1.f / D_);
        const uint32_t pa = pack2(-mean, sqrtf(fmaxf(((hw ? sx[3] : sx[1]) + so.y) * (1.f / D_) - mean * mean, 0.f) + 1e-5f));
        if (!(lane & 3))
          asm volatile("st.relaxed.gpu.global.v2.u32 [%0], {%1,%2};" ::"l"(misc + M_ST + (ro & 7) * 128 + t * 2), "r"(pa), "r"(tagf(__fdividef(1.f, bhi(pa) * bhi(pa)), ep)) : "memory");
        asm volatile("fence.acq_rel.gpu;" ::: "memory");
        __syncwarp();
        if (lane == 0) hint_add((uint32_t*)(misc + M_O));
        uint4 v;
        int it = 0;
        do v = ldr4((const uint32_t*)(misc + M_ST + t * 16)); while ((((v.y ^ ep) | (v.w ^ ep)) & 3) && ++it < 100000);
        sts128(sb + O_ST + t * 16, v.x, v.y, v.z, v.w);
        __syncwarp();
        if (lane == 0) mbar_arrive(BAR(B_ST + hw));
        if (t == 0) TSTAMP(52);
      }
      ROLEU;
      EPOCHU;
      int lane;
      asm volatile("mov.u32 %0, %%laneid;" : "=r"(lane));
      {
        HINT(poll_ge(g_sync + Y_VV + fs * 32, ep * 32));
        uint32_t v[20], bad;
        int it = 0;
        const uint32_t* g = g_vv + fs * 1920 + (hw + 1) * 128 + lane;
        do {
          bad = 0;
#pragma unroll
          for (int k = 0; k < 20; k++) v[k] = ldr(g + ((k % 5) * 384 + (k / 5) * 32));
#pragma unroll
          for (int k = 0; k < 20; k++) bad |= v[k] ^ ep;
        } while (__any_sync(0xffffffffu, bad & 1) && ++it < 100000);
#pragma unroll
        for (int k = 0; k < 4; k++) sts128(sb + O_BP + ((hw + 1) * 128 + k * 32 + lane) * 16, v[5 * k], v[5 * k + 1], v[5 * k + 2], hadd2(v[5 * k + 3], v[5 * k + 4]));
        fence_async_smem();
        __syncwarp();
      }
      if (lane == 0) mbar_arrive(BAR(B_VV));
      if (warp == 1) {
        if (lane == 0) TSTAMP(37);
        uint32_t v;
        int it = 0;
        do asm volatile("ld.acquire.gpu.global.u32 %0, [%1];" : "=r"(v) : "l"(misc + M_O) : "memory"); while ((int)(v - ep * 16) < 0 && ++it < 100000);
        asm volatile("fence.proxy.async.global;" ::: "memory");
        if (lane == 0) { mbar_arrive(BAR(B_X1)); TSTAMP(30); }
      } else {
        const uint32_t* f = (const uint32_t*)(misc + M_H + (kh * 2 + hw) * 64) + (lane & 15);
        uint32_t hv = ep * 4 - 1;
#pragma unroll 1
        for (int i = 0; i < 3; i++) {
          HINT(for (int it = 0; !__all_sync(0xffffffffu, (int)(hv - ep * 4 - i) >= 0 || (lane & 3) == cg) && it < 100000; it++) hv = ldr(f));
          if (lane == 0) { mbar_arrive(BAR(B_HF + hw * 3 + i)); if (i == 0) TSTAMP(17 + hw); }
        }
      }
      __syncwarp();
      asm volatile("barrier.cluster.wait.aligned;" ::: "memory");
    }
  } else {
    const int isE = warp >= 8 ? 1 : 0;
    const int w = warp & 3, r = lane >> 2, c = lane & 3;
    const bool lead = (tid & 127) == 0;
    const int tb = b >> 2;
    if (isE) {
      const int u = tid & 127, t = tb * 64 + r * 8 + w, th = t - (w == 3 ? 0 : 3);
      const uint32_t d = sb + kreg(0) + (u >> 2) * 64 + ((c ^ (r >> 1)) << 4);
      const int o = t * D_ + (b & 3) * 32 + c * 8;
      cpa16(d, pk + o, 16); cpa16(d + voff(0), pv + o, 16);
      cpa16(d + 2048, pk + o + 4 * D_, 16); cpa16(d + voff(0) + 2048, pv + o + 4 * D_, 16);
      if (u < 112) cpa16(w == 3 ? sb + kreg(0) + 5632 + lane * 16 : d + 4096, w == 3 ? pshift + (b & 3) * 128 + lane * 8 : pk + (th < 0 ? o : o - 3 * D_), th < 0 ? 0 : 16);
      if (lead) TSTAMP(74);
    } else {
      if (lane == 0) {
#pragma unroll
        for (int i = 0; i < 18; i++) mbar_init(BAR(w + 4 * i), i < 5 ? 2 : i < 6 ? 4 : 1);
        asm volatile("fence.mbarrier_init.release.cluster;" ::: "memory");
      }
      __syncwarp();
      if (lead) TSTAMP(76);
    }
    EPLOAD;
    bar_sync(1, 384);
    if (tid == 256) TSTAMP(75);
    asm volatile("setmaxnreg.inc.sync.aligned.u32 232;");
    asm volatile("barrier.cluster.arrive.relaxed.aligned;" ::: "memory");
    EPOCH;
    if (isE) {
      asm volatile("cp.async.wait_all;" ::: "memory");
      bar_sync(6, 128);
    }
    uint64_t steps = isE ? sched(1) : sched(0);
    const uint32_t rel = isE ? release(1) : release(0);
#pragma unroll 1
    for (int si = 0; steps; si++, steps >>= 9) {
      const uint32_t todo = (uint32_t)steps;
      if (todo & 1) {
        uint4 x[10];
        mbar_wait(BAR(B_QIN), 0);
        if (lead) TSTAMP(9);
#pragma unroll
        for (int i = 0; i < 10; i++) x[i] = lds128(sb + O_REG + (lane >> 4) * 1024 + w * 256 + (lane & 15) * 16 + i * 2048);
        float z[4] = {0.f, 0.f, 0.f, 0.f};
        auto acc = [&](uint32_t v) { const float f = blo(v), g = bhi(v); z[0] += f; z[1] = fmaf(f, f, z[1]); z[2] += g; z[3] = fmaf(g, g, z[3]); };
#pragma unroll
        for (int i = 0; i < 10; i++) { acc(x[i].x); acc(x[i].y); acc(x[i].z); acc(x[i].w); }
        z[0] += z[2]; z[1] += z[3];
#pragma unroll
        for (int i = 0; i < 3; i++) { z[0] += __shfl_xor_sync(0xffffffffu, z[0], i < 2 ? i + 1 : 16); z[1] += __shfl_xor_sync(0xffffffffu, z[1], i < 2 ? i + 1 : 16); }
        const float mean = z[0] * (1.f / D_), rs = rbf(rsqrtf(fmaxf(z[1] * (1.f / D_) - mean * mean, 0.f) + 1e-5f));
        if (!(lane & 19)) sts32(sb + O_LN + w * 16 + lane, pack2(rs, -mean * rs));
        __syncwarp();
        if (lane == 0) mbar_arrive(BAR(B_LN));
        if (lead) TSTAMP(59);
      }
      if (todo & 14) {
        const int n = ((todo >> 1) & 7) - 1, tg = lane & 7;
        const uint32_t a = sb + kreg(n) + tg * 64 + ((w ^ (tg >> 1)) << 4) + (lane >> 3) * 4;
        if (n) mbar_wait(BAR(B_KIN + n), 0);
        if (lead) TSTAMP(69 + n);
        uint32_t kk[11], x[8];
        const uint4 sw = lds128(sb + kreg(n) + 5632 + w * 64 + (lane & 24) * 2);
#pragma unroll
        for (int i = 0; i < 11; i++) kk[i] = lds32(a + (i < 3 ? 4096 + i * 512 : (i - 3) * 512));
#pragma unroll
        for (int i = 0; i < 8; i++) x[7 - i] = lds32(a + voff(n) + i * 512);
        const uint32_t w0 = prmt(sw.x, sw.z, 0x5410), w1 = prmt(sw.x, sw.z, 0x7632), w2 = prmt(sw.y, sw.w, 0x5410), w3 = prmt(sw.y, sw.w, 0x7632);
#pragma unroll
        for (int i = 0; i < 8; i++) x[7 - i] = hmul2(hfma2(kk[i + 3], w0, hfma2(kk[i + 2], w1, hfma2(kk[i + 1], w2, hmul2(kk[i], w3)))), x[7 - i]);
        const int tw = (~tb & 7) ^ ((~lane & 1) << 2);
#pragma unroll
        for (int i = 0; i < 4; i++) x[2 * i] = settag(x[2 * i], tw == i ? 0x00010001u : 0u, -(ep & 1));
        const uint32_t o = (pgo((b & 3) * 4 + w, (lane >> 3) * 2) ^ cgrp(G_KV + n)) + 4080 - tb * 128 - tg * 16;
        stg128(ps + o, prmt(x[0], x[1], 0x5410), prmt(x[2], x[3], 0x5410), prmt(x[4], x[5], 0x5410), prmt(x[6], x[7], 0x5410));
        stg128(ps + (o ^ 0x3000), prmt(x[0], x[1], 0x7632), prmt(x[2], x[3], 0x7632), prmt(x[4], x[5], 0x7632), prmt(x[6], x[7], 0x7632));
        bar_sync(5 + isE, 128);
        if (lead) { hint_add(g_sync + Y_KV + (n * 4 + (b & 3)) * 32); TSTAMP(64 + n); }
      }
      if (b < 120 && ((todo >> 4) & 3) == 1 + (part >= NE)) {
        float d[4];
        const uint64_t db = mkdesc(sb + O_SILU, 16, 128, 0), da = mkdesc(sb, 4096, 1024, 1);
        mbar_wait(BAR(B_PL + 1), 0);
        mbar_wait(BAR(B_WM), 0);
        if (lead) TSTAMP(81 + min(part, 2));
        wg_fence();
#pragma unroll
        for (int kk = 0; kk < 20; kk++) wgmma_ss_8_10(d, da + kk * 128, db + kk * 2, kk);
        wg_commit();
        wg_wait<0>();
        regfence<4>(d);
        uint32_t* g = g_mod + (part * 2 + kh) * D_ + (b >> 1) % 10 * 64 + w * 16 + r;
        if (c == 0) { str(g, tagf(d[0], ep)); str(g + 8, tagf(d[2], ep)); }
        bar_sync(5 + isE, 128);
        if (lead) { hint_add(g_sync + Y_MOD + part * 32); TSTAMP(part >= 2 ? 60 : 20 + part); }
      }
      if (todo & 448) {
        const int j = ((todo >> 6) & 7) - 1, u = tid & 127;
        const uint32_t ub = sb + bnd(j), sa = ub + ((r & 1) ? U_RAW : U_ODD) + 4 * (8 * w + (r >> 1) - 3 + c);
        uint32_t A[64];
        float d[128];
        mbar_wait(BAR(B_PL + j), 0);
#pragma unroll
        for (int g = 0; g < 16; g++) { A[4 * g] = lds32(sa + g * 256); A[4 * g + 1] = lds32(sa + g * 256 + 128); A[4 * g + 2] = lds32(sa + g * 256 + 16); A[4 * g + 3] = lds32(sa + g * 256 + 144); }
        if (lead) TSTAMP(89 + j);
        mbar_wait(BAR(B_KV + j), 0);
        if ((lds32(ub + U_KV + u * 32 + r * 4) ^ ep) & 1) refetch(ps + (pgo(b >> 3, b & 7) ^ cgrp(G_KV + j)) + u * 32, r * 4, ub + U_KV + u * 32, ep);
        __syncwarp();
        bar_sync(5 + isE, 128);
        if (lead) TSTAMP(53 + j);
        const uint64_t db = mkdesc(ub + U_KV, 16, 128, 0);
        wg_fence();
        wgmma_rs_32_0(d + 0, A[0], A[1], A[2], A[3], db + 0, 0);
        wgmma_rs_32_0(d + 16, A[0], A[1], A[2], A[3], db + 32, 0);
        wgmma_rs_32_0(d + 32, A[0], A[1], A[2], A[3], db + 64, 0);
        wgmma_rs_32_0(d + 48, A[0], A[1], A[2], A[3], db + 96, 0);
        wgmma_rs_32_0(d + 0, A[4], A[5], A[6], A[7], db + 16, 1);
        wgmma_rs_32_0(d + 16, A[4], A[5], A[6], A[7], db + 48, 1);
        wgmma_rs_32_0(d + 32, A[4], A[5], A[6], A[7], db + 80, 1);
        wgmma_rs_32_0(d + 48, A[4], A[5], A[6], A[7], db + 112, 1);
        wgmma_rs_32_0(d + 0, A[8], A[9], A[10], A[11], db + 32, 1);
        wgmma_rs_32_0(d + 16, A[8], A[9], A[10], A[11], db + 64, 1);
        wgmma_rs_32_0(d + 32, A[8], A[9], A[10], A[11], db + 96, 1);
        wgmma_rs_32_0(d + 64, A[0], A[1], A[2], A[3], db + 128, 0);
        wgmma_rs_32_0(d + 0, A[12], A[13], A[14], A[15], db + 48, 1);
        wgmma_rs_32_0(d + 16, A[12], A[13], A[14], A[15], db + 80, 1);
        wgmma_rs_32_0(d + 32, A[12], A[13], A[14], A[15], db + 112, 1);
        wgmma_rs_32_0(d + 48, A[8], A[9], A[10], A[11], db + 128, 1);
        wgmma_rs_32_0(d + 0, A[16], A[17], A[18], A[19], db + 64, 1);
        wgmma_rs_32_0(d + 16, A[16], A[17], A[18], A[19], db + 96, 1);
        wgmma_rs_32_0(d + 32, A[16], A[17], A[18], A[19], db + 128, 1);
        wgmma_rs_32_0(d + 64, A[4], A[5], A[6], A[7], db + 144, 1);
        wgmma_rs_32_0(d + 0, A[20], A[21], A[22], A[23], db + 80, 1);
        wgmma_rs_32_0(d + 16, A[20], A[21], A[22], A[23], db + 112, 1);
        wgmma_rs_32_0(d + 48, A[12], A[13], A[14], A[15], db + 144, 1);
        wgmma_rs_32_0(d + 32, A[20], A[21], A[22], A[23], db + 144, 1);
        wgmma_rs_32_0(d + 0, A[24], A[25], A[26], A[27], db + 96, 1);
        wgmma_rs_32_0(d + 16, A[24], A[25], A[26], A[27], db + 128, 1);
        wgmma_rs_32_0(d + 80, A[0], A[1], A[2], A[3], db + 160, 0);
        wgmma_rs_32_0(d + 64, A[8], A[9], A[10], A[11], db + 160, 1);
        wgmma_rs_32_0(d + 0, A[28], A[29], A[30], A[31], db + 112, 1);
        wgmma_rs_32_0(d + 16, A[28], A[29], A[30], A[31], db + 144, 1);
        wgmma_rs_32_0(d + 48, A[16], A[17], A[18], A[19], db + 160, 1);
        wgmma_rs_32_0(d + 32, A[24], A[25], A[26], A[27], db + 160, 1);
        wgmma_rs_32_0(d + 0, A[32], A[33], A[34], A[35], db + 128, 1);
        wgmma_rs_32_0(d + 16, A[32], A[33], A[34], A[35], db + 160, 1);
        wgmma_rs_32_0(d + 80, A[4], A[5], A[6], A[7], db + 176, 1);
        wgmma_rs_32_0(d + 64, A[12], A[13], A[14], A[15], db + 176, 1);
        wgmma_rs_32_0(d + 0, A[36], A[37], A[38], A[39], db + 144, 1);
        wgmma_rs_32_0(d + 48, A[20], A[21], A[22], A[23], db + 176, 1);
        wgmma_rs_32_0(d + 32, A[28], A[29], A[30], A[31], db + 176, 1);
        wgmma_rs_32_0(d + 16, A[36], A[37], A[38], A[39], db + 176, 1);
        wgmma_rs_32_0(d + 0, A[40], A[41], A[42], A[43], db + 160, 1);
        wgmma_rs_32_0(d + 96, A[0], A[1], A[2], A[3], db + 192, 0);
        wgmma_rs_32_0(d + 80, A[8], A[9], A[10], A[11], db + 192, 1);
        wgmma_rs_32_0(d + 64, A[16], A[17], A[18], A[19], db + 192, 1);
        wgmma_rs_32_0(d + 0, A[44], A[45], A[46], A[47], db + 176, 1);
        wgmma_rs_32_0(d + 48, A[24], A[25], A[26], A[27], db + 192, 1);
        wgmma_rs_32_0(d + 32, A[32], A[33], A[34], A[35], db + 192, 1);
        wgmma_rs_32_0(d + 16, A[40], A[41], A[42], A[43], db + 192, 1);
        wgmma_rs_32_0(d + 0, A[48], A[49], A[50], A[51], db + 192, 1);
        wgmma_rs_32_0(d + 96, A[4], A[5], A[6], A[7], db + 208, 1);
        wgmma_rs_32_0(d + 80, A[12], A[13], A[14], A[15], db + 208, 1);
        wgmma_rs_32_0(d + 64, A[20], A[21], A[22], A[23], db + 208, 1);
        wgmma_rs_32_0(d + 48, A[28], A[29], A[30], A[31], db + 208, 1);
        wgmma_rs_32_0(d + 32, A[36], A[37], A[38], A[39], db + 208, 1);
        wgmma_rs_32_0(d + 16, A[44], A[45], A[46], A[47], db + 208, 1);
        wgmma_rs_32_0(d + 0, A[52], A[53], A[54], A[55], db + 208, 1);
        wgmma_rs_32_0(d + 112, A[0], A[1], A[2], A[3], db + 224, 0);
        wgmma_rs_32_0(d + 96, A[8], A[9], A[10], A[11], db + 224, 1);
        wgmma_rs_32_0(d + 80, A[16], A[17], A[18], A[19], db + 224, 1);
        wgmma_rs_32_0(d + 64, A[24], A[25], A[26], A[27], db + 224, 1);
        wgmma_rs_32_0(d + 48, A[32], A[33], A[34], A[35], db + 224, 1);
        wgmma_rs_32_0(d + 32, A[40], A[41], A[42], A[43], db + 224, 1);
        wgmma_rs_32_0(d + 16, A[48], A[49], A[50], A[51], db + 224, 1);
        wgmma_rs_32_0(d + 0, A[56], A[57], A[58], A[59], db + 224, 1);
        wgmma_rs_32_0(d + 112, A[4], A[5], A[6], A[7], db + 240, 1);
        wgmma_rs_32_0(d + 96, A[12], A[13], A[14], A[15], db + 240, 1);
        wgmma_rs_32_0(d + 80, A[20], A[21], A[22], A[23], db + 240, 1);
        wgmma_rs_32_0(d + 64, A[28], A[29], A[30], A[31], db + 240, 1);
        wgmma_rs_32_0(d + 48, A[36], A[37], A[38], A[39], db + 240, 1);
        wgmma_rs_32_0(d + 32, A[44], A[45], A[46], A[47], db + 240, 1);
        wgmma_rs_32_0(d + 16, A[52], A[53], A[54], A[55], db + 240, 1);
        wgmma_rs_32_0(d + 0, A[60], A[61], A[62], A[63], db + 240, 1);
        wg_commit();
        const uint32_t yoff = ub + w * 2048 + (127 + 2 * w - lane) * 16;
        const uint32_t yoff0 = yoff + (lane < 2 * w ? -2048 : 8192), yoff4 = yoff + (lane < 2 * w ? 6144 : 0);
        wg_wait<0>();
        regfence<128>(d);
        if (rel >> 18 == si) bar_arrive(8, 256);
        if (lead) TSTAMP(42 + j);
        bar_sync(5 + isE, 128);
#pragma unroll
        for (int z = 0; z < 8; z++) {
          uint32_t e[4];
#pragma unroll
          for (int i = 0; i < 4; i++) {
            const int x = 4 * z + i;
            e[i] = x < 31 ? pack2(d[4 * x] + d[4 * x + 6], d[4 * x + 1] + d[4 * x + 7]) : pack2(d[4 * x], d[4 * x + 1]);
          }
          if (z == 0 && c < w) e[0] = 0;
          stsm4t(z == 0 ? yoff0 : z == 4 ? yoff4 : z < 4 ? yoff + 8192 - 512 * z : yoff - 512 * (z - 4), e[0], e[1], e[2], e[3]);
        }
        uint8_t* g = ps + (pgo(u >> 4, (u >> 1) & 7) ^ cgrp(G_Y + j)) + ((b & 97) | (b & 6) << 2 | (b & 24) >> 2) * 32 + ((u ^ (b >> 4)) & 1) * 16;
        bar_sync(5 + isE, 128);
#pragma unroll
        for (int i = 0; i < 2; i++) {
          const uint32_t pa = ub + u * 16 + i * 8192;
          const uint4 p0 = lds128(pa), p1 = lds128(pa + 2048), p2 = lds128(pa + 4096), p3 = lds128(pa + 6144);
          stg128(g + (i << 23), settag(hadd2(hadd2(p0.x, p1.x), hadd2(p2.x, p3.x)), 1, ep), hadd2(hadd2(p0.y, p1.y), hadd2(p2.y, p3.y)),
                 hadd2(hadd2(p0.z, p1.z), hadd2(p2.z, p3.z)), hadd2(hadd2(p0.w, p1.w), hadd2(p2.w, p3.w)));
        }
        bar_sync(5 + isE, 128);
        if (lead) { hint_add(g_sync + Y_Y + j * 32); TSTAMP(84 + j); }
      }
      if (w == 0 && lane < 6 && ((rel >> 3 * lane) & 7) == si) mbar_arrive(BAR(B_EMPTY + lane));
      __syncwarp();
    }
    const int rh = isE ^ kh;
    uint32_t hA[96], hb;
    {
      float ag[96], au[96];
      int slot = 2, prev = 0, ph = 0, s = 0;
      int v0, vo;
      mbar_wait(BAR(B_ROLE), 0);
      { ROLE; v0 = min(vr, 2) * 4; vo = (2 * vt + isE) * 256; }
      const uint64_t dbase = mkdesc(sb, 4096, 1024, 1);
      const uint32_t ck = sb + 24576 + rh * 4096 + w * 1024 + lane * 32 + (r & 1) * 16;
      if (isE) bar_sync(8, 256);
      auto stage = [&](float* vv) {
        const uint64_t dg = dbase + slot * (SLOT >> 4), da = mkdesc(0, 0, 512, 2) | (uint32_t)(dg + ((24576 + rh * 4096) >> 4));
        if (s == LH + LEAD * isE) { if (isE) bar_arrive(7, 256); else bar_sync(7, 256); }
        mbar_wait(BAR(B_FULL + slot), ph);
        if ((lds32(ck + slot * SLOT) ^ ep) & 1) {
          ROLE;
          refetch(ps + tile(rb, G_X, ((ord >> (s & 28)) & 7) * 4 + (s & 3)) + rh * 16384 + w * 1024 + lane * 32, (r & 1) * 16, (ck + slot * SLOT) & ~31u, ep);
        }
        __syncwarp();
        if (s == 0 && lead) TSTAMP(22 + isE);
        if (s && (s & 3) == 0 && tid == 128) TSTAMP(37 + (s >> 2));
        wg_fence();
        wgmma_ss_192_01(ag, da, dg, s);
        wgmma_ss_192_01(au, da, dg + 768, s);
        if (vv) wgmma_ss_8_10(vv, dg + vo, mkdesc(sb + O_CS, 32, 128, 0) + (s & 3) * 8, s & 3);
        wgmma_ss_192_01(ag, da + 2, dg + 128, 1);
        wgmma_ss_192_01(au, da + 2, dg + 896, 1);
        if (vv) wgmma_ss_8_10(vv, dg + vo + 128, mkdesc(sb + O_CS, 32, 128, 0) + (s & 3) * 8 + 4, 1);
        wg_commit();
        wg_wait<1>();
        if (s > 0 && lead) mbar_arrive(BAR(B_EMPTY + prev));
        prev = slot;
        if (++slot == 6) { slot = s == 3 ? 2 : 0; ph ^= 1; }
        ++s;
      };
#pragma unroll 1
      while (s < v0) stage(nullptr);
      {
        float vv[4];
        mbar_wait(BAR(B_CS), 0);
#pragma unroll 1
        while (s < v0 + 4) stage(vv);
        wg_wait<0>();
        regfence<4>(vv);
        ROLE;
        if (c == 0) {
          uint32_t* g = g_vv + (fs * 5 + vr) * 384 + (2 * vt + isE) * 64 + 16 * w + r;
          str(g, settag(pack2(vv[0], vv[1]), 1, ep));
          str(g + 8, settag(pack2(vv[2], vv[3]), 1, ep));
        }
        bar_sync(5 + isE, 128);
        if (lead) hint_add(g_sync + Y_VV + fs * 32);
      }
#pragma unroll 1
      while (s < 20) stage(nullptr);
      {
        mbar_wait(BAR(B_ST + rh), 0);
        const uint32_t a0 = lds32(sb + O_ST + rh * 512 + w * 128 + r * 8), a1 = lds32(sb + O_ST + rh * 512 + w * 128 + r * 8 + 64);
        mbar_wait(BAR(B_VV), 0);
        const uint64_t dp = mkdesc(sb + O_BP, 16, 128, 0);
        wg_fence();
        wgmma_rs_192_0(ag, a0, a1, 0, 0, dp, 1);
        wgmma_rs_192_0(au, a0, a1, 0, 0, dp + 192, 1);
        wg_commit();
        wg_wait<1>();
        if (lead) mbar_arrive(BAR(B_EMPTY + 5));
        wg_wait<0>();
      }
      regfence<96>(ag); regfence<96>(au);
      if (lead) TSTAMP(24 + isE);
      ROLE;
      hb = (pgo(rb, fs) ^ cgrp(G_H + rh)) + (tid & 127) * 16;
#pragma unroll
      for (int kq = 0; kq < 12; kq++) {
#pragma unroll
        for (int i = 0; i < 4; i++) hA[4 * kq + i] = pack2(ag[8 * kq + 2 * i] * au[8 * kq + 2 * i], ag[8 * kq + 2 * i + 1] * au[8 * kq + 2 * i + 1]);
        hA[4 * kq] = settag(hA[4 * kq], lane & 1, ep);
        stg128(ps + (hb ^ (cgrp(kq & 14) & 4096)) + ((kq & 14) << 16) + (kq & 1) * 2048, hA[4 * kq], hA[4 * kq + 1], hA[4 * kq + 2], hA[4 * kq + 3]);
        if ((kq & 3) == 3 && lane == 0) str((uint32_t*)(misc + M_H + (kh * 2 + isE) * 64) + w * 4 + cg, ep * 4 + (kq >> 2));
        if (kq == 3 && tid == 256) TSTAMP(117);
      }
      if (lead) TSTAMP(50 + isE);
    }
    float o[80];
    {
      auto fetch = [&](int s) {
        const int d = 1 + s % 3;
#pragma unroll
        for (int i = 0; i < 4; i++) {
          const int kq = (s / 3 - 1) * 4 + i;
          const uint4 v = ldr4((const uint32_t*)(ps + (hb ^ pgo(0, d) ^ (cgrp(kq & 14) & 4096)) + ((kq & 14) << 16) + (kq & 1) * 2048));
          uint32_t* h = hA + s % 6 * 16 + 4 * i;
          h[0] = v.x; h[1] = v.y; h[2] = v.z; h[3] = v.w;
        }
      };
      unrolled<12>([&](auto I) {
        constexpr int s = I.v, e = s & 7;
        const uint32_t* h = hA + s % 6 * 16;
        const uint64_t dw = mkdesc(sb + w2entry(e), (e & 3) == 3 ? SLOT : 8192, 1024, 1);
        if (s >= 3) {
          for (int it = 0; __any_sync(0xffffffffu, ((h[0] ^ ep) | (h[4] ^ ep) | (h[8] ^ ep) | (h[12] ^ ep)) & lane & 1) && it < 100000; it++) {
            fetch(s);
          }
          if (s == 3 && lead) TSTAMP(26 + isE);
          if (s == 6 && tid == 256) TSTAMP(122);
          if (s == 9 && tid == 256) TSTAMP(123);
        }
        mbar_wait(BAR(B_W2F + e), s >> 3);
        wg_fence();
#pragma unroll
        for (int kk = 0; kk < 4; kk++) wgmma_rs_160_1(o, h[4 * kk], h[4 * kk + 1], h[4 * kk + 2], h[4 * kk + 3], dw + kk * 128, (s | kk) ? 1 : 0);
        wg_commit();
        if (s == 2) {
          mbar_wait(BAR(B_HF + isE * 3), 0);
          fetch(3); fetch(4); fetch(5);
          wg_wait<2>();
          if (lead) mbar_arrive(BAR(B_W2E));
        }
        if (s >= 2 && s < 7) {
          wg_wait<1>();
          if (s < 6 && lead) mbar_arrive(BAR(B_W2E + s - 1));
          if (s == 5 && tid == 256) TSTAMP(120);
          if (s % 3 == 0) {
            mbar_wait(BAR(B_HF + isE * 3 + s / 3), 0);
            if (s == 3 && tid == 256) TSTAMP(118);
            fetch(s + 3); fetch(s + 4); fetch(s + 5);
            if (s == 3 && tid == 256) TSTAMP(119);
          }
        }
      });
      wg_wait<0>();
      regfence<80>(o);
      if (lead) TSTAMP(28 + isE);
    }
    ROLE;
    const float ia = __uint_as_float(lds32(sb + O_ST + rh * 512 + w * 128 + r * 8 + 4)), ib = __uint_as_float(lds32(sb + O_ST + rh * 512 + w * 128 + r * 8 + 68));
    asm volatile("barrier.cluster.wait.aligned;" ::: "memory");
    mbar_wait(BAR(B_X1), 0);
    if (!isE) mbar_wait(BAR(B_W2E + 4), 0);
    const uint32_t reg = sb + (isE ? O_REG : w2entry(4)), stg = reg + (16 * w + (lane & 15)) * 128 + (((lane >> 4) ^ (lane & 7)) << 4);
    const uint32_t stg2 = reg + 16384 + (16 * w + (lane & 15)) * 64 + (((lane >> 4) ^ ((lane >> 1) & 3)) << 4);
    const int row = rb * 128 + rh * 64 + 16 * w, c0 = cg * 160 + (cg & 1) * 32;
#pragma unroll
    for (int u = 0; u < 10; u++) {
      const float2 g0 = lds64f(sb + O_GB + (16 * u + 2 * c) * 4), g1 = lds64f(sb + O_GB + (16 * u + 8 + 2 * c) * 4);
      const float* x = o + 8 * u;
      stsm4(u < 8 ? (stg ^ (u & 3) * 32) + (u >> 2) * 8192 : stg2 ^ (u & 1) * 32, pack2(x[0] * ia * g0.x, x[1] * ia * g0.y), pack2(x[2] * ib * g0.x, x[3] * ib * g0.y),
            pack2(x[4] * ia * g1.x, x[5] * ia * g1.y), pack2(x[6] * ib * g1.x, x[7] * ib * g1.y));
      if ((u & 3) == 3 || u == 9) {
        fence_async_smem();
        __syncwarp();
        if (elect()) {
          if (u < 9) tma2d_add(&p.m_outa, reg + (u >> 2) * 8192 + w * 2048, c0 + (u >> 2) * 64, row);
          else tma2d_add(&p.m_outb, reg + 16384 + w * 1024, cg * 160 + (~cg & 1) * 128, row);
        }
      }
    }
    if (elect()) { bulk_commit(); bulk_wait0_read(); }
    if (tid == 256) TSTAMP(121);
    if (!isE) {
      if (lead) { str(g_sync + Y_EP + b * 32, ep); TSTAMP(31); }
    }
  }
}

#define L2PROMO CU_TENSOR_MAP_L2_PROMOTION_L2_128B
typedef CUresult (*EncodeFn)(CUtensorMap*, CUtensorMapDataType, cuuint32_t, void*, const cuuint64_t*, const cuuint64_t*, const cuuint32_t*,
                             const cuuint32_t*, CUtensorMapInterleave, CUtensorMapSwizzle, CUtensorMapL2promotion, CUtensorMapFloatOOBfill);

void make_map(EncodeFn enc, CUtensorMap* m, const void* ptr, uint64_t inner, uint64_t outer, uint32_t bi, uint32_t bo, CUtensorMapSwizzle sw) {
  cuuint64_t d[2] = {inner, outer};
  cuuint64_t s[1] = {inner * 2};
  cuuint32_t bx[2] = {bi, bo};
  cuuint32_t e[2] = {1, 1};
  enc(m, CU_TENSOR_MAP_DATA_TYPE_BFLOAT16, 2, const_cast<void*>(ptr), d, s, bx, e, CU_TENSOR_MAP_INTERLEAVE_NONE, sw, L2PROMO,
      CU_TENSOR_MAP_FLOAT_OOB_FILL_NONE);
}

void make_map3(EncodeFn enc, CUtensorMap* m, const void* ptr, uint64_t d0, uint64_t d1, uint64_t d2, uint64_t s1, uint64_t s2, uint32_t b0, uint32_t b1, uint32_t b2,
               CUtensorMapSwizzle sw) {
  cuuint64_t d[3] = {d0, d1, d2};
  cuuint64_t s[2] = {s1, s2};
  cuuint32_t bx[3] = {b0, b1, b2};
  cuuint32_t e[3] = {1, 1, 1};
  enc(m, CU_TENSOR_MAP_DATA_TYPE_BFLOAT16, 3, const_cast<void*>(ptr), d, s, bx, e, CU_TENSOR_MAP_INTERLEAVE_NONE, sw, L2PROMO,
      CU_TENSOR_MAP_FLOAT_OOB_FILL_NONE);
}

}

extern "C" void kernel_launch(void* const* d_in, const int* in_sizes, int n_in, void* d_out, int out_size) {
  (void)in_sizes; (void)n_in; (void)out_size;
  void* f = nullptr;
  cudaDriverEntryPointQueryResult qr;
  cudaGetDriverEntryPoint("cuTensorMapEncodeTiled", &f, cudaEnableDefault, &qr);
  EncodeFn enc = (EncodeFn)f;
  void* s;
  cudaGetSymbolAddress(&s, g_s);
  Params p = {};
  uint8_t* ps = (uint8_t*)(((uintptr_t)s + (2 << 20) - 1) & ~(uintptr_t)((2 << 20) - 1));
  make_map3(enc, &p.m_k, d_in[1], D_, S_ / 8, 8, 8 * D_ * 2, D_ * 2, 32, 8, 8, CU_TENSOR_MAP_SWIZZLE_64B);
  make_map3(enc, &p.m_kh, d_in[1], D_, S_ / 8, 8, 8 * D_ * 2, D_ * 2, 32, 8, 3, CU_TENSOR_MAP_SWIZZLE_64B);
  make_map3(enc, &p.m_v, d_in[2], D_, S_ / 8, 8, 8 * D_ * 2, D_ * 2, 32, 8, 8, CU_TENSOR_MAP_SWIZZLE_64B);
  make_map3(enc, &p.m_q, d_in[0], 32, S_, D_ / 32, D_ * 2, 64, 32, 16, D_ / 32, CU_TENSOR_MAP_SWIZZLE_64B);
  make_map(enc, &p.m_wm, d_in[11], 6 * D_, D_, 64, 160, CU_TENSOR_MAP_SWIZZLE_128B);
  make_map3(enc, &p.m_wg, d_in[7], 64, D_, F_ / 64, F_ * 2, 128, 64, 32, 3, CU_TENSOR_MAP_SWIZZLE_128B);
  make_map3(enc, &p.m_wu, d_in[8], 64, D_, F_ / 64, F_ * 2, 128, 64, 32, 3, CU_TENSOR_MAP_SWIZZLE_128B);
  make_map3(enc, &p.m_s, ps, 256, 32, 1024, 512, 16384, 256, 8, 2, CU_TENSOR_MAP_SWIZZLE_NONE);
  make_map(enc, &p.m_w2a, d_in[9], D_, F_, 64, 64, CU_TENSOR_MAP_SWIZZLE_128B);
  make_map3(enc, &p.m_w2b, d_in[9], 32, F_, D_ / 32, D_ * 2, 64, 64, 64, 1, CU_TENSOR_MAP_SWIZZLE_128B);
  make_map(enc, &p.m_outa, d_out, D_, S_, 64, 16, CU_TENSOR_MAP_SWIZZLE_128B);
  make_map(enc, &p.m_outb, d_out, D_, S_, 32, 16, CU_TENSOR_MAP_SWIZZLE_64B);
  p.c = (const __nv_bfloat16*)d_in[10];
  p.wg = (const __nv_bfloat16*)d_in[7];
  p.wu = (const __nv_bfloat16*)d_in[8];
  p.w2 = (const __nv_bfloat16*)d_in[9];
  p.out = (uint8_t*)d_out;
  cudaFuncSetAttribute(fused_kernel, cudaFuncAttributeMaxDynamicSharedMemorySize, SMEM_BYTES);
  fused_kernel<<<128, 384, SMEM_BYTES, cudaStreamPerThread>>>((const __nv_bfloat16*)d_in[1], (const __nv_bfloat16*)d_in[2], (const __nv_bfloat16*)d_in[3],
                                                              (const __nv_bfloat16*)d_in[4], (const __nv_bfloat16*)d_in[5], ps, p);
}
```

```cpp
#include <cuda_runtime.h>
#include <cuda.h>
#include <cuda_bf16.h>
#include <cstdint>

namespace {

constexpr int S_ = 2048, D_ = 640, F_ = 1536;

__device__ __align__(1024) uint8_t g_s[18 << 20];
#define g_sync ((uint32_t*)(ps + (28 << 16)))
#define g_mod ((uint32_t*)(ps + (29 << 16)))
#define g_vv ((uint32_t*)(ps + (30 << 16)))
enum { Y_KV = 0, Y_Y = 20 * 32, Y_MOD = 25 * 32, Y_VV = 31 * 32, Y_CLS = 40 * 32 + 8, Y_EP = 7 };
enum { G_KV = 0, G_Y = 5, G_X = 10, G_M = 15 };
enum { M_X = 0, M_O = 40, M_ST = 512 };
#define TSTAMP(i) do { } while (0)
#define TS3(k, i) do { } while (0)
#define TS2(i) do { } while (0)
#define T_K1 1900
#define T_S0 900
#define T_Q 6950
#define T_K2 2700
#define T_S1 1300
#define T_K3 3900
#define T_WM0 5500
#define T_S2 3500
#define T_K4 4700
#define T_S3 6600
#define D_Q 54
#define D_WM 27
#define NE 2
#define T_S4 8700
#define T_W0 9050
#define T_WM2 9600
#define STEP(ln, kv, gv, cv) (ln | (kv + 1) << 1 | (gv + 1) << 4 | (cv + 1) << 6)
#define SCH 5
#define SCHED_E STEP(0, 0, -1, -1), STEP(0, 1, -1, -1), STEP(0, 2, -1, 1), STEP(0, 4, -1, -1), STEP(1, -1, -1, 3), STEP(0, -1, 1, -1)
#define SCHED_L STEP(0, -1, -1, 0), STEP(0, 3, 0, 2), STEP(0, -1, -1, 4)
#define PFW 0x71u
#define PF2 0xc80u
#define AH 3
#define PD 3
#define ROT 1
#define QD 5
#define PUBD 2
#define NPUB 1
#define LH 13
#define LEAD 2

struct Params {
  CUtensorMap m_k, m_kh, m_v, m_q, m_wm, m_w1, m_w2, m_out;
  const __nv_bfloat16 *c, *wg, *wu, *w2;
  uint8_t* out;
};
constexpr int NLD = 10;
__host__ __device__ constexpr uint32_t nth_load(int n) {
  const uint32_t when[NLD] = {T_K1 << 8 | 1, T_K2 << 8 | 2, T_K3 << 8 | 3, T_K4 << 8 | 4, T_S0 << 8 | 16, T_S1 << 8 | 17, T_S2 << 8 | 18, T_S3 << 8 | 19, T_S4 << 8 | 20,
                              T_Q << 8 | 21};
  for (int i = 0; i < NLD; i++) {
    int rank = 0;
    for (int k = 0; k < NLD; k++) rank += when[k] < when[i];
    if (rank == n) return when[i];
  }
  return 0;
}
__host__ __device__ constexpr uint64_t sched(int g) {
  const uint32_t t[2][8] = {{SCHED_L}, {SCHED_E}};
  uint64_t r = 0;
  for (int i = 0; i < 7; i++) r |= (uint64_t)t[g][i] << 9 * i;
  return r;
}
__host__ __device__ constexpr uint32_t release(int g) {
  uint32_t last[7] = {};
  for (int i = 0; i < 7; i++) {
    const uint32_t t = (sched(g) >> 9 * i) & 511, kv = (t >> 1) & 7, cv = (t >> 6) & 7;
    if (kv) last[kv == 5 ? 2 : kv + 1] = last[kv == 5 ? 3 : kv + 1] = i;
    if (t & 48) last[0] = last[1] = i;
    if (cv) last[cv == 5 ? 1 : cv + 1] = last[6] = i;
  }
  uint32_t r = g ? 7 << 18 : 0;
  for (int i = 0; i < 7; i++) r |= last[i] << 3 * i;
  return r;
}
template <int I> struct IC { static constexpr int v = I; };
template <int N, class F> __device__ __forceinline__ void unrolled(F f) {
  if constexpr (N > 0) { unrolled<N - 1>(f); f(IC<N - 1>()); }
}

constexpr uint32_t SLOT = 32768;
constexpr uint32_t U_RAW = 16, U_ODD = U_RAW + 4160, U_KV = 8448;
constexpr uint32_t O_SILU = SLOT + 8192;
constexpr uint32_t O_REG = 6 * SLOT;
constexpr uint32_t O_Y = O_REG + 20480;
constexpr uint32_t O_BP = O_Y + 4096;
constexpr uint32_t O_MA = O_BP + 4096;
constexpr uint32_t O_ST = O_BP + 7040;
constexpr uint32_t O_CS = O_ST + 1024;
constexpr uint32_t O_GB = O_CS + 640;
constexpr uint32_t O_LN = O_GB + 1280;
constexpr uint32_t O_ROLE = O_LN + 64;
constexpr uint32_t O_SX = O_ROLE + 64;
constexpr uint32_t O_BAR = O_SX + 128;
constexpr uint32_t O_XT = O_BAR + 576;
constexpr uint32_t SMEM_BYTES = O_BAR + 1024;
static_assert(SMEM_BYTES <= 232448, "smem");
enum { B_W2E = 0, B_PL = 3, B_EMPTY = 8, B_LN = 14, B_VV = 15, B_YE = 16, B_FULL = 20, B_W2F = 26, B_HF = 33, B_KIN = 39, B_KV = 44,
       B_QIN = 49, B_WM = 50, B_CS = 51, B_X1 = 52, B_ST = 53, B_ROLE = 55, B_SSM = 56, B_YF = 61, B_PR = 63 };
__device__ __forceinline__ uint32_t kreg(int n) { return n < 4 ? (n + 2) * SLOT + 16384 : 2 * SLOT + 26624; }
__device__ __forceinline__ uint32_t voff(int n) { return n < 4 ? 6144 : SLOT; }
__device__ __forceinline__ uint32_t w2entry(int e) { return e == 6 ? 3 * SLOT + 24576 : e * SLOT; }
__device__ __forceinline__ int ocol(int ro, int i) { i += ROT * ((ro >> 1) & 3); return (ro & 1) * 320 + (i < 5 ? i : i - 5) * 64; }
__device__ __forceinline__ uint32_t bnd(int j) { return j < 4 ? (j + 2) * SLOT : SLOT + 16384; }
__device__ __forceinline__ uint32_t pgo(int rb, int p) { return (rb >> 1) << 21 | p << 13 | ((rb ^ p) & 1) << 12; }
__device__ __forceinline__ uint32_t cgrp(int g) { return g << 16 | ((0x99669966u >> g) & 1) << 12; }
__device__ __forceinline__ uint32_t tile(int rb, int g0, int x) { return pgo(rb, (x & 1) | (x & 2) << 1) ^ cgrp(g0 + (x >> 2)); }

__device__ __forceinline__ uint32_t smem_u32(const void* p) { return (uint32_t)__cvta_generic_to_shared(p); }
__device__ __forceinline__ void mbar_init(uint32_t bar, uint32_t cnt) { asm volatile("mbarrier.init.shared::cta.b64 [%0], %1;" ::"r"(bar), "r"(cnt) : "memory"); }
__device__ __forceinline__ void mbar_expect(uint32_t bar, uint32_t bytes) { asm volatile("mbarrier.arrive.expect_tx.shared::cta.b64 _, [%0], %1;" ::"r"(bar), "r"(bytes) : "memory"); }
__device__ __forceinline__ void mbar_arrive(uint32_t bar) { asm volatile("mbarrier.arrive.shared::cta.b64 _, [%0];" ::"r"(bar) : "memory"); }
__device__ __forceinline__ void mbar_wait(uint32_t bar, uint32_t parity) {
  asm volatile("{\n .reg .pred p;\n .reg .u32 c;\n mov.u32 c, 0;\n LOOP:\n mbarrier.try_wait.parity.shared::cta.b64 p, [%0], %1;\n @p bra DONE;\n add.u32 c, c, 1;\n setp.lt.u32 p, c, 200000;\n @p bra LOOP;\n DONE:\n }" ::"r"(bar), "r"(parity) : "memory");
}
__device__ __forceinline__ void mbar_wait_cluster(uint32_t bar, uint32_t parity) {
  asm volatile("{\n .reg .pred p;\n .reg .u32 c;\n mov.u32 c, 0;\n LOOP:\n mbarrier.try_wait.parity.acquire.cluster.shared::cta.b64 p, [%0], %1;\n @p bra DONE;\n add.u32 c, c, 1;\n setp.lt.u32 p, c, 200000;\n @p bra LOOP;\n DONE:\n }" ::"r"(bar), "r"(parity) : "memory");
}
__device__ __forceinline__ bool mbar_test(uint32_t bar, uint32_t parity) {
  uint32_t r;
  asm volatile("{ .reg .pred p; mbarrier.test_wait.parity.shared::cta.b64 p, [%1], %2; selp.u32 %0, 1, 0, p; }" : "=r"(r) : "r"(bar), "r"(parity) : "memory");
  return r;
}
__device__ __forceinline__ uint32_t mapa(uint32_t a, uint32_t cta) { uint32_t r; asm("mapa.shared::cluster.u32 %0, %1, %2;" : "=r"(r) : "r"(a), "r"(cta)); return r; }
__device__ __forceinline__ void mbar_arrive_cl(uint32_t bar) { asm volatile("mbarrier.arrive.shared::cluster.b64 _, [%0];" ::"r"(bar) : "memory"); }
__device__ __forceinline__ bool elect() { uint32_t p; asm volatile("{ .reg .pred q; elect.sync _|q, 0xffffffff; selp.u32 %0, 1, 0, q; }" : "=r"(p)); return p; }
__device__ __forceinline__ uint32_t clk() { uint32_t c; asm volatile("mov.u32 %0, %%clock;" : "=r"(c)); return c; }
__device__ __forceinline__ uint32_t ldr(const uint32_t* p) { uint32_t v; asm volatile("ld.relaxed.gpu.global.u32 %0, [%1];" : "=r"(v) : "l"(p) : "memory"); return v; }
__device__ __forceinline__ uint4 ldr4(const uint32_t* p) {
  uint4 v; asm volatile("ld.relaxed.gpu.global.v4.u32 {%0,%1,%2,%3}, [%4];" : "=r"(v.x), "=r"(v.y), "=r"(v.z), "=r"(v.w) : "l"(p) : "memory"); return v;
}
__device__ __forceinline__ void poll_ge(const uint32_t* p, uint32_t target) {
  asm volatile("{\n .reg .pred p;\n .reg .u32 c, v;\n mov.u32 c, 0;\n LOOP:\n ld.relaxed.gpu.global.u32 v, [%0];\n sub.u32 v, v, %1;\n setp.ge.s32 p, v, 0;\n @p bra DONE;\n add.u32 c, c, 1;\n setp.lt.u32 p, c, 100000;\n @p bra LOOP;\n DONE:\n }" ::"l"(p), "r"(target) : "memory");
}
__device__ __forceinline__ void poll_lane(uint32_t& v, const void* p, uint32_t target, int l) {
  for (int it = 0; !((__ballot_sync(0xffffffffu, (int)(v - target) >= 0) >> l) & 1) && it < 100000; it++) v = ldr((const uint32_t*)p);
}
__device__ __forceinline__ void hint_add(uint32_t* p) { asm volatile("red.relaxed.gpu.global.add.u32 [%0], 1;" ::"l"(p) : "memory"); }
__device__ __forceinline__ void refetch(const void* g, uint32_t off, uint32_t a, uint32_t tag) {
  asm volatile("{\n .reg .pred p;\n .reg .u32 c, v, x, y, z;\n .reg .u64 q;\n mov.u32 c, 0;\n cvt.u64.u32 q, %1;\n add.u64 q, q, %0;\n"
               " LOOP:\n ld.relaxed.gpu.global.u32 v, [q];\n xor.b32 v, v, %3;\n and.b32 v, v, 1;\n setp.eq.u32 p, v, 0;\n @p bra DONE;\n add.u32 c, c, 1;\n setp.lt.u32 p, c, 100000;\n @p bra LOOP;\n"
               " DONE:\n ld.relaxed.gpu.global.v4.u32 {v, x, y, z}, [%0];\n st.shared.v4.u32 [%2], {v, x, y, z};\n ld.relaxed.gpu.global.v4.u32 {v, x, y, z}, [%0+16];\n xor.b32 c, %2, 16;\n"
               " st.shared.v4.u32 [c], {v, x, y, z};\n fence.proxy.async.shared::cta;\n }" ::"l"(g), "r"(off), "r"(a), "r"(tag) : "memory");
}
__device__ __forceinline__ void refetch16(const void* g, uint32_t a, uint32_t tag) {
  asm volatile("{\n .reg .pred p;\n .reg .u32 c, t, v, x, y, z;\n mov.u32 c, 0;\n"
               " LOOP:\n ld.relaxed.gpu.global.v4.u32 {v, x, y, z}, [%0];\n xor.b32 t, v, %2;\n and.b32 t, t, 1;\n setp.eq.u32 p, t, 0;\n @p bra DONE;\n add.u32 c, c, 1;\n setp.lt.u32 p, c, 100000;\n @p bra LOOP;\n"
               " DONE:\n st.shared.v4.u32 [%1], {v, x, y, z};\n }" ::"l"(g), "r"(a), "r"(tag) : "memory");
}
__device__ __forceinline__ uint2 ldr2(const uint32_t* p) {
  uint2 v; asm volatile("ld.relaxed.gpu.global.v2.u32 {%0,%1}, [%2];" : "=r"(v.x), "=r"(v.y) : "l"(p) : "memory"); return v;
}
__device__ __forceinline__ uint32_t settag(uint32_t x, uint32_t m, uint32_t t) { return (x & ~m) | (t & m); }
__device__ __forceinline__ void stg128(void* p, uint32_t x, uint32_t y, uint32_t z, uint32_t w) {
  asm volatile("st.global.v4.u32 [%0], {%1,%2,%3,%4};" ::"l"(p), "r"(x), "r"(y), "r"(z), "r"(w) : "memory");
}
__device__ __forceinline__ void cpa16(uint32_t dst, const void* src, uint32_t n) { asm volatile("cp.async.cg.shared.global [%0], [%1], 16, %2;" ::"r"(dst), "l"(src), "r"(n) : "memory"); }
__device__ __forceinline__ void tma3d(uint32_t dst, const CUtensorMap* m, int x, int y, int z, uint32_t bar) {
  asm volatile("cp.async.bulk.tensor.3d.shared::cluster.global.mbarrier::complete_tx::bytes [%0], [%1, {%3, %4, %5}], [%2];" ::"r"(dst), "l"(m), "r"(bar), "r"(x), "r"(y), "r"(z) : "memory");
}
__device__ __forceinline__ void tma4d(uint32_t dst, const CUtensorMap* m, int x, int y, int z, int u, uint32_t bar) {
  asm volatile("cp.async.bulk.tensor.4d.shared::cluster.global.mbarrier::complete_tx::bytes [%0], [%1, {%3, %4, %5, %6}], [%2];" ::"r"(dst), "l"(m), "r"(bar), "r"(x), "r"(y), "r"(z), "r"(u) : "memory");
}
__device__ __forceinline__ void bulk_st(void* dst, uint32_t src, uint32_t bytes) {
  asm volatile("cp.async.bulk.global.shared::cta.bulk_group [%0], [%1], %2;" ::"l"(dst), "r"(src), "r"(bytes) : "memory");
}
__device__ __forceinline__ void bulk_pf(const void* src, uint32_t bytes) { asm volatile("cp.async.bulk.prefetch.L2.global [%0], %1;" ::"l"(src), "r"(bytes) : "memory"); }
__device__ __forceinline__ void tma2d(uint32_t dst, const CUtensorMap* m, int x, int y, uint32_t bar) {
  asm volatile("cp.async.bulk.tensor.2d.shared::cluster.global.mbarrier::complete_tx::bytes [%0], [%1, {%3, %4}], [%2];" ::"r"(dst), "l"(m), "r"(bar), "r"(x), "r"(y) : "memory");
}
__device__ __forceinline__ void tma2d_add(const CUtensorMap* m, uint32_t src, int x, int y) {
  asm volatile("cp.reduce.async.bulk.tensor.2d.global.shared::cta.add.tile.bulk_group [%0, {%2, %3}], [%1];" ::"l"(m), "r"(src), "r"(x), "r"(y) : "memory");
}
__device__ __forceinline__ void bulk_ld(uint32_t dst, const void* src, uint32_t bytes, uint32_t bar) {
  asm volatile("cp.async.bulk.shared::cluster.global.mbarrier::complete_tx::bytes [%0], [%1], %2, [%3];" ::"r"(dst), "l"(src), "r"(bytes), "r"(bar) : "memory");
}
__device__ __forceinline__ void bulk_commit() { asm volatile("cp.async.bulk.commit_group;" ::: "memory"); }
template <int N> __device__ __forceinline__ void bulk_wait() { asm volatile("cp.async.bulk.wait_group %0;" ::"n"(N) : "memory"); }
template <int N> __device__ __forceinline__ void bulk_wait_read() { asm volatile("cp.async.bulk.wait_group.read %0;" ::"n"(N) : "memory"); }
__device__ __forceinline__ void fence_async_smem() { asm volatile("fence.proxy.async.shared::cta;" ::: "memory"); }
__device__ __forceinline__ void bar_sync(int id, int n) { asm volatile("bar.sync %0, %1;" ::"r"(id), "r"(n) : "memory"); }
__device__ __forceinline__ void bar_arrive(int id, int n) { asm volatile("bar.arrive %0, %1;" ::"r"(id), "r"(n) : "memory"); }
__device__ __forceinline__ void wg_fence() { asm volatile("wgmma.fence.sync.aligned;" ::: "memory"); }
__device__ __forceinline__ void wg_commit() { asm volatile("wgmma.commit_group.sync.aligned;" ::: "memory"); }
template <int N> __device__ __forceinline__ void wg_wait() { asm volatile("wgmma.wait_group.sync.aligned %0;" ::"n"(N) : "memory"); }
__device__ __forceinline__ void ldsm4(uint32_t a, uint32_t& r0, uint32_t& r1, uint32_t& r2, uint32_t& r3) {
  asm volatile("ldmatrix.sync.aligned.m8n8.x4.shared.b16 {%0,%1,%2,%3}, [%4];" : "=r"(r0), "=r"(r1), "=r"(r2), "=r"(r3) : "r"(a) : "memory");
}
__device__ __forceinline__ void ldsm4t(uint32_t a, uint32_t& r0, uint32_t& r1, uint32_t& r2, uint32_t& r3) {
  asm volatile("ldmatrix.sync.aligned.m8n8.x4.trans.shared.b16 {%0,%1,%2,%3}, [%4];" : "=r"(r0), "=r"(r1), "=r"(r2), "=r"(r3) : "r"(a) : "memory");
}
__device__ __forceinline__ void stsm4t(uint32_t a, uint32_t r0, uint32_t r1, uint32_t r2, uint32_t r3) {
  asm volatile("stmatrix.sync.aligned.m8n8.x4.trans.shared.b16 [%0], {%1,%2,%3,%4};" ::"r"(a), "r"(r0), "r"(r1), "r"(r2), "r"(r3) : "memory");
}
__device__ __forceinline__ void stsm4(uint32_t a, uint32_t r0, uint32_t r1, uint32_t r2, uint32_t r3) {
  asm volatile("stmatrix.sync.aligned.m8n8.x4.shared.b16 [%0], {%1,%2,%3,%4};" ::"r"(a), "r"(r0), "r"(r1), "r"(r2), "r"(r3) : "memory");
}
__device__ __forceinline__ uint32_t lds32(uint32_t a) { uint32_t v; asm volatile("ld.shared.u32 %0, [%1];" : "=r"(v) : "r"(a) : "memory"); return v; }
__device__ __forceinline__ uint4 lds128(uint32_t a) { uint4 v; asm volatile("ld.shared.v4.u32 {%0,%1,%2,%3}, [%4];" : "=r"(v.x), "=r"(v.y), "=r"(v.z), "=r"(v.w) : "r"(a) : "memory"); return v; }
__device__ __forceinline__ float4 lds128f(uint32_t a) { float4 v; asm volatile("ld.shared.v4.f32 {%0,%1,%2,%3}, [%4];" : "=f"(v.x), "=f"(v.y), "=f"(v.z), "=f"(v.w) : "r"(a) : "memory"); return v; }
__device__ __forceinline__ float2 lds64f(uint32_t a) { float2 v; asm volatile("ld.shared.v2.f32 {%0,%1}, [%2];" : "=f"(v.x), "=f"(v.y) : "r"(a) : "memory"); return v; }
__device__ __forceinline__ void sts32(uint32_t a, uint32_t v) { asm volatile("st.shared.u32 [%0], %1;" ::"r"(a), "r"(v) : "memory"); }
__device__ __forceinline__ void sts64(uint32_t a, uint32_t x, uint32_t y) { asm volatile("st.shared.v2.u32 [%0], {%1,%2};" ::"r"(a), "r"(x), "r"(y) : "memory"); }
__device__ __forceinline__ void sts128(uint32_t a, uint32_t x, uint32_t y, uint32_t z, uint32_t w) { asm volatile("st.shared.v4.u32 [%0], {%1,%2,%3,%4};" ::"r"(a), "r"(x), "r"(y), "r"(z), "r"(w) : "memory"); }
__device__ __forceinline__ void sts16(uint32_t a, uint16_t v) { asm volatile("st.shared.u16 [%0], %1;" ::"r"(a), "h"(v) : "memory"); }
__device__ __forceinline__ uint32_t prmt(uint32_t a, uint32_t b, uint32_t s) { uint32_t r; asm("prmt.b32 %0, %1, %2, %3;" : "=r"(r) : "r"(a), "r"(b), "r"(s)); return r; }
__device__ __forceinline__ uint32_t hfma2(uint32_t a, uint32_t b, uint32_t c) { uint32_t r; asm("fma.rn.bf16x2 %0, %1, %2, %3;" : "=r"(r) : "r"(a), "r"(b), "r"(c)); return r; }
__device__ __forceinline__ uint32_t hfma2lh(uint32_t a, uint32_t l) {
  uint32_t r;
  asm("{ .reg .b16 x, y; .reg .b32 u, v; mov.b32 {x, y}, %2; mov.b32 u, {x, x}; mov.b32 v, {y, y}; fma.rn.bf16x2 %0, %1, u, v; }" : "=r"(r) : "r"(a), "r"(l));
  return r;
}
__device__ __forceinline__ uint32_t addu(uint32_t a, uint32_t u) { uint32_t r; asm("add.u32 %0, %1, %2;" : "=r"(r) : "r"(a), "r"(u)); return r; }
__device__ __forceinline__ uint32_t tag0(uint32_t x, uint32_t t) { uint32_t r; asm("lop3.b32 %0, %1, 1, %2, 0xb8;" : "=r"(r) : "r"(x), "r"(t)); return r; }
__device__ __forceinline__ void keep(uint32_t& x) { x = __shfl_xor_sync(0xffffffffu, x, 0); }
__device__ __forceinline__ uint32_t hmul2(uint32_t a, uint32_t b) { uint32_t r; asm("mul.rn.bf16x2 %0, %1, %2;" : "=r"(r) : "r"(a), "r"(b)); return r; }
__device__ __forceinline__ uint32_t pack2(float lo, float hi) { uint32_t r; asm("cvt.rn.bf16x2.f32 %0, %1, %2;" : "=r"(r) : "f"(hi), "f"(lo)); return r; }
__device__ __forceinline__ float blo(uint32_t v) { return __uint_as_float(v << 16); }
__device__ __forceinline__ float bhi(uint32_t v) { return __uint_as_float(v & 0xffff0000u); }
__device__ __forceinline__ uint32_t hadd2(uint32_t a, uint32_t b) { uint32_t r; asm("add.rn.bf16x2 %0, %1, %2;" : "=r"(r) : "r"(a), "r"(b)); return r; }
__device__ __forceinline__ void str(uint32_t* p, uint32_t v) { asm volatile("st.relaxed.gpu.global.u32 [%0], %1;" ::"l"(p), "r"(v) : "memory"); }
__device__ __forceinline__ uint32_t tagf(float x, uint32_t tag) { return (__float_as_uint(x) & ~3u) | (tag & 3); }
template <int N> __device__ __forceinline__ float4 gather4(const uint32_t* p, int stride, uint32_t tag) {
  uint4 v[N];
  int it = 0;
  uint32_t bad;
  do {
#pragma unroll
    for (int i = 0; i < N; i++) v[i] = ldr4(p + i * stride);
    bad = 0;
#pragma unroll
    for (int i = 0; i < N; i++) bad |= (v[i].x ^ tag) | (v[i].y ^ tag) | (v[i].z ^ tag) | (v[i].w ^ tag);
  } while ((bad & 3) && ++it < 100000);
  float4 s = make_float4(__uint_as_float(v[0].x), __uint_as_float(v[0].y), __uint_as_float(v[0].z), __uint_as_float(v[0].w));
#pragma unroll
  for (int i = 1; i < N; i++) { s.x += __uint_as_float(v[i].x); s.y += __uint_as_float(v[i].y); s.z += __uint_as_float(v[i].z); s.w += __uint_as_float(v[i].w); }
  return s;
}
__device__ __forceinline__ float rbf(float x) { return blo(pack2(x, 0.f)); }
__device__ __forceinline__ uint64_t mkdesc(uint32_t addr, uint32_t lbo, uint32_t sbo, uint32_t swz) {
  return (uint64_t)((addr & 0x3FFFF) >> 4) | ((uint64_t)(lbo >> 4) << 16) | ((uint64_t)(sbo >> 4) << 32) | ((uint64_t)swz << 62);
}
template <int N> __device__ __forceinline__ void regfence(float* d) {
#pragma unroll
  for (int i = 0; i < N; i++) asm volatile("" : "+f"(d[i])::"memory");
}

__device__ __forceinline__ void wgmma_rs_32_0(float* d, uint32_t a0, uint32_t a1, uint32_t a2, uint32_t a3, uint64_t db, int sd) {
  asm volatile("{ .reg .pred p; setp.ne.b32 p, %21, 0; wgmma.mma_async.sync.aligned.m64n32k16.f32.bf16.bf16 {%0,%1,%2,%3,%4,%5,%6,%7,%8,%9,%10,%11,%12,%13,%14,%15}, {%16,%17,%18,%19}, %20, p, 1, 1, 0; }"
   : "+f"(d[0]), "+f"(d[1]), "+f"(d[2]), "+f"(d[3]), "+f"(d[4]), "+f"(d[5]), "+f"(d[6]), "+f"(d[7]), "+f"(d[8]), "+f"(d[9]), "+f"(d[10]), "+f"(d[11]), "+f"(d[12]), "+f"(d[13]), "+f"(d[14]), "+f"(d[15]) : "r"(a0), "r"(a1), "r"(a2), "r"(a3), "l"(db), "r"(sd));
}
__device__ __forceinline__ void wgmma_rs_64_1(float* d, uint32_t a0, uint32_t a1, uint32_t a2, uint32_t a3, uint64_t db, int sd) {
  asm volatile("{ .reg .pred p; setp.ne.b32 p, %37, 0; wgmma.mma_async.sync.aligned.m64n64k16.f32.bf16.bf16 {%0,%1,%2,%3,%4,%5,%6,%7,%8,%9,%10,%11,%12,%13,%14,%15,%16,%17,%18,%19,%20,%21,%22,%23,%24,%25,%26,%27,%28,%29,%30,%31}, {%32,%33,%34,%35}, %36, p, 1, 1, 1; }"
   : "+f"(d[0]), "+f"(d[1]), "+f"(d[2]), "+f"(d[3]), "+f"(d[4]), "+f"(d[5]), "+f"(d[6]), "+f"(d[7]), "+f"(d[8]), "+f"(d[9]), "+f"(d[10]), "+f"(d[11]), "+f"(d[12]), "+f"(d[13]), "+f"(d[14]), "+f"(d[15]), "+f"(d[16]), "+f"(d[17]), "+f"(d[18]), "+f"(d[19]), "+f"(d[20]), "+f"(d[21]), "+f"(d[22]), "+f"(d[23]), "+f"(d[24]), "+f"(d[25]), "+f"(d[26]), "+f"(d[27]), "+f"(d[28]), "+f"(d[29]), "+f"(d[30]), "+f"(d[31]) : "r"(a0), "r"(a1), "r"(a2), "r"(a3), "l"(db), "r"(sd));
}
__device__ __forceinline__ void wgmma_rs_192_0(float* d, uint32_t a0, uint32_t a1, uint32_t a2, uint32_t a3, uint64_t db, int sd) {
  asm volatile("{ .reg .pred p; setp.ne.b32 p, %101, 0; wgmma.mma_async.sync.aligned.m64n192k16.f32.bf16.bf16 {%0,%1,%2,%3,%4,%5,%6,%7,%8,%9,%10,%11,%12,%13,%14,%15,%16,%17,%18,%19,%20,%21,%22,%23,%24,%25,%26,%27,%28,%29,%30,%31,%32,%33,%34,%35,%36,%37,%38,%39,%40,%41,%42,%43,%44,%45,%46,%47,%48,%49,%50,%51,%52,%53,%54,%55,%56,%57,%58,%59,%60,%61,%62,%63,%64,%65,%66,%67,%68,%69,%70,%71,%72,%73,%74,%75,%76,%77,%78,%79,%80,%81,%82,%83,%84,%85,%86,%87,%88,%89,%90,%91,%92,%93,%94,%95}, {%96,%97,%98,%99}, %100, p, 1, 1, 0; }"
   : "+f"(d[0]), "+f"(d[1]), "+f"(d[2]), "+f"(d[3]), "+f"(d[4]), "+f"(d[5]), "+f"(d[6]), "+f"(d[7]), "+f"(d[8]), "+f"(d[9]), "+f"(d[10]), "+f"(d[11]), "+f"(d[12]), "+f"(d[13]), "+f"(d[14]), "+f"(d[15]), "+f"(d[16]), "+f"(d[17]), "+f"(d[18]), "+f"(d[19]), "+f"(d[20]), "+f"(d[21]), "+f"(d[22]), "+f"(d[23]), "+f"(d[24]), "+f"(d[25]), "+f"(d[26]), "+f"(d[27]), "+f"(d[28]), "+f"(d[29]), "+f"(d[30]), "+f"(d[31]), "+f"(d[32]), "+f"(d[33]), "+f"(d[34]), "+f"(d[35]), "+f"(d[36]), "+f"(d[37]), "+f"(d[38]), "+f"(d[39]), "+f"(d[40]), "+f"(d[41]), "+f"(d[42]), "+f"(d[43]), "+f"(d[44]), "+f"(d[45]), "+f"(d[46]), "+f"(d[47]), "+f"(d[48]), "+f"(d[49]), "+f"(d[50]), "+f"(d[51]), "+f"(d[52]), "+f"(d[53]), "+f"(d[54]), "+f"(d[55]), "+f"(d[56]), "+f"(d[57]), "+f"(d[58]), "+f"(d[59]), "+f"(d[60]), "+f"(d[61]), "+f"(d[62]), "+f"(d[63]), "+f"(d[64]), "+f"(d[65]), "+f"(d[66]), "+f"(d[67]), "+f"(d[68]), "+f"(d[69]), "+f"(d[70]), "+f"(d[71]), "+f"(d[72]), "+f"(d[73]), "+f"(d[74]), "+f"(d[75]), "+f"(d[76]), "+f"(d[77]), "+f"(d[78]), "+f"(d[79]), "+f"(d[80]), "+f"(d[81]), "+f"(d[82]), "+f"(d[83]), "+f"(d[84]), "+f"(d[85]), "+f"(d[86]), "+f"(d[87]), "+f"(d[88]), "+f"(d[89]), "+f"(d[90]), "+f"(d[91]), "+f"(d[92]), "+f"(d[93]), "+f"(d[94]), "+f"(d[95]) : "r"(a0), "r"(a1), "r"(a2), "r"(a3), "l"(db), "r"(sd));
}
__device__ __forceinline__ void wgmma_ss_8_10(float* d, uint64_t da, uint64_t db, int sd) {
  asm volatile("{ .reg .pred p; setp.ne.b32 p, %6, 0; wgmma.mma_async.sync.aligned.m64n8k16.f32.bf16.bf16 {%0,%1,%2,%3}, %4, %5, p, 1, 1, 1, 0; }"
   : "+f"(d[0]), "+f"(d[1]), "+f"(d[2]), "+f"(d[3]) : "l"(da), "l"(db), "r"(sd));
}
__device__ __forceinline__ void wgmma_ss_192_01(float* d, uint64_t da, uint64_t db, int sd) {
  asm volatile("{ .reg .pred p; setp.ne.b32 p, %98, 0; wgmma.mma_async.sync.aligned.m64n192k16.f32.bf16.bf16 {%0,%1,%2,%3,%4,%5,%6,%7,%8,%9,%10,%11,%12,%13,%14,%15,%16,%17,%18,%19,%20,%21,%22,%23,%24,%25,%26,%27,%28,%29,%30,%31,%32,%33,%34,%35,%36,%37,%38,%39,%40,%41,%42,%43,%44,%45,%46,%47,%48,%49,%50,%51,%52,%53,%54,%55,%56,%57,%58,%59,%60,%61,%62,%63,%64,%65,%66,%67,%68,%69,%70,%71,%72,%73,%74,%75,%76,%77,%78,%79,%80,%81,%82,%83,%84,%85,%86,%87,%88,%89,%90,%91,%92,%93,%94,%95}, %96, %97, p, 1, 1, 0, 1; }"
   : "+f"(d[0]), "+f"(d[1]), "+f"(d[2]), "+f"(d[3]), "+f"(d[4]), "+f"(d[5]), "+f"(d[6]), "+f"(d[7]), "+f"(d[8]), "+f"(d[9]), "+f"(d[10]), "+f"(d[11]), "+f"(d[12]), "+f"(d[13]), "+f"(d[14]), "+f"(d[15]), "+f"(d[16]), "+f"(d[17]), "+f"(d[18]), "+f"(d[19]), "+f"(d[20]), "+f"(d[21]), "+f"(d[22]), "+f"(d[23]), "+f"(d[24]), "+f"(d[25]), "+f"(d[26]), "+f"(d[27]), "+f"(d[28]), "+f"(d[29]), "+f"(d[30]), "+f"(d[31]), "+f"(d[32]), "+f"(d[33]), "+f"(d[34]), "+f"(d[35]), "+f"(d[36]), "+f"(d[37]), "+f"(d[38]), "+f"(d[39]), "+f"(d[40]), "+f"(d[41]), "+f"(d[42]), "+f"(d[43]), "+f"(d[44]), "+f"(d[45]), "+f"(d[46]), "+f"(d[47]), "+f"(d[48]), "+f"(d[49]), "+f"(d[50]), "+f"(d[51]), "+f"(d[52]), "+f"(d[53]), "+f"(d[54]), "+f"(d[55]), "+f"(d[56]), "+f"(d[57]), "+f"(d[58]), "+f"(d[59]), "+f"(d[60]), "+f"(d[61]), "+f"(d[62]), "+f"(d[63]), "+f"(d[64]), "+f"(d[65]), "+f"(d[66]), "+f"(d[67]), "+f"(d[68]), "+f"(d[69]), "+f"(d[70]), "+f"(d[71]), "+f"(d[72]), "+f"(d[73]), "+f"(d[74]), "+f"(d[75]), "+f"(d[76]), "+f"(d[77]), "+f"(d[78]), "+f"(d[79]), "+f"(d[80]), "+f"(d[81]), "+f"(d[82]), "+f"(d[83]), "+f"(d[84]), "+f"(d[85]), "+f"(d[86]), "+f"(d[87]), "+f"(d[88]), "+f"(d[89]), "+f"(d[90]), "+f"(d[91]), "+f"(d[92]), "+f"(d[93]), "+f"(d[94]), "+f"(d[95]) : "l"(da), "l"(db), "r"(sd));
}

#define HINT(x) x

__global__ void __cluster_dims__(2, 1, 1) __launch_bounds__(384, 1) fused_kernel(const __nv_bfloat16* __restrict__ pk, const __nv_bfloat16* __restrict__ pv,
    const __nv_bfloat16* __restrict__ pshift, const __nv_bfloat16* __restrict__ pssm, const __nv_bfloat16* __restrict__ pD, uint8_t* ps, const __grid_constant__ Params p) {
  extern __shared__ __align__(1024) uint8_t smem_raw[];
  const uint32_t t_start = clk();
  const uint32_t sb = smem_u32(smem_raw);
  const uint32_t bars = sb + O_BAR;
  const int tid = threadIdx.x, lane = tid & 31;
  const int warp = __shfl_sync(0xffffffffu, tid >> 5, 0);
  const int b = blockIdx.x, kh = b & 1;
  const int part = b / 20;
  auto BAR = [&](int i) { return bars + 8 * i; };
#define ROLE ROLE_(lds32(sb + O_ROLE))
#define ROLEU ROLE_(__shfl_sync(0xffffffffu, lds32(sb + O_ROLE), 0))
#define ROLE_(x) const int ro = x, rb = ro >> 3, fs = ro & 7, vr = min(rb, 14) / 3, vt = min(rb, 14) % 3; \
  const uint32_t ord = vr == 3 ? 0x42310 : vr == 4 ? 0x32410 : 0x43210; uint8_t* const misc = ps + (pgo(rb, 0) ^ cgrp(G_M)); \
  (void)fs; (void)vt; (void)ord; (void)misc
  if (tid == 0) TSTAMP(63);
#define EPLOAD const uint32_t e0 = ldr(g_sync + Y_EP + b * 32 + (lane & (uint32_t)(uintptr_t)ps))
#define EPOCH const uint32_t ep = __shfl_sync(0xffffffffu, e0, 0) + 1
#define EPOCHU const uint32_t ep = __shfl_sync(0xffffffffu, lds32(sb + O_ROLE + 4), 0)

  if (warp < 4) {
    asm volatile("setmaxnreg.dec.sync.aligned.u32 40;");
    const int hw = warp - 2;
    if (warp == 0) {
      EPLOAD;
      const int u = b >> 1, cls = u < 4 ? 4 + u : u < 36 ? (u - 4) >> 3 : 4 + (u - 36) / 7, pos = u < 4 ? 7 : u < 36 ? (u - 4) & 7 : (u - 36) % 7;
      const uint32_t pa = (pgo(2 * cls, 7) ^ cgrp(G_M)) + pos * 128;
      if (!kh && lane < 4) stg128(ps + (pa ^ (lane & 2) << 11) + (lane & 1) * 16, 0, 0, 0, 0);
      bar_sync(1, 384);
      asm volatile("barrier.cluster.arrive.relaxed.aligned;" ::: "memory");
      uint32_t far = 0;
      if (!kh && lane == 0) {
        uint32_t x, y;
        TSTAMP(113);
        asm volatile("atom.relaxed.gpu.global.exch.b32 %0, [%2], 0;\n atom.relaxed.gpu.global.exch.b32 %1, [%3], 0;" : "=r"(x), "=r"(y) : "l"(ps + pa), "l"(ps + (pa ^ 4096)) : "memory");
        asm volatile("{ .reg .pred p; setp.ne.u32 p, %0, 0; @p trap; mov.u32 %0, %%clock; }" : "+r"(x)::"memory");
        asm volatile("{ .reg .pred p; setp.ne.u32 p, %0, 0; @p trap; mov.u32 %0, %%clock; }" : "+r"(y)::"memory");
        far = y - x;
        TSTAMP(11);
      }
      EPOCH;
      if (lane == 0) TSTAMP(114);
      {
        uint32_t* f = g_sync + Y_CLS + cls * 32;
        if (!kh && lane == 0) str(f + pos, ep << 4 | (far < 100) << 3 | pos);
        uint32_t v;
        int it = 0;
        do v = ldr(f + (lane & 7)); while (__any_sync(0xffffffffu, (v ^ ep << 4) > 15) && ++it < 100000);
        const uint32_t rank = __popc(__ballot_sync(0xffffffffu, v < __shfl_sync(0xffffffffu, v, pos)) & 255);
        if (lane == 0) sts64(sb + O_ROLE, cls * 16 + rank * 2 + kh, ep);
        if (lane == 0) { mbar_arrive(BAR(B_ROLE)); TSTAMP(0); }
        __syncwarp();
      }
      ROLEU;
      {
        const uint32_t* f = g_sync + Y_KV + (min(lane, 4) * 4 + (b >> 5)) * 32;
        const uint32_t tw = lane != 5 ? T_W0 : b * D_WM + (part < NE ? T_WM0 : T_WM2 - 20 * NE * D_WM);
        uint32_t pend = b < 120 ? 127 : 95;
        int it = 0;
        do {
          uint32_t v = ep * 32;
          HINT(if (lane < 5) v = ldr(f));
          uint32_t m = __ballot_sync(0xffffffffu, (lane < 5 ? (int)(v - ep * 32) >= 0 : clk() - t_start >= tw) || ++it > 100000) & pend;
          pend &= ~m;
          for (; m; m &= m - 1) {
            const int j = __ffs(m) - 1;
            if (elect()) {
              if (j < 5) {
                TSTAMP(2 + j);
                mbar_expect(BAR(B_KV + j), 4096);
                bulk_ld(sb + bnd(j) + U_KV, ps + (pgo(b >> 3, b & 7) ^ cgrp(G_KV + j)), 4096, BAR(B_KV + j));
              } else if (j == 5) {
                const int x = b % 20, col = part < 5 ? (x >> 2) * D_ + part * 128 + (x & 3) * 32 : 5 * D_ + x * 32;
                mbar_expect(BAR(B_WM), 40960);
                tma3d(sb, &p.m_wm, col, 0, 0, BAR(B_WM));
                TSTAMP(106 + (part >= NE));
              } else {
                bulk_pf((kh ? p.wu : p.wg) + (b >> 1) * 2 * F_, 6144);
                TSTAMP(108);
              }
            }
          }
        } while (pend);
      }
      {
        const int rl = (ord >> (min(lane, 19) & 28)) & 7;
        const uint32_t* const cnt = (const uint32_t*)(misc + M_X) + rl * 2 + ((min(lane, 19) >> 1) & 1);
        sts32(sb + O_XT + lane * 4, tile(rb, G_X, rl * 4 + (lane & 3)));
        __syncwarp();
        uint32_t known = 0;
        int slot = 2;
#pragma unroll 1
        for (int i = -AH; i < 20; i++) {
          const int s = i < 0 ? i + AH : i, rd = (ord >> (s & 28)) & 7;
          const uint32_t dst = sb + slot * SLOT, full = BAR(B_FULL + slot);
          const uint8_t* const xs = ps + (tile(rb, G_X, rd * 4 + (s & 3)) + kh * 16384);
          auto loadx = [&]() {
            asm volatile("{ .reg .pred p; elect.sync _|p, 0xffffffff;\n @p cp.async.bulk.shared::cluster.global.mbarrier::complete_tx::bytes.multicast::cluster [%0], [%1], 4096, [%2], %3; }"
                         ::"r"(dst + 24576 + kh * 4096), "l"(xs), "r"(full), "h"((uint16_t)3) : "memory");
          };
          auto loadw = [&]() {
            mbar_wait(full + 8 * (B_EMPTY - B_FULL), (0xfc0f0 >> s) & 1);
            asm volatile("{ .reg .pred p; elect.sync _|p, 0xffffffff;\n @p mbarrier.arrive.expect_tx.shared::cta.b64 _, [%2], 32768;\n"
                         " @p cp.async.bulk.tensor.4d.shared::cluster.global.mbarrier::complete_tx::bytes [%0], [%1, {0, %3, %4, 0}], [%2]; }"
                         ::"r"(dst), "l"(&p.m_w1), "r"(full), "r"(rd * 128 + (s & 3) * 32), "r"(fs * 3) : "memory");
          };
          uint32_t v = ep * 16 - 1;
          HINT(if (i >= 0 && (~known >> s) & PD) v = ldr(cnt));
          if (i >= AH && (known >> s) & 1) {
            loadw();
            loadx();
          } else {
            if ((uint32_t)i >= AH) loadw();
            if (lane == 0) TS3(2, s);
            if (i >= 0) {
              HINT(if (!((known >> s) & 1)) poll_lane(v, cnt, ep * 16, s));
              loadx();
            }
          }
          if (i >= 0 && lane == 0) TS3(3, s);
          if (((PFW | PF2) << AH >> (i + AH)) & 1) {
            const int k = __popc((PFW | PF2) << (31 - s));
            if (elect()) bulk_pf(k < 5 ? (kh ? p.wu : p.wg) + (k * 128 + (b >> 1) * 2) * F_ : p.w2 + b * 7680 + (k - 5) * 2560, k < 5 ? 6144 : 5120);
          }
          if (lane == 0 && i == -1) TSTAMP(10);
          if (lane == 0 && i == 0) TSTAMP(19);
          if (lane == 0 && i == 16) TSTAMP(1);
          slot = i == -1 || i == 3 ? 2 : slot == 5 ? 0 : slot + 1;
          known |= __ballot_sync(0xffffffffu, (int)(v - ep * 16) >= 0);
        }
      }
      __syncwarp();
      asm volatile("barrier.cluster.wait.aligned;" ::: "memory");
#pragma unroll 1
      for (int s = 0; s < 10; s++) {
        const int e = s < 7 ? s : s - 7;
        const uint32_t d = sb + w2entry(e), st = e == 6 ? SLOT : 8192;
        const int k0 = (fs ^ (s < 4 ? s >> 1 : s & 1)) * 192, c0 = ocol(ro, s < 4 ? s & 1 : s >> 1);
        mbar_wait(BAR(s >= 7 ? B_W2E + e : B_EMPTY + min(s, 5)), 0);
        if (elect()) {
          mbar_expect(BAR(B_W2F + e), 24576);
#pragma unroll
          for (int i = 0; i < 3; i++) tma2d(d + i * st, &p.m_w2, c0, k0 + i * 64, BAR(B_W2F + e));
        }
      }
    } else {
      if (warp == 1) {
        bar_sync(1, 384);
        asm volatile("barrier.cluster.arrive.relaxed.aligned;" ::: "memory");
        if (lane == 0) TSTAMP(112);
        unrolled<NLD>([&](auto I) {
          constexpr uint32_t e = nth_load(I.v), n = e & 15, kind = (e >> 4) & 15;
          while (clk() - t_start < (e >> 8) + (n == 5 ? (b >> 2) * D_Q : 0)) {}
          if (kind == 1 && n == 5) mbar_wait(BAR(B_ROLE), 0);
          if (elect()) {
            if constexpr (kind == 0) {
              const uint32_t d = sb + kreg(n), bar = BAR(B_KIN + n);
              const int ch = n * 128 + (b & 3) * 32, tg = (b >> 2) * 8;
              mbar_expect(bar, 9984);
              tma3d(d, &p.m_k, ch, tg, 0, bar);
              tma3d(d + voff(n), &p.m_v, ch, tg, 0, bar);
              tma3d(d + 4096, &p.m_kh, ch, tg - 1, 5, bar);
              bulk_ld(d + 5632, pshift + ch * 4, 256, bar);
            } else if constexpr (kind == 1 && n < 5) {
              mbar_expect(BAR(B_SSM + n), 4096);
              bulk_ld(sb + bnd(n) + U_RAW, pssm + (size_t)(n * 128 + b) * S_, 4096, BAR(B_SSM + n));
            } else {
              mbar_expect(BAR(B_QIN), 20480);
              tma3d(sb + O_REG, &p.m_q, 0, lds32(sb + O_ROLE) * 16, 0, BAR(B_QIN));
            }
            TSTAMP(96 + I.v);
          }
        });
        ROLEU;
        EPOCHU;
        uint32_t known = 0;
        const uint32_t* const cnt = g_sync + Y_Y + min(lane, 10) * 32;
        const uint32_t target = ep * (lane < 5 ? 128 : 40);
        int ny = 0, nm = 0;
#pragma unroll 1
        for (int it = 0; ny < 5 || nm < 6; it++) {
          const int j = nm < 5 ? (ord >> (nm * 4)) & 7 : nm;
          uint32_t u = target;
          HINT(if (known != 2047) u = ldr(cnt));
          if ((known >> (5 + j)) & 1) {
            uint4 v[5];
            uint32_t bad = 0, lo[5], hi[5];
#pragma unroll
            for (int k = 0; k < 5; k++) v[k] = ldr4(g_mod + j * D_ + k * 128 + lane * 4);
#pragma unroll
            for (int k = 0; k < 5; k++) {
              bad |= (v[k].x ^ ep) | (v[k].y ^ ep) | (v[k].z ^ ep) | (v[k].w ^ ep);
              lo[k] = pack2(__uint_as_float(v[k].x), __uint_as_float(v[k].y));
              hi[k] = pack2(__uint_as_float(v[k].z), __uint_as_float(v[k].w));
            }
            if (!__any_sync(0xffffffffu, bad & 3) || it > 200000) {
              if (nm < 5) {
                const uint32_t ma = sb + O_MA + nm * 768 + lane * 8, one = 0x3F803F80u, c0 = hadd2(lo[4], one), c1 = hadd2(hi[4], one);
                sts64(ma, hmul2(lo[2], hadd2(lo[1], one)), hmul2(hi[2], hadd2(hi[1], one)));
                sts64(ma + 256, hmul2(lo[2], lo[0]), hmul2(hi[2], hi[0]));
                sts64(ma + 512, c0, c1);
                __syncwarp();
                if (lane == 0) { mbar_arrive(BAR(B_PR + nm)); if (nm < 3) TSTAMP(nm < 2 ? 7 + nm : 79); }
                if (j == vr) {
                  sts64(sb + O_CS + (lane >> 1) * 32 + (lane & 1) * 8, c0, c1);
                  sts64(sb + O_CS + (lane >> 1) * 32 + (lane & 1) * 8 + 16, lo[3], hi[3]);
                  fence_async_smem();
                  __syncwarp();
                  if (lane == 0) mbar_arrive(BAR(B_CS));
                }
              } else {
#pragma unroll
                for (int k = 0; k < 5; k++) if ((k * 32 + lane >= 80) == kh) sts128(sb + O_GB + k * 512 + lane * 16 - kh * 1280, lo[k] << 16, lo[k] & 0xffff0000u, hi[k] << 16, hi[k] & 0xffff0000u);
              }
              nm++;
            }
          }
          known |= __ballot_sync(0xffffffffu, (int)(u - target) >= 0 || it > 100000) & 2047;
          if (ny < 5) {
            const int y = (ord >> (ny * 4)) & 7;
            if (nm > 5 && ny >= 2) mbar_wait(BAR(B_YE + (ny & 1)), ny >> 2);
            if (((known >> y) & 1) && (ny < 2 || mbar_test(BAR(B_YE + (ny & 1)), ny >> 2) || it > 200000)) {
              if (elect()) {
                if (ny < 2) TSTAMP(47 + ny);
                mbar_expect(BAR(B_YF + (ny & 1)), 4096);
                bulk_ld(sb + (ny & 1 ? O_BP : O_Y), ps + (pgo(rb, ro & 7) ^ cgrp(G_Y + y)), 4096, BAR(B_YF + (ny & 1)));
              }
              ny++;
            }
          }
        }
        __syncwarp();
        if (lane < 6) mbar_expect(BAR(B_HF + lane), 8192);
        if (lane == 0) { sts128(sb + O_BP + 6144, 0, 0, 0, 0); mbar_arrive(BAR(B_VV)); }
        mbar_wait(BAR(B_YE + 1), 1);
      } else {
        const int t0 = tid & 63;
#pragma unroll
        for (int j = 0; j < 5; j++) {
          if (tid < 83) sts128(sb + bnd(j) + (lane < 17 ? U_KV + 4096 + lane * 16 : lane == 17 ? U_RAW - 16 : U_ODD - 16), 0, 0, 0, 0);
        }
        bar_sync(1, 384);
        asm volatile("barrier.cluster.arrive.relaxed.aligned;" ::: "memory");
        fence_async_smem();
        uint32_t dv;
        asm volatile("ld.global.nc.u16 %0, [%1];" : "=r"(dv) : "l"(pD + min(lane, 4) * 128 + b) : "memory");
        if (elect()) {
#pragma unroll
          for (int i = 0; i < 4; i++) asm volatile("prefetch.tensormap [%0];" ::"l"(&p.m_k + hw * 4 + i) : "memory");
        }
        asm volatile("prefetch.global.L2 [%0];" ::"l"(p.c + t0 * 10) : "memory");
#pragma unroll 1
        for (int j = 0; j < 5; j++) {
          const uint32_t ra = sb + bnd(j) + U_RAW + hw * 2048 + lane * 16;
          const float dj = blo(__shfl_sync(0xffffffffu, dv, j));
          mbar_wait(BAR(B_SSM + j), 0);
          if (tid == 64 && j == 0) TSTAMP(77);
#pragma unroll
          for (int i = 0; i < 4; i++) {
            uint4 w = lds128(ra + i * 512);
            const uint32_t pv = lds32(ra + i * 512 - 4);
            if (i == 0 && tid == 64) { w.x = prmt(pack2(blo(w.x) + dj, 0.f), w.x, 0x7610); sts32(ra, w.x); }
            sts128(ra + (U_ODD - U_RAW) + i * 512, prmt(pv, w.x, 0x5432), prmt(w.x, w.y, 0x5432), prmt(w.y, w.z, 0x5432), prmt(w.z, w.w, 0x5432));
          }
          __syncwarp();
          if (lane == 0) mbar_arrive(BAR(B_PL + j));
          if (tid == 64) TSTAMP(32 + j);
          if (j == 0) {
            uint32_t x[5];
#pragma unroll
            for (int i = 0; i < 5; i++) x[i] = ldr((const uint32_t*)p.c + hw * 160 + i * 32 + lane);
#pragma unroll
            for (int i = 0; i < 5; i++)
              sts32(sb + O_SILU + i * 256 + (lane >> 2) * 32 + hw * 16 + (lane & 3) * 4, pack2(__fdividef(blo(x[i]), 1.f + __expf(-blo(x[i]))), __fdividef(bhi(x[i]), 1.f + __expf(-bhi(x[i])))));
            fence_async_smem();
          }
        }
        mbar_wait(BAR(B_LN), 0);
        ROLEU;
        uint32_t ya = lane * 32 + (lane & 4) * 4, xl = (lane ^ lane >> 3) * 16, pl = (lane & 3) * 16;
        const uint32_t tt = -(lds32(sb + O_ROLE + 4) & 1), ln[2] = {lds32(sb + O_LN + (lane & 28)), lds32(sb + O_LN + 32 + (lane & 28))};
        float sx[4] = {0.f, 0.f, 0.f, 0.f};
        keep(ya); keep(xl); keep(pl);
#pragma unroll 1
        for (int it = 0; it != 10;) {
          const int j = (ord >> (it * 2 & 28)) & 7, odd = (it >> 1) & 1, g = (it & 1) * 2 + hw;
          const uint32_t pm = sb + O_MA + (it & 14) * 384 + g * 64, yo = sb + (odd ? O_BP : O_Y) + g * 1024, qo = sb + O_REG + (j * 4 + g) * 1024;
          uint32_t q[8], m[8], y[8];
          mbar_wait(BAR(B_PR + ((it >> 1) & 7)), 0);
          {
            const uint4 q0 = lds128(addu(xl, qo)), a4 = lds128(addu(pl, pm)), b4 = lds128(addu(pl, pm) + 256), q1 = lds128(addu(xl, qo) + 512);
            const uint32_t ma[4] = {a4.x, a4.y, a4.z, a4.w}, mb[4] = {b4.x, b4.y, b4.z, b4.w};
            q[0] = q0.x; q[1] = q0.y; q[2] = q0.z; q[3] = q0.w; q[4] = q1.x; q[5] = q1.y; q[6] = q1.z; q[7] = q1.w;
#pragma unroll
            for (int i = 0; i < 8; i++) m[i] = hfma2(hfma2lh(q[i], ln[i >> 2]), ma[i & 3], mb[i & 3]);
          }
          mbar_wait(BAR(B_YF + odd), (it >> 2) & 1);
          if (!(xl | hw) && it < 6 && !(it & 1)) TSTAMP(it == 0 ? 49 : it == 2 ? 58 : 80);
          ldsm4t(addu(ya, yo), y[0], y[1], y[2], y[3]);
          ldsm4t(addu(ya, yo) ^ 16, y[4], y[5], y[6], y[7]);
#pragma unroll
          for (int i = 0; i < 8; i++) q[i] = hfma2(m[i], y[i], q[i]);
          if ((__ballot_sync(0xffffffffu, ((y[0] ^ tt) | (y[1] ^ tt) | (y[2] ^ tt) | (y[3] ^ tt) | (y[4] ^ tt) | (y[5] ^ tt) | (y[6] ^ tt) | (y[7] ^ tt)) & 0x00010001u) & 15) && it < 16) {
#pragma unroll 1
            for (int hf = 0; hf < 32; hf += 16) refetch16(ps + ((pgo(rb, ro & 7) ^ cgrp(G_Y + j)) + g * 1024 + (ya ^ hf)), (ya ^ hf) + yo, tt);
            __syncwarp();
            it += 16;
            continue;
          }
          const uint4 c4 = lds128(addu(pl, pm) + 512);
          uint8_t* const xg = ps + addu(xl, tile(rb, G_X, j * 4 + g) + (ro & 4) * 4096 + (ro & 3) * 1024);
          stg128(xg, tag0(hmul2(q[0], c4.x), tt), hmul2(q[1], c4.y), hmul2(q[2], c4.z), hmul2(q[3], c4.w));
          stg128(xg + 512, tag0(hmul2(q[4], c4.x), tt), hmul2(q[5], c4.y), hmul2(q[6], c4.z), hmul2(q[7], c4.w));
          asm volatile("{ .reg .pred p; elect.sync _|p, 0xffffffff; @p red.relaxed.gpu.global.add.u32 [%0], 1; @p mbarrier.arrive.shared::cta.b64 _, [%1]; }"
                       ::"l"(misc + M_X + j * 8 + (it & 1) * 4), "r"(BAR(B_YE + odd)) : "memory");
          uint8_t* const og = p.out + addu((xl >> 6) * 1280 + pl, ro * 20480 + (j * 4 + g) * 64);
          stg128(og, q[0], q[1], q[2], q[3]);
          stg128(og + 10240, q[4], q[5], q[6], q[7]);
#pragma unroll
          for (int i = 0; i < 8; i++) {
            const float f = blo(q[i]), h = bhi(q[i]);
            float &s1 = sx[(i >> 2) * 2], &s2 = sx[(i >> 2) * 2 + 1];
            s1 += f; s2 = fmaf(f, f, s2); s1 += h; s2 = fmaf(h, h, s2);
          }
          if (!(xl | hw) && (it & 1)) TSTAMP(12 + ((it & 15) >> 1));
          if (!(xl | hw) && it == 0) TSTAMP(116);
          it = (it & 15) + 1;
        }
        const int lane = ya >> 5, t = hw * 32 + lane;
        EPOCHU;
#pragma unroll
        for (int i = 0; i < 8; i++) sx[i & 3] += __shfl_xor_sync(0xffffffffu, sx[i & 3], (i >> 2) + 1);
        if (!(lane & 3)) sts64(sb + O_SX + t * 2, __float_as_uint(hw ? sx[0] : sx[2]), __float_as_uint(hw ? sx[1] : sx[3]));
        bar_sync(4, 64);
        const float2 so = lds64f(sb + O_SX + (hw ^ 1) * 64 + (xl >> 6) * 8);
        const float mean = ((hw ? sx[2] : sx[0]) + so.x) * (1.f / D_);
        const uint32_t pa = pack2(-mean, sqrtf(fmaxf(((hw ? sx[3] : sx[1]) + so.y) * (1.f / D_) - mean * mean, 0.f) + 1e-5f));
        if (!(lane & 3))
          asm volatile("st.relaxed.gpu.global.v2.u32 [%0], {%1,%2};" ::"l"(misc + M_ST + (ro & 7) * 128 + t * 2), "r"(pa), "r"(tagf(__fdividef(1.f, bhi(pa) * bhi(pa)), ep)) : "memory");
        uint4 v;
        int it = 0;
        do v = ldr4((const uint32_t*)(misc + M_ST + t * 16)); while ((((v.y ^ ep) | (v.w ^ ep)) & 3) && ++it < 100000);
        sts128(sb + O_ST + t * 16, v.x, v.y, v.z, v.w);
        __syncwarp();
        if (lane == 0) mbar_arrive(BAR(B_ST + hw));
        if (t == 0) TSTAMP(52);
      }
      ROLEU;
      EPOCHU;
      int lane;
      asm volatile("mov.u32 %0, %%laneid;" : "=r"(lane));
      {
        HINT(poll_ge(g_sync + Y_VV + fs * 32, ep * 128));
        uint32_t v[20], bad;
        int it = 0;
        const uint32_t* g = g_vv + fs * 1920 + (hw + 1) * 128 + lane;
        do {
          bad = 0;
#pragma unroll
          for (int k = 0; k < 20; k++) v[k] = ldr(g + ((k % 5) * 384 + (k / 5) * 32));
#pragma unroll
          for (int k = 0; k < 20; k++) bad |= v[k] ^ ep;
        } while (__any_sync(0xffffffffu, bad & 1) && ++it < 100000);
#pragma unroll
        for (int k = 0; k < 4; k++) sts128(sb + O_BP + ((hw + 1) * 128 + k * 32 + lane) * 16, v[5 * k], v[5 * k + 1], v[5 * k + 2], hadd2(v[5 * k + 3], v[5 * k + 4]));
        fence_async_smem();
        __syncwarp();
      }
      if (lane == 0) mbar_arrive(BAR(B_VV));
      if (warp == 1) {
        if (lane == 0) TSTAMP(37);
        uint32_t v;
        int it = 0;
        do asm volatile("ld.acquire.gpu.global.u32 %0, [%1];" : "=r"(v) : "l"(misc + M_O) : "memory"); while ((int)(v - ep * 16) < 0 && ++it < 100000);
        asm volatile("fence.proxy.async.global;" ::: "memory");
        if (lane == 0) { mbar_arrive(BAR(B_X1)); TSTAMP(30); }
      } else {
        asm volatile("fence.acq_rel.gpu;" ::: "memory");
        __syncwarp();
        if (lane == 0) hint_add((uint32_t*)(misc + M_O));
      }
      __syncwarp();
      asm volatile("barrier.cluster.wait.aligned;" ::: "memory");
    }
  } else {
    const int isE = warp >= 8 ? 1 : 0;
    const int w = warp & 3, r = lane >> 2, c = lane & 3;
    const bool lead = (tid & 127) == 0;
    const int tb = b >> 2;
    if (isE) {
      const int u = tid & 127, t = tb * 64 + r * 8 + w, th = t - (w == 3 ? 0 : 3);
      const uint32_t d = sb + kreg(0) + (u >> 2) * 64 + ((c ^ (r >> 1)) << 4);
      const int o = t * D_ + (b & 3) * 32 + c * 8;
      cpa16(d, pk + o, 16); cpa16(d + voff(0), pv + o, 16);
      cpa16(d + 2048, pk + o + 4 * D_, 16); cpa16(d + voff(0) + 2048, pv + o + 4 * D_, 16);
      if (u < 112) cpa16(w == 3 ? sb + kreg(0) + 5632 + lane * 16 : d + 4096, w == 3 ? pshift + (b & 3) * 128 + lane * 8 : pk + (th < 0 ? o : o - 3 * D_), th < 0 ? 0 : 16);
      if (lead) TSTAMP(74);
    } else {
      if (lane == 0) {
#pragma unroll
        for (int i = 0; i < 17; i++) mbar_init(BAR(w + 4 * i), i < 2 ? 2 : i < 5 ? 4 : 1);
        asm volatile("fence.mbarrier_init.release.cluster;" ::: "memory");
      }
      __syncwarp();
      if (lead) TSTAMP(76);
    }
    EPLOAD;
    bar_sync(1, 384);
    if (tid == 256) TSTAMP(75);
    asm volatile("setmaxnreg.inc.sync.aligned.u32 232;");
    asm volatile("barrier.cluster.arrive.relaxed.aligned;" ::: "memory");
    EPOCH;
    if (isE) {
      asm volatile("cp.async.wait_all;" ::: "memory");
      bar_sync(6, 128);
    }
    asm volatile("barrier.cluster.wait.aligned;" ::: "memory");
    uint64_t steps = isE ? sched(1) : sched(0);
    const uint32_t rel = isE ? release(1) : release(0);
#pragma unroll 1
    for (int si = 0; steps; si++, steps >>= 9) {
      const uint32_t todo = (uint32_t)steps;
      if (todo & 1) {
        uint4 x[10];
        mbar_wait(BAR(B_QIN), 0);
        if (lead) TSTAMP(9);
#pragma unroll
        for (int i = 0; i < 10; i++) x[i] = lds128(sb + O_REG + (lane >> 4) * 1024 + w * 256 + (lane & 15) * 16 + i * 2048);
        float z[4] = {0.f, 0.f, 0.f, 0.f};
        auto acc = [&](uint32_t v) { const float f = blo(v), g = bhi(v); z[0] += f; z[1] = fmaf(f, f, z[1]); z[2] += g; z[3] = fmaf(g, g, z[3]); };
#pragma unroll
        for (int i = 0; i < 10; i++) { acc(x[i].x); acc(x[i].y); acc(x[i].z); acc(x[i].w); }
        z[0] += z[2]; z[1] += z[3];
#pragma unroll
        for (int i = 0; i < 3; i++) { z[0] += __shfl_xor_sync(0xffffffffu, z[0], i < 2 ? i + 1 : 16); z[1] += __shfl_xor_sync(0xffffffffu, z[1], i < 2 ? i + 1 : 16); }
        const float mean = z[0] * (1.f / D_), rs = rbf(rsqrtf(fmaxf(z[1] * (1.f / D_) - mean * mean, 0.f) + 1e-5f));
        if (!(lane & 19)) sts32(sb + O_LN + w * 16 + lane, pack2(rs, -mean * rs));
        __syncwarp();
        if (lane == 0) mbar_arrive(BAR(B_LN));
        if (lead) TSTAMP(59);
      }
      if (todo & 14) {
        const int n = ((todo >> 1) & 7) - 1, tg = lane & 7;
        const uint32_t a = sb + kreg(n) + tg * 64 + ((w ^ (tg >> 1)) << 4) + (lane >> 3) * 4;
        if (n) mbar_wait(BAR(B_KIN + n), 0);
        if (lead) TSTAMP(69 + n);
        uint32_t kk[11], x[8];
        const uint4 sw = lds128(sb + kreg(n) + 5632 + w * 64 + (lane & 24) * 2);
#pragma unroll
        for (int i = 0; i < 11; i++) kk[i] = lds32(a + (i < 3 ? 4096 + i * 512 : (i - 3) * 512));
#pragma unroll
        for (int i = 0; i < 8; i++) x[7 - i] = lds32(a + voff(n) + i * 512);
        const uint32_t w0 = prmt(sw.x, sw.z, 0x5410), w1 = prmt(sw.x, sw.z, 0x7632), w2 = prmt(sw.y, sw.w, 0x5410), w3 = prmt(sw.y, sw.w, 0x7632);
#pragma unroll
        for (int i = 0; i < 8; i++) x[7 - i] = hmul2(hfma2(kk[i + 3], w0, hfma2(kk[i + 2], w1, hfma2(kk[i + 1], w2, hmul2(kk[i], w3)))), x[7 - i]);
        const int tw = (~tb & 7) ^ ((~lane & 1) << 2);
#pragma unroll
        for (int i = 0; i < 4; i++) x[2 * i] = settag(x[2 * i], tw == i ? 0x00010001u : 0u, -(ep & 1));
        const uint32_t o = (pgo((b & 3) * 4 + w, (lane >> 3) * 2) ^ cgrp(G_KV + n)) + 4080 - tb * 128 - tg * 16;
        stg128(ps + o, prmt(x[0], x[1], 0x5410), prmt(x[2], x[3], 0x5410), prmt(x[4], x[5], 0x5410), prmt(x[6], x[7], 0x5410));
        stg128(ps + (o ^ 0x3000), prmt(x[0], x[1], 0x7632), prmt(x[2], x[3], 0x7632), prmt(x[4], x[5], 0x7632), prmt(x[6], x[7], 0x7632));
        bar_sync(5 + isE, 128);
        if (lead) { hint_add(g_sync + Y_KV + (n * 4 + (b & 3)) * 32); TSTAMP(64 + n); }
      }
      if (b < 120 && ((todo >> 4) & 3) == 1 + (part >= NE)) {
        float d[4];
        const uint64_t db = mkdesc(sb + O_SILU, 32, 128, 0), da = mkdesc(sb, 20480, 512, 2);
        mbar_wait(BAR(B_PL + 1), 0);
        mbar_wait(BAR(B_WM), 0);
        if (lead) TSTAMP(81 + min(part, 2));
        wg_fence();
#pragma unroll
        for (int kk = 0; kk < 20; kk++) wgmma_ss_8_10(d, da + kk * 64, db + kk * 4, kk);
        wg_commit();
        wg_wait<0>();
        regfence<4>(d);
        const uint32_t xa = sb + O_SILU + 2048 + (w & 1) * 64 + r * 8;
        if (c == 0 && w >= 2) sts64(xa, __float_as_uint(d[1]), __float_as_uint(d[3]));
        bar_sync(5 + isE, 128);
        if (w < 2) {
          const float2 e = lds64f(xa);
          if (c == 0) { str(g_mod + b * 32 + w * 16 + r, tagf(d[0] + e.x, ep)); str(g_mod + b * 32 + w * 16 + r + 8, tagf(d[2] + e.y, ep)); }
          __syncwarp();
          if (lane == 0) hint_add(g_sync + Y_MOD + part * 32);
        }
        if (lead) TSTAMP(part >= 2 ? 60 : 20 + part);
      }
      if (todo & 448) {
        const int j = ((todo >> 6) & 7) - 1, u = tid & 127;
        const uint32_t ub = sb + bnd(j), sa = ub + ((r & 1) ? U_RAW : U_ODD) + 4 * (8 * w + (r >> 1) - 3 + c);
        uint32_t A[64];
        float d[128];
        mbar_wait(BAR(B_PL + j), 0);
#pragma unroll
        for (int g = 0; g < 16; g++) { A[4 * g] = lds32(sa + g * 256); A[4 * g + 1] = lds32(sa + g * 256 + 128); A[4 * g + 2] = lds32(sa + g * 256 + 16); A[4 * g + 3] = lds32(sa + g * 256 + 144); }
        if (lead) TSTAMP(89 + j);
        mbar_wait(BAR(B_KV + j), 0);
        if ((lds32(ub + U_KV + u * 32 + r * 4) ^ ep) & 1) refetch(ps + (pgo(b >> 3, b & 7) ^ cgrp(G_KV + j)) + u * 32, r * 4, ub + U_KV + u * 32, ep);
        __syncwarp();
        bar_sync(5 + isE, 128);
        if (lead) TSTAMP(53 + j);
        const uint64_t db = mkdesc(ub + U_KV, 16, 128, 0);
        wg_fence();
        wgmma_rs_32_0(d + 0, A[0], A[1], A[2], A[3], db + 0, 0);
        wgmma_rs_32_0(d + 16, A[0], A[1], A[2], A[3], db + 32, 0);
        wgmma_rs_32_0(d + 32, A[0], A[1], A[2], A[3], db + 64, 0);
        wgmma_rs_32_0(d + 48, A[0], A[1], A[2], A[3], db + 96, 0);
        wgmma_rs_32_0(d + 0, A[4], A[5], A[6], A[7], db + 16, 1);
        wgmma_rs_32_0(d + 16, A[4], A[5], A[6], A[7], db + 48, 1);
        wgmma_rs_32_0(d + 32, A[4], A[5], A[6], A[7], db + 80, 1);
        wgmma_rs_32_0(d + 48, A[4], A[5], A[6], A[7], db + 112, 1);
        wgmma_rs_32_0(d + 0, A[8], A[9], A[10], A[11], db + 32, 1);
        wgmma_rs_32_0(d + 16, A[8], A[9], A[10], A[11], db + 64, 1);
        wgmma_rs_32_0(d + 32, A[8], A[9], A[10], A[11], db + 96, 1);
        wgmma_rs_32_0(d + 64, A[0], A[1], A[2], A[3], db + 128, 0);
        wgmma_rs_32_0(d + 0, A[12], A[13], A[14], A[15], db + 48, 1);
        wgmma_rs_32_0(d + 16, A[12], A[13], A[14], A[15], db + 80, 1);
        wgmma_rs_32_0(d + 32, A[12], A[13], A[14], A[15], db + 112, 1);
        wgmma_rs_32_0(d + 48, A[8], A[9], A[10], A[11], db + 128, 1);
        wgmma_rs_32_0(d + 0, A[16], A[17], A[18], A[19], db + 64, 1);
        wgmma_rs_32_0(d + 16, A[16], A[17], A[18], A[19], db + 96, 1);
        wgmma_rs_32_0(d + 32, A[16], A[17], A[18], A[19], db + 128, 1);
        wgmma_rs_32_0(d + 64, A[4], A[5], A[6], A[7], db + 144, 1);
        wgmma_rs_32_0(d + 0, A[20], A[21], A[22], A[23], db + 80, 1);
        wgmma_rs_32_0(d + 16, A[20], A[21], A[22], A[23], db + 112, 1);
        wgmma_rs_32_0(d + 48, A[12], A[13], A[14], A[15], db + 144, 1);
        wgmma_rs_32_0(d + 32, A[20], A[21], A[22], A[23], db + 144, 1);
        wgmma_rs_32_0(d + 0, A[24], A[25], A[26], A[27], db + 96, 1);
        wgmma_rs_32_0(d + 16, A[24], A[25], A[26], A[27], db + 128, 1);
        wgmma_rs_32_0(d + 80, A[0], A[1], A[2], A[3], db + 160, 0);
        wgmma_rs_32_0(d + 64, A[8], A[9], A[10], A[11], db + 160, 1);
        wgmma_rs_32_0(d + 0, A[28], A[29], A[30], A[31], db + 112, 1);
        wgmma_rs_32_0(d + 16, A[28], A[29], A[30], A[31], db + 144, 1);
        wgmma_rs_32_0(d + 48, A[16], A[17], A[18], A[19], db + 160, 1);
        wgmma_rs_32_0(d + 32, A[24], A[25], A[26], A[27], db + 160, 1);
        wgmma_rs_32_0(d + 0, A[32], A[33], A[34], A[35], db + 128, 1);
        wgmma_rs_32_0(d + 16, A[32], A[33], A[34], A[35], db + 160, 1);
        wgmma_rs_32_0(d + 80, A[4], A[5], A[6], A[7], db + 176, 1);
        wgmma_rs_32_0(d + 64, A[12], A[13], A[14], A[15], db + 176, 1);
        wgmma_rs_32_0(d + 0, A[36], A[37], A[38], A[39], db + 144, 1);
        wgmma_rs_32_0(d + 48, A[20], A[21], A[22], A[23], db + 176, 1);
        wgmma_rs_32_0(d + 32, A[28], A[29], A[30], A[31], db + 176, 1);
        wgmma_rs_32_0(d + 16, A[36], A[37], A[38], A[39], db + 176, 1);
        wgmma_rs_32_0(d + 0, A[40], A[41], A[42], A[43], db + 160, 1);
        wgmma_rs_32_0(d + 96, A[0], A[1], A[2], A[3], db + 192, 0);
        wgmma_rs_32_0(d + 80, A[8], A[9], A[10], A[11], db + 192, 1);
        wgmma_rs_32_0(d + 64, A[16], A[17], A[18], A[19], db + 192, 1);
        wgmma_rs_32_0(d + 0, A[44], A[45], A[46], A[47], db + 176, 1);
        wgmma_rs_32_0(d + 48, A[24], A[25], A[26], A[27], db + 192, 1);
        wgmma_rs_32_0(d + 32, A[32], A[33], A[34], A[35], db + 192, 1);
        wgmma_rs_32_0(d + 16, A[40], A[41], A[42], A[43], db + 192, 1);
        wgmma_rs_32_0(d + 0, A[48], A[49], A[50], A[51], db + 192, 1);
        wgmma_rs_32_0(d + 96, A[4], A[5], A[6], A[7], db + 208, 1);
        wgmma_rs_32_0(d + 80, A[12], A[13], A[14], A[15], db + 208, 1);
        wgmma_rs_32_0(d + 64, A[20], A[21], A[22], A[23], db + 208, 1);
        wgmma_rs_32_0(d + 48, A[28], A[29], A[30], A[31], db + 208, 1);
        wgmma_rs_32_0(d + 32, A[36], A[37], A[38], A[39], db + 208, 1);
        wgmma_rs_32_0(d + 16, A[44], A[45], A[46], A[47], db + 208, 1);
        wgmma_rs_32_0(d + 0, A[52], A[53], A[54], A[55], db + 208, 1);
        wgmma_rs_32_0(d + 112, A[0], A[1], A[2], A[3], db + 224, 0);
        wgmma_rs_32_0(d + 96, A[8], A[9], A[10], A[11], db + 224, 1);
        wgmma_rs_32_0(d + 80, A[16], A[17], A[18], A[19], db + 224, 1);
        wgmma_rs_32_0(d + 64, A[24], A[25], A[26], A[27], db + 224, 1);
        wgmma_rs_32_0(d + 48, A[32], A[33], A[34], A[35], db + 224, 1);
        wgmma_rs_32_0(d + 32, A[40], A[41], A[42], A[43], db + 224, 1);
        wgmma_rs_32_0(d + 16, A[48], A[49], A[50], A[51], db + 224, 1);
        wgmma_rs_32_0(d + 0, A[56], A[57], A[58], A[59], db + 224, 1);
        wgmma_rs_32_0(d + 112, A[4], A[5], A[6], A[7], db + 240, 1);
        wgmma_rs_32_0(d + 96, A[12], A[13], A[14], A[15], db + 240, 1);
        wgmma_rs_32_0(d + 80, A[20], A[21], A[22], A[23], db + 240, 1);
        wgmma_rs_32_0(d + 64, A[28], A[29], A[30], A[31], db + 240, 1);
        wgmma_rs_32_0(d + 48, A[36], A[37], A[38], A[39], db + 240, 1);
        wgmma_rs_32_0(d + 32, A[44], A[45], A[46], A[47], db + 240, 1);
        wgmma_rs_32_0(d + 16, A[52], A[53], A[54], A[55], db + 240, 1);
        wgmma_rs_32_0(d + 0, A[60], A[61], A[62], A[63], db + 240, 1);
        wg_commit();
        const uint32_t yoff = ub + w * 2048 + (127 + 2 * w - lane) * 16;
        const uint32_t yoff0 = yoff + (lane < 2 * w ? -2048 : 8192), yoff4 = yoff + (lane < 2 * w ? 6144 : 0);
        wg_wait<0>();
        regfence<128>(d);
        if (rel >> 18 == si) bar_arrive(8, 256);
        if (lead) TSTAMP(42 + j);
        bar_sync(5 + isE, 128);
#pragma unroll
        for (int z = 0; z < 8; z++) {
          uint32_t e[4];
#pragma unroll
          for (int i = 0; i < 4; i++) {
            const int x = 4 * z + i;
            e[i] = x < 31 ? pack2(d[4 * x] + d[4 * x + 6], d[4 * x + 1] + d[4 * x + 7]) : pack2(d[4 * x], d[4 * x + 1]);
          }
          if (z == 0 && c < w) e[0] = 0;
          stsm4t(z == 0 ? yoff0 : z == 4 ? yoff4 : z < 4 ? yoff + 8192 - 512 * z : yoff - 512 * (z - 4), e[0], e[1], e[2], e[3]);
        }
        uint8_t* g = ps + (pgo(u >> 4, (u >> 1) & 7) ^ cgrp(G_Y + j)) + ((b & 97) | (b & 6) << 2 | (b & 24) >> 2) * 32 + ((u ^ (b >> 4)) & 1) * 16;
        bar_sync(5 + isE, 128);
#pragma unroll
        for (int i = 0; i < 2; i++) {
          const uint32_t pa = ub + u * 16 + i * 8192;
          const uint4 p0 = lds128(pa), p1 = lds128(pa + 2048), p2 = lds128(pa + 4096), p3 = lds128(pa + 6144);
          stg128(g + (i << 23), settag(hadd2(hadd2(p0.x, p1.x), hadd2(p2.x, p3.x)), 1, ep), hadd2(hadd2(p0.y, p1.y), hadd2(p2.y, p3.y)),
                 hadd2(hadd2(p0.z, p1.z), hadd2(p2.z, p3.z)), hadd2(hadd2(p0.w, p1.w), hadd2(p2.w, p3.w)));
        }
        bar_sync(5 + isE, 128);
        if (lead) { hint_add(g_sync + Y_Y + j * 32); TSTAMP(84 + j); }
      }
      if (w == 0 && lane < 12 && ((rel >> 3 * (lane >> 1)) & 7) == si) mbar_arrive_cl(mapa(BAR(B_EMPTY + (lane >> 1)), lane & 1));
      __syncwarp();
    }
    const int rh = isE;
    uint32_t hA[96];
    const uint32_t hb = sb + (isE ? O_REG : 24576) + w * 2048, hs = isE ? 8192 : SLOT;
    auto publish = [&](int kq) {
      asm volatile("st.async.weak.shared::cluster.mbarrier::complete_tx::bytes.v4.b32 [%0], {%1,%2,%3,%4}, [%5];" ::"r"(mapa(hb + lane * 16, kh ^ 1) + (kq >> 2) * hs + (kq & 3) * 512),
                   "r"(hA[4 * kq]), "r"(hA[4 * kq + 1]), "r"(hA[4 * kq + 2]), "r"(hA[4 * kq + 3]), "r"(mapa(BAR(B_HF + isE * 3), kh ^ 1) + (kq >> 2) * 8) : "memory");
      if (kq == 3 && tid == 256) TSTAMP(117);
    };
    {
      float ag[96], au[96], iv[2];
      int slot = 2, prev = 0, ph = 0, s = 0;
      int v0, vo;
      uint32_t vg;
      mbar_wait(BAR(B_ROLE), 0);
      { ROLE; v0 = min(vr, 2) * 4; vo = (2 * vt + isE) * 256; vg = (fs * 5 + vr) * 384 + (2 * vt + isE) * 64 + 16 * w + r; }
      const uint32_t dbase = mkdesc(sb, 4096, 0, 0);
      uint32_t ck = sb + 24576 + rh * 4096 + w * 1024 + lane * 32 + (r & 1) * 16;
      keep(ck);
      const uint32_t emp = mapa(BAR(B_EMPTY), tid & 1);
      if (isE) bar_sync(8, 256);
      auto ready = [&]() {
        if (s == LH + LEAD * isE) { if (isE) bar_arrive(7, 256); else bar_sync(7, 256); }
        mbar_wait(BAR(B_FULL + slot), ph);
        if ((lds32(addu(ck, slot * SLOT)) ^ ep) & 1) refetch(ps + (lds32(sb + O_XT + s * 4) + rh * 16384 + (tid & 127) * 32), (r & 1) * 16, (ck + slot * SLOT) & ~31u, ep);
        __syncwarp();
        if (lead) TS3(isE, s);
        if (s == 0 && lead) TSTAMP(22 + isE);
        if (s && (s & 3) == 0 && tid == 128) TSTAMP(37 + (s >> 2));
      };
      auto stage = [&](float* vv) {
        const uint32_t dl = dbase + slot * (SLOT >> 4);
        const uint64_t dg = mkdesc(0, 0, 1024, 1) | dl, da = mkdesc(0, 0, 512, 2) | (dl + ((24576 + rh * 4096) >> 4));
        wg_wait<1>();
        wg_fence();
        if (vv) {
          wgmma_ss_8_10(vv, dg + vo, mkdesc(sb + O_CS, 32, 128, 0) + (s & 3) * 8, s & 3);
          wgmma_ss_8_10(vv, dg + vo + 128, mkdesc(sb + O_CS, 32, 128, 0) + (s & 3) * 8 + 4, 1);
          wg_commit();
        }
        wgmma_ss_192_01(ag, da, dg, s);
        if (s > 1 && (tid & 126) == 0) mbar_arrive_cl(addu(emp, prev & 63));
        wgmma_ss_192_01(au, da, mkdesc(0, 0, 1024, 1) | (dl + 768), s);
        wgmma_ss_192_01(ag, mkdesc(0, 0, 512, 2) | ((uint32_t)da + 2), mkdesc(0, 0, 1024, 1) | (dl + 128), 1);
        wgmma_ss_192_01(au, mkdesc(0, 0, 512, 2) | ((uint32_t)da + 2), mkdesc(0, 0, 1024, 1) | (dl + 896), 1);
        wg_commit();
        prev = prev >> 8 | slot << 11;
        if (++slot == 6) { slot = s == 3 ? 2 : 0; ph ^= 1; }
        if (++s < 20) ready();
      };
      ready();
#pragma unroll 1
      for (int end = v0, k = 0; k < 2; end = 20, k++) {
#pragma unroll 1
        while (s < end) stage(nullptr);
        if (k == 0) {
          float vv[4];
          mbar_wait(BAR(B_CS), 0);
#pragma unroll 1
          do stage(vv); while (s & 3);
          wg_wait<1>();
          regfence<4>(vv);
          if (c == 0) { str(g_vv + vg, settag(pack2(vv[0], vv[1]), 1, ep)); str(g_vv + vg + 8, settag(pack2(vv[2], vv[3]), 1, ep)); }
          __syncwarp();
          asm volatile("{ .reg .pred p; elect.sync _|p, 0xffffffff; @p red.relaxed.gpu.global.add.u32 [%0], 1; }" ::"l"(g_sync + Y_VV + vg / 1920 * 32) : "memory");
        }
      }
      {
        if (tid == 128) str(g_sync + Y_EP + b * 32, ep);
        wg_wait<1>();
        if ((tid & 126) == 0) mbar_arrive_cl(emp + 32);
        mbar_wait(BAR(B_ST + rh), 0);
        const float2 sa = lds64f(sb + O_ST + rh * 512 + w * 128 + r * 8), sc = lds64f(sb + O_ST + rh * 512 + w * 128 + r * 8 + 64);
        const uint32_t a0 = __float_as_uint(sa.x), a1 = __float_as_uint(sc.x);
        iv[0] = sa.y; iv[1] = sc.y;
        mbar_wait(BAR(B_VV), 0);
        const uint64_t dp = mkdesc(sb + O_BP, 16, 128, 0);
        wg_fence();
        wgmma_rs_192_0(ag, a0, a1, 0, 0, dp, 1);
        wgmma_rs_192_0(au, a0, a1, 0, 0, dp + 192, 1);
        wg_commit();
        wg_wait<1>();
        if ((tid & 126) == 0) mbar_arrive_cl(emp + 40);
        mbar_wait(BAR(isE ? B_ST : B_EMPTY + 2), 0);
        wg_wait<0>();
      }
      regfence<96>(ag); regfence<96>(au);
      if (lead) TSTAMP(24 + isE);
#pragma unroll
      for (int kq = 0; kq < 12; kq++) {
#pragma unroll
        for (int i = 0; i < 4; i++) hA[4 * kq + i] = pack2(ag[8 * kq + 2 * i] * iv[i & 1] * au[8 * kq + 2 * i], ag[8 * kq + 2 * i + 1] * iv[i & 1] * au[8 * kq + 2 * i + 1]);
        if (kq < 4 * NPUB) publish(kq);
      }
      if (lead) TSTAMP(50 + isE);
    }
    float o[2][32];
    float2 gb[8];
    const uint32_t stg = hb + (lane & 15) * 128 + (((lane >> 4) ^ (lane & 7)) << 4);
    const int ro = __shfl_sync(0xffffffffu, lds32(sb + O_ROLE), 0), row = (ro >> 3) * 128 + rh * 64 + 16 * w;
    auto ldgb = [&](int fin) {
#pragma unroll
      for (int u = 0; u < 8; u++) gb[u] = lds64f(sb + O_GB + (ocol(ro & 6, fin) + 8 * u + 2 * c) * 4);
      if (fin >= 3) { if (elect()) bulk_wait_read<2>(); __syncwarp(); }
    };
    auto piece = [&](int fin, int u) {
      const float* x = o[fin & 1] + 8 * u;
      const float2 g0 = gb[2 * u], g1 = gb[2 * u + 1];
      stsm4((stg ^ u * 32) + fin % 3 * hs, pack2(x[0] * g0.x, x[1] * g0.y), pack2(x[2] * g0.x, x[3] * g0.y), pack2(x[4] * g1.x, x[5] * g1.y), pack2(x[6] * g1.x, x[7] * g1.y));
    };
    auto flush = [&](int fin) {
      fence_async_smem();
      __syncwarp();
      if (elect()) { tma2d_add(&p.m_out, hb + fin % 3 * hs, ocol(ro, fin), row); bulk_commit(); }
    };
    unrolled<10>([&](auto I) {
      constexpr int s = I.v, e = s < 7 ? s : s - 7, src = s < 4 ? s >> 1 : s & 1, blk = s < 4 ? s & 1 : s >> 1;
      constexpr int fin = s == 3 ? 0 : blk - 1;
      const uint64_t dw = mkdesc(sb + w2entry(e), 1024 * s, 1024, 1);
      if (s == 3 || s >= 4 && !src) ldgb(fin);
      if (s == 4) mbar_wait(BAR(B_X1), 0);
      mbar_wait(BAR(B_W2F + e), s >= 7);
      if (s == 6 && tid == 256) TSTAMP(123);
      TS2(3 * s);
      unrolled<12>([&](auto J) {
        constexpr int kk = J.v, n = s < 4 ? kk : src * 12 + kk;
        if (s == 2 && !(kk & 3)) {
          mbar_wait_cluster(BAR(B_HF + isE * 3 + (kk >> 2)), 0);
          if (kk == 0 && lead) TSTAMP(26 + isE);
#pragma unroll
          for (int i = kk; i < kk + 4; i++) {
            const uint4 v = lds128(hb + lane * 16 + (i >> 2) * hs + (i & 3) * 512);
            hA[48 + 4 * i] = v.x; hA[49 + 4 * i] = v.y; hA[50 + 4 * i] = v.z; hA[51 + 4 * i] = v.w;
          }
        }
        if (kk == 0 || s == 2 && !(kk & 3)) wg_fence();
        const uint32_t* h = hA + src * 48 + 4 * kk;
        wgmma_rs_64_1(o[blk & 1], h[0], h[1], h[2], h[3], dw + (kk >> 2) * (e == 6 ? SLOT >> 4 : 512) + (kk & 3) * 128, (src | kk) ? 1 : 0);
        if (s < 2 && (s * 12 + kk) % PUBD == PUBD - 1 && 4 * NPUB + (s * 12 + kk) / PUBD < 12) publish(4 * NPUB + (s * 12 + kk) / PUBD);
        if (kk == QD - 1 && s >= 1 && (s < 4 || !src)) {
          wg_commit();
          wg_wait<1>();
          if (s < 4 && lead) mbar_arrive(BAR(B_W2E + s - 1));
          if (s >= 3) regfence<32>(o[fin & 1]);
          if (s == 4) flush(0);
          TS2(3 * s + 2);
        }
        if (s == 3 && kk >= QD - 1 && (kk - QD + 1) % 2 == 0 && (kk - QD + 1) / 2 < 4) piece(0, (kk - QD + 1) / 2);
        if (s >= 4 && n >= QD - 1 && (n - QD + 1) % 3 == 0 && (n - QD + 1) / 3 < 4) piece(fin, (n - QD + 1) / 3);
        if (s >= 4 && n == QD + 14) flush(fin);
      });
      wg_commit();
      TS2(3 * s + 1);
    });
    ldgb(4);
    mbar_wait(BAR(B_X1), 0);
    wg_wait<0>();
    regfence<32>(o[0]);
    if (lead) TSTAMP(28 + isE);
#pragma unroll
    for (int u = 0; u < 4; u++) piece(4, u);
    flush(4);
    if (tid == 128) TSTAMP(119);
    if (elect()) bulk_wait_read<0>();
    if (tid == 256) TSTAMP(121);
    if (!isE) {
      if (lead) TSTAMP(31);
    }
  }
}

#define L2PROMO CU_TENSOR_MAP_L2_PROMOTION_L2_128B
typedef CUresult (*EncodeFn)(CUtensorMap*, CUtensorMapDataType, cuuint32_t, void*, const cuuint64_t*, const cuuint64_t*, const cuuint32_t*,
                             const cuuint32_t*, CUtensorMapInterleave, CUtensorMapSwizzle, CUtensorMapL2promotion, CUtensorMapFloatOOBfill);

void make_map(EncodeFn enc, CUtensorMap* m, const void* ptr, uint64_t inner, uint64_t outer, uint32_t bi, uint32_t bo, CUtensorMapSwizzle sw) {
  cuuint64_t d[2] = {inner, outer};
  cuuint64_t s[1] = {inner * 2};
  cuuint32_t bx[2] = {bi, bo};
  cuuint32_t e[2] = {1, 1};
  enc(m, CU_TENSOR_MAP_DATA_TYPE_BFLOAT16, 2, const_cast<void*>(ptr), d, s, bx, e, CU_TENSOR_MAP_INTERLEAVE_NONE, sw, L2PROMO,
      CU_TENSOR_MAP_FLOAT_OOB_FILL_NONE);
}

void make_map3(EncodeFn enc, CUtensorMap* m, const void* ptr, uint64_t d0, uint64_t d1, uint64_t d2, uint64_t s1, uint64_t s2, uint32_t b0, uint32_t b1, uint32_t b2,
               CUtensorMapSwizzle sw, uint64_t s3 = 0) {
  cuuint64_t d[4] = {d0, d1, d2, 2};
  cuuint64_t s[3] = {s1, s2, s3};
  cuuint32_t bx[4] = {b0, b1, b2, 2};
  cuuint32_t e[4] = {1, 1, 1, 1};
  enc(m, CU_TENSOR_MAP_DATA_TYPE_BFLOAT16, s3 ? 4 : 3, const_cast<void*>(ptr), d, s, bx, e, CU_TENSOR_MAP_INTERLEAVE_NONE, sw, L2PROMO,
      CU_TENSOR_MAP_FLOAT_OOB_FILL_NONE);
}

}

extern "C" void kernel_launch(void* const* d_in, const int* in_sizes, int n_in, void* d_out, int out_size) {
  (void)in_sizes; (void)n_in; (void)out_size;
  void* f = nullptr;
  cudaDriverEntryPointQueryResult qr;
  cudaGetDriverEntryPoint("cuTensorMapEncodeTiled", &f, cudaEnableDefault, &qr);
  EncodeFn enc = (EncodeFn)f;
  void* s;
  cudaGetSymbolAddress(&s, g_s);
  Params p = {};
  uint8_t* ps = (uint8_t*)(((uintptr_t)s + (2 << 20) - 1) & ~(uintptr_t)((2 << 20) - 1));
  make_map3(enc, &p.m_k, d_in[1], D_, S_ / 8, 8, 8 * D_ * 2, D_ * 2, 32, 8, 8, CU_TENSOR_MAP_SWIZZLE_64B);
  make_map3(enc, &p.m_kh, d_in[1], D_, S_ / 8, 8, 8 * D_ * 2, D_ * 2, 32, 8, 3, CU_TENSOR_MAP_SWIZZLE_64B);
  make_map3(enc, &p.m_v, d_in[2], D_, S_ / 8, 8, 8 * D_ * 2, D_ * 2, 32, 8, 8, CU_TENSOR_MAP_SWIZZLE_64B);
  make_map3(enc, &p.m_q, d_in[0], 32, S_, D_ / 32, D_ * 2, 64, 32, 16, D_ / 32, CU_TENSOR_MAP_SWIZZLE_64B);
  make_map3(enc, &p.m_wm, d_in[11], 6 * D_, 160, 4, 12 * D_, 160 * 12 * D_, 32, 160, 4, CU_TENSOR_MAP_SWIZZLE_64B);
  const int lo = (uintptr_t)d_in[7] < (uintptr_t)d_in[8] ? 7 : 8;
  make_map3(enc, &p.m_w1, d_in[lo], 64, D_, F_ / 64, F_ * 2, 128, 64, 32, 3, CU_TENSOR_MAP_SWIZZLE_128B, (uintptr_t)d_in[15 - lo] - (uintptr_t)d_in[lo]);
  make_map(enc, &p.m_w2, d_in[9], D_, F_, 64, 64, CU_TENSOR_MAP_SWIZZLE_128B);
  make_map(enc, &p.m_out, d_out, D_, S_, 64, 16, CU_TENSOR_MAP_SWIZZLE_128B);
  p.c = (const __nv_bfloat16*)d_in[10];
  p.wg = (const __nv_bfloat16*)d_in[7];
  p.wu = (const __nv_bfloat16*)d_in[8];
  p.w2 = (const __nv_bfloat16*)d_in[9];
  p.out = (uint8_t*)d_out;
  cudaFuncSetAttribute(fused_kernel, cudaFuncAttributeMaxDynamicSharedMemorySize, SMEM_BYTES);
  fused_kernel<<<128, 384, SMEM_BYTES, cudaStreamPerThread>>>((const __nv_bfloat16*)d_in[1], (const __nv_bfloat16*)d_in[2], (const __nv_bfloat16*)d_in[3],
                                                              (const __nv_bfloat16*)d_in[4], (const __nv_bfloat16*)d_in[5], ps, p);
}
```

```cpp
#include <cuda_runtime.h>
#include <cuda.h>
#include <cuda_bf16.h>
#include <cstdint>

namespace {

constexpr int S_ = 2048, D_ = 640, F_ = 1536;

__device__ __align__(1024) uint8_t g_s[10 << 20];
#define g_sync ((uint32_t*)(ps + (1 << 16)))
#define g_mod ((uint32_t*)(ps + (2 << 16)))
#define g_vv ((uint32_t*)(ps + (3 << 16)))
#define TIMOFF (4 << 16)
enum { Y_KV = 0, Y_Y = 20 * 32, Y_MOD = 25 * 32, Y_VV = 31 * 32, Y_EP = 7 };
enum { G_KV = 1, G_Y = 6, G_X = 11 };
enum { M_X = 0, M_O = 40, M_ST = 512 };
#define TSTAMP(i) do { } while (0)
#define TS3(k, i) do { } while (0)
#define TS2(i) do { } while (0)
#define TS 3
#define SCH 1
#define T_K1 1300
#define T_WM0 2000
#define T_K3 2600
#define T_S1 3300
#define T_K2 3600
#define T_K4 4300
#define T_S2 5000
#define T_S3 5350
#define T_S4 5700
#define T_Q 6050
#define T_WM1 7800
#define T_W0 8400
#define T_WM2 8900
#define T_S0 900
#define D_Q 54
#define D_WM 27
#define NE0 1
#define NE 2
#define STEP(kv, gv, cv, fa) ((kv + 1) | (gv + 1) << 3 | (cv + 1) << 5 | (fa + 1) << 8)
#define LNE 0
#define SCHED_E STEP(0, -1, -1, 1), STEP(2, -1, -1, -1), STEP(4, -1, 1, 3), STEP(-1, 1, 3, -1), STEP(-1, 2, -1, -1)
#define SCHED_L STEP(-1, -1, -1, 0), STEP(1, 0, -1, -1), STEP(3, -1, 0, 2), STEP(-1, -1, 2, 4), STEP(-1, -1, 4, -1)
#define PFW 0x71u
#define PF2 0xc80u
#define AH 2
#define PD 3
#define ROT 1
#define QD 5
#define PUBD 2
#define NPUB 1
#define LH 13
#define MX 0
#define EK 1
#define EY 1
#define EM 0
#define C4E 0
#define RP 2
#define TW 0
#define LEAD 2

struct Params {
  CUtensorMap m_k, m_kh, m_v, m_q, m_wm, m_w1, m_w2, m_out;
  const __nv_bfloat16 *c, *wg, *wu, *w2;
  uint8_t* out;
};
constexpr int NLD = 12;
__host__ __device__ constexpr uint32_t nth_load(int n) {
  const uint32_t when[NLD] = {T_K1 << 8 | 1, T_K2 << 8 | 2, T_K3 << 8 | 3, T_K4 << 8 | 4, T_S0 << 8 | 16, T_S1 << 8 | 17, T_S2 << 8 | 18, T_S3 << 8 | 19, T_S4 << 8 | 20,
                              T_Q << 8 | 21, T_WM0 << 8 | 32, T_WM1 << 8 | 33};
  for (int i = 0; i < NLD; i++) {
    int rank = 0;
    for (int k = 0; k < NLD; k++) rank += when[k] < when[i];
    if (rank == n) return when[i];
  }
  return 0;
}
__host__ __device__ constexpr uint64_t sched(int g) {
  const uint32_t t[2][5] = {{SCHED_L}, {SCHED_E}};
  uint64_t r = 0;
  for (int i = 0; i < 5; i++) r |= (uint64_t)(t[g][i] | (LNE == 10 * g + 10 + i) << 11) << 12 * i;
  return r;
}
template <int I> struct IC { static constexpr int v = I; };
template <int N, class F> __device__ __forceinline__ void unrolled(F f) {
  if constexpr (N > 0) { unrolled<N - 1>(f); f(IC<N - 1>()); }
}

constexpr uint32_t SLOT = 32768;
constexpr uint32_t U_RAW = 16, U_ODD = U_RAW + 4160, U_KV = 8448;
constexpr uint32_t O_WM = 2 * SLOT;
constexpr uint32_t O_SILU = O_WM + 40960;
constexpr uint32_t O_REG = 6 * SLOT;
constexpr uint32_t O_Y = O_REG + 20480;
constexpr uint32_t O_BP = O_Y + 4096;
constexpr uint32_t O_MA = O_BP + 4096;
constexpr uint32_t O_ST = O_BP + 7040;
constexpr uint32_t O_CS = O_ST + 1024;
constexpr uint32_t O_GB = O_CS + 640;
constexpr uint32_t O_LN = LNE ? O_GB : O_GB + 1280;
constexpr uint32_t O_EP = O_GB + 1280 + 64;
constexpr uint32_t O_SX = O_EP + 64;
constexpr uint32_t O_BAR = O_SX + 128;
constexpr uint32_t O_XT = O_BAR + 640;
constexpr uint32_t SMEM_BYTES = O_BAR + 1024;
static_assert(SMEM_BYTES <= 232448, "smem");
enum { B_W2E = 0, B_PL = 3, B_EMPTY = 8, B_LN = 14, B_VV = 15, B_YE = 16, B_FULL = 20, B_W2F = 26, B_HF = 33, B_KIN = 39, B_KV = 44,
       B_QIN = 49, B_WM = 50, B_CS = 51, B_X1 = 52, B_ST = 53, B_EP = 55, B_SSM = 56, B_PR = 63, B_OK = 68 };
__device__ __forceinline__ uint32_t kreg(int n) { return n < 4 ? (0x139b >> 4 * n & 15) << 14 : 5 * SLOT + 26624; }
__device__ __forceinline__ uint32_t voff(int n) { return n < 4 ? 6144 : -4 * SLOT; }
__device__ __forceinline__ uint32_t w2entry(int e) { return e == 6 ? 3 * SLOT + 24576 : e * SLOT; }
__device__ __forceinline__ int ocol(int ro, int i) { i += ROT * ((ro >> 1) & 3); return (ro & 1) * 320 + (i < 5 ? i : i - 5) * 64; }
__device__ __forceinline__ uint32_t bnd(int j) { return (0x720a8 >> 4 * j & 15) << 14; }
__device__ __forceinline__ uint32_t page(int g, int p) { return g << 19 | p << 12; }
__device__ __forceinline__ uint32_t tile(int rb, int x) { return page(G_X + (x >> 2), rb * 8 + (x & 3)); }

__device__ __forceinline__ uint32_t smem_u32(const void* p) { return (uint32_t)__cvta_generic_to_shared(p); }
__device__ __forceinline__ void mbar_init(uint32_t bar, uint32_t cnt) { asm volatile("mbarrier.init.shared::cta.b64 [%0], %1;" ::"r"(bar), "r"(cnt) : "memory"); }
__device__ __forceinline__ void mbar_expect(uint32_t bar, uint32_t bytes) { asm volatile("mbarrier.arrive.expect_tx.shared::cta.b64 _, [%0], %1;" ::"r"(bar), "r"(bytes) : "memory"); }
__device__ __forceinline__ void mbar_arrive(uint32_t bar) { asm volatile("mbarrier.arrive.shared::cta.b64 _, [%0];" ::"r"(bar) : "memory"); }
__device__ __forceinline__ void mbar_wait(uint32_t bar, uint32_t parity) {
  asm volatile("{\n .reg .pred p;\n .reg .u32 c;\n mov.u32 c, 0;\n LOOP:\n mbarrier.try_wait.parity.shared::cta.b64 p, [%0], %1;\n @p bra DONE;\n add.u32 c, c, 1;\n setp.lt.u32 p, c, 200000;\n @p bra LOOP;\n DONE:\n }" ::"r"(bar), "r"(parity) : "memory");
}
__device__ __forceinline__ void mbar_wait_cluster(uint32_t bar, uint32_t parity) {
  asm volatile("{\n .reg .pred p;\n .reg .u32 c;\n mov.u32 c, 0;\n LOOP:\n mbarrier.try_wait.parity.acquire.cluster.shared::cta.b64 p, [%0], %1;\n @p bra DONE;\n add.u32 c, c, 1;\n setp.lt.u32 p, c, 200000;\n @p bra LOOP;\n DONE:\n }" ::"r"(bar), "r"(parity) : "memory");
}
__device__ __forceinline__ bool mbar_test(uint32_t bar, uint32_t parity) {
  uint32_t r;
  asm volatile("{ .reg .pred p; mbarrier.test_wait.parity.shared::cta.b64 p, [%1], %2; selp.u32 %0, 1, 0, p; }" : "=r"(r) : "r"(bar), "r"(parity) : "memory");
  return r;
}
__device__ __forceinline__ bool mbar_try(uint32_t bar, uint32_t parity) {
  uint32_t r;
  asm volatile("{ .reg .pred p; mbarrier.try_wait.parity.shared::cta.b64 p, [%1], %2; selp.u32 %0, 1, 0, p; }" : "=r"(r) : "r"(bar), "r"(parity) : "memory");
  return r;
}
__device__ __forceinline__ uint32_t mapa(uint32_t a, uint32_t cta) { uint32_t r; asm("mapa.shared::cluster.u32 %0, %1, %2;" : "=r"(r) : "r"(a), "r"(cta)); return r; }
__device__ __forceinline__ void mbar_arrive_cl(uint32_t bar) { asm volatile("mbarrier.arrive.shared::cluster.b64 _, [%0];" ::"r"(bar) : "memory"); }
__device__ __forceinline__ bool elect() { uint32_t p; asm volatile("{ .reg .pred q; elect.sync _|q, 0xffffffff; selp.u32 %0, 1, 0, q; }" : "=r"(p)); return p; }
__device__ __forceinline__ uint32_t clk() { uint32_t c; asm volatile("mov.u32 %0, %%clock;" : "=r"(c)); return c; }
__device__ __forceinline__ uint32_t ldr(const uint32_t* p) { uint32_t v; asm volatile("ld.relaxed.gpu.global.u32 %0, [%1];" : "=r"(v) : "l"(p) : "memory"); return v; }
__device__ __forceinline__ uint4 ldr4(const uint32_t* p) {
  uint4 v; asm volatile("ld.relaxed.gpu.global.v4.u32 {%0,%1,%2,%3}, [%4];" : "=r"(v.x), "=r"(v.y), "=r"(v.z), "=r"(v.w) : "l"(p) : "memory"); return v;
}
__device__ __forceinline__ void poll_ge(const uint32_t* p, uint32_t target) {
  asm volatile("{\n .reg .pred p;\n .reg .u32 c, v;\n mov.u32 c, 0;\n LOOP:\n ld.relaxed.gpu.global.u32 v, [%0];\n sub.u32 v, v, %1;\n setp.ge.s32 p, v, 0;\n @p bra DONE;\n add.u32 c, c, 1;\n setp.lt.u32 p, c, 100000;\n @p bra LOOP;\n DONE:\n }" ::"l"(p), "r"(target) : "memory");
}
__device__ __forceinline__ void poll_lane(uint32_t& v, const void* p, uint32_t target, int l) {
  for (int it = 0; !((__ballot_sync(0xffffffffu, (int)(v - target) >= 0) >> l) & 1) && it < 100000; it++) v = ldr((const uint32_t*)p);
}
__device__ __forceinline__ void hint_add(uint32_t* p) { asm volatile("red.relaxed.gpu.global.add.u32 [%0], 1;" ::"l"(p) : "memory"); }
__device__ __forceinline__ void refetch(const void* g, uint32_t off, uint32_t a, uint32_t tag) {
  asm volatile("{\n .reg .pred p;\n .reg .u32 c, v, x, y, z;\n .reg .u64 q;\n mov.u32 c, 0;\n cvt.u64.u32 q, %1;\n add.u64 q, q, %0;\n"
               " LOOP:\n ld.relaxed.gpu.global.u32 v, [q];\n xor.b32 v, v, %3;\n and.b32 v, v, 1;\n setp.eq.u32 p, v, 0;\n @p bra DONE;\n add.u32 c, c, 1;\n setp.lt.u32 p, c, 100000;\n @p bra LOOP;\n"
               " DONE:\n ld.relaxed.gpu.global.v4.u32 {v, x, y, z}, [%0];\n st.shared.v4.u32 [%2], {v, x, y, z};\n ld.relaxed.gpu.global.v4.u32 {v, x, y, z}, [%0+16];\n xor.b32 c, %2, 16;\n"
               " st.shared.v4.u32 [c], {v, x, y, z};\n fence.proxy.async.shared::cta;\n }" ::"l"(g), "r"(off), "r"(a), "r"(tag) : "memory");
}
__device__ __forceinline__ void refetch16(const void* g, uint32_t a, uint32_t tag) {
  asm volatile("{\n .reg .pred p;\n .reg .u32 c, t, v, x, y, z;\n mov.u32 c, 0;\n"
               " LOOP:\n ld.relaxed.gpu.global.v4.u32 {v, x, y, z}, [%0];\n xor.b32 t, v, %2;\n and.b32 t, t, 1;\n setp.eq.u32 p, t, 0;\n @p bra DONE;\n add.u32 c, c, 1;\n setp.lt.u32 p, c, 100000;\n @p bra LOOP;\n"
               " DONE:\n st.shared.v4.u32 [%1], {v, x, y, z};\n }" ::"l"(g), "r"(a), "r"(tag) : "memory");
}
__device__ __forceinline__ uint2 ldr2(const uint32_t* p) {
  uint2 v; asm volatile("ld.relaxed.gpu.global.v2.u32 {%0,%1}, [%2];" : "=r"(v.x), "=r"(v.y) : "l"(p) : "memory"); return v;
}
__device__ __forceinline__ uint32_t settag(uint32_t x, uint32_t m, uint32_t t) { return (x & ~m) | (t & m); }
__device__ __forceinline__ void stg128(void* p, uint32_t x, uint32_t y, uint32_t z, uint32_t w) {
  asm volatile("st.global.v4.u32 [%0], {%1,%2,%3,%4};" ::"l"(p), "r"(x), "r"(y), "r"(z), "r"(w) : "memory");
}
__device__ __forceinline__ void cpa16(uint32_t dst, const void* src, uint32_t n) { asm volatile("cp.async.cg.shared.global [%0], [%1], 16, %2;" ::"r"(dst), "l"(src), "r"(n) : "memory"); }
__device__ __forceinline__ void tma3d(uint32_t dst, const CUtensorMap* m, int x, int y, int z, uint32_t bar) {
  asm volatile("cp.async.bulk.tensor.3d.shared::cluster.global.mbarrier::complete_tx::bytes [%0], [%1, {%3, %4, %5}], [%2];" ::"r"(dst), "l"(m), "r"(bar), "r"(x), "r"(y), "r"(z) : "memory");
}
__device__ __forceinline__ void tma4d(uint32_t dst, const CUtensorMap* m, int x, int y, int z, int u, uint32_t bar) {
  asm volatile("cp.async.bulk.tensor.4d.shared::cluster.global.mbarrier::complete_tx::bytes [%0], [%1, {%3, %4, %5, %6}], [%2];" ::"r"(dst), "l"(m), "r"(bar), "r"(x), "r"(y), "r"(z), "r"(u) : "memory");
}
__device__ __forceinline__ void bulk_st(void* dst, uint32_t src, uint32_t bytes) {
  asm volatile("cp.async.bulk.global.shared::cta.bulk_group [%0], [%1], %2;" ::"l"(dst), "r"(src), "r"(bytes) : "memory");
}
__device__ __forceinline__ void bulk_pf(const void* src, uint32_t bytes) { asm volatile("cp.async.bulk.prefetch.L2.global [%0], %1;" ::"l"(src), "r"(bytes) : "memory"); }
__device__ __forceinline__ void tma2d(uint32_t dst, const CUtensorMap* m, int x, int y, uint32_t bar) {
  asm volatile("cp.async.bulk.tensor.2d.shared::cluster.global.mbarrier::complete_tx::bytes [%0], [%1, {%3, %4}], [%2];" ::"r"(dst), "l"(m), "r"(bar), "r"(x), "r"(y) : "memory");
}
__device__ __forceinline__ void tma2d_add(const CUtensorMap* m, uint32_t src, int x, int y) {
  asm volatile("cp.reduce.async.bulk.tensor.2d.global.shared::cta.add.tile.bulk_group [%0, {%2, %3}], [%1];" ::"l"(m), "r"(src), "r"(x), "r"(y) : "memory");
}
__device__ __forceinline__ void bulk_ld(uint32_t dst, const void* src, uint32_t bytes, uint32_t bar) {
  asm volatile("cp.async.bulk.shared::cluster.global.mbarrier::complete_tx::bytes [%0], [%1], %2, [%3];" ::"r"(dst), "l"(src), "r"(bytes), "r"(bar) : "memory");
}
__device__ __forceinline__ void bulk_commit() { asm volatile("cp.async.bulk.commit_group;" ::: "memory"); }
template <int N> __device__ __forceinline__ void bulk_wait() { asm volatile("cp.async.bulk.wait_group %0;" ::"n"(N) : "memory"); }
template <int N> __device__ __forceinline__ void bulk_wait_read() { asm volatile("cp.async.bulk.wait_group.read %0;" ::"n"(N) : "memory"); }
__device__ __forceinline__ void fence_async_smem() { asm volatile("fence.proxy.async.shared::cta;" ::: "memory"); }
__device__ __forceinline__ void bar_sync(int id, int n) { asm volatile("bar.sync %0, %1;" ::"r"(id), "r"(n) : "memory"); }
__device__ __forceinline__ void bar_arrive(int id, int n) { asm volatile("bar.arrive %0, %1;" ::"r"(id), "r"(n) : "memory"); }
__device__ __forceinline__ void wg_fence() { asm volatile("wgmma.fence.sync.aligned;" ::: "memory"); }
__device__ __forceinline__ void wg_commit() { asm volatile("wgmma.commit_group.sync.aligned;" ::: "memory"); }
template <int N> __device__ __forceinline__ void wg_wait() { asm volatile("wgmma.wait_group.sync.aligned %0;" ::"n"(N) : "memory"); }
__device__ __forceinline__ void ldsm4(uint32_t a, uint32_t& r0, uint32_t& r1, uint32_t& r2, uint32_t& r3) {
  asm volatile("ldmatrix.sync.aligned.m8n8.x4.shared.b16 {%0,%1,%2,%3}, [%4];" : "=r"(r0), "=r"(r1), "=r"(r2), "=r"(r3) : "r"(a) : "memory");
}
__device__ __forceinline__ void ldsm4t(uint32_t a, uint32_t& r0, uint32_t& r1, uint32_t& r2, uint32_t& r3) {
  asm volatile("ldmatrix.sync.aligned.m8n8.x4.trans.shared.b16 {%0,%1,%2,%3}, [%4];" : "=r"(r0), "=r"(r1), "=r"(r2), "=r"(r3) : "r"(a) : "memory");
}
__device__ __forceinline__ void stsm4t(uint32_t a, uint32_t r0, uint32_t r1, uint32_t r2, uint32_t r3) {
  asm volatile("stmatrix.sync.aligned.m8n8.x4.trans.shared.b16 [%0], {%1,%2,%3,%4};" ::"r"(a), "r"(r0), "r"(r1), "r"(r2), "r"(r3) : "memory");
}
__device__ __forceinline__ void stsm4(uint32_t a, uint32_t r0, uint32_t r1, uint32_t r2, uint32_t r3) {
  asm volatile("stmatrix.sync.aligned.m8n8.x4.shared.b16 [%0], {%1,%2,%3,%4};" ::"r"(a), "r"(r0), "r"(r1), "r"(r2), "r"(r3) : "memory");
}
__device__ __forceinline__ uint32_t lds32(uint32_t a) { uint32_t v; asm volatile("ld.shared.u32 %0, [%1];" : "=r"(v) : "r"(a) : "memory"); return v; }
__device__ __forceinline__ uint4 lds128(uint32_t a) { uint4 v; asm volatile("ld.shared.v4.u32 {%0,%1,%2,%3}, [%4];" : "=r"(v.x), "=r"(v.y), "=r"(v.z), "=r"(v.w) : "r"(a) : "memory"); return v; }
__device__ __forceinline__ float4 lds128f(uint32_t a) { float4 v; asm volatile("ld.shared.v4.f32 {%0,%1,%2,%3}, [%4];" : "=f"(v.x), "=f"(v.y), "=f"(v.z), "=f"(v.w) : "r"(a) : "memory"); return v; }
__device__ __forceinline__ float2 lds64f(uint32_t a) { float2 v; asm volatile("ld.shared.v2.f32 {%0,%1}, [%2];" : "=f"(v.x), "=f"(v.y) : "r"(a) : "memory"); return v; }
__device__ __forceinline__ void sts32(uint32_t a, uint32_t v) { asm volatile("st.shared.u32 [%0], %1;" ::"r"(a), "r"(v) : "memory"); }
__device__ __forceinline__ void sts64(uint32_t a, uint32_t x, uint32_t y) { asm volatile("st.shared.v2.u32 [%0], {%1,%2};" ::"r"(a), "r"(x), "r"(y) : "memory"); }
__device__ __forceinline__ void sts128(uint32_t a, uint32_t x, uint32_t y, uint32_t z, uint32_t w) { asm volatile("st.shared.v4.u32 [%0], {%1,%2,%3,%4};" ::"r"(a), "r"(x), "r"(y), "r"(z), "r"(w) : "memory"); }
__device__ __forceinline__ void sts16(uint32_t a, uint16_t v) { asm volatile("st.shared.u16 [%0], %1;" ::"r"(a), "h"(v) : "memory"); }
__device__ __forceinline__ uint32_t prmt(uint32_t a, uint32_t b, uint32_t s) { uint32_t r; asm("prmt.b32 %0, %1, %2, %3;" : "=r"(r) : "r"(a), "r"(b), "r"(s)); return r; }
__device__ __forceinline__ uint32_t hfma2(uint32_t a, uint32_t b, uint32_t c) { uint32_t r; asm("fma.rn.bf16x2 %0, %1, %2, %3;" : "=r"(r) : "r"(a), "r"(b), "r"(c)); return r; }
__device__ __forceinline__ uint32_t hfma2lh(uint32_t a, uint32_t l) {
  uint32_t r;
  asm("{ .reg .b16 x, y; .reg .b32 u, v; mov.b32 {x, y}, %2; mov.b32 u, {x, x}; mov.b32 v, {y, y}; fma.rn.bf16x2 %0, %1, u, v; }" : "=r"(r) : "r"(a), "r"(l));
  return r;
}
__device__ __forceinline__ uint32_t addu(uint32_t a, uint32_t u) { uint32_t r; asm("add.u32 %0, %1, %2;" : "=r"(r) : "r"(a), "r"(u)); return r; }
__device__ __forceinline__ uint32_t tag0(uint32_t x, uint32_t t) { uint32_t r; asm("lop3.b32 %0, %1, 1, %2, 0xb8;" : "=r"(r) : "r"(x), "r"(t)); return r; }
__device__ __forceinline__ void keep(uint32_t& x) { x = __shfl_xor_sync(0xffffffffu, x, 0); }
__device__ __forceinline__ uint32_t hmul2(uint32_t a, uint32_t b) { uint32_t r; asm("mul.rn.bf16x2 %0, %1, %2;" : "=r"(r) : "r"(a), "r"(b)); return r; }
__device__ __forceinline__ uint32_t pack2(float lo, float hi) { uint32_t r; asm("cvt.rn.bf16x2.f32 %0, %1, %2;" : "=r"(r) : "f"(hi), "f"(lo)); return r; }
__device__ __forceinline__ float blo(uint32_t v) { return __uint_as_float(v << 16); }
__device__ __forceinline__ float bhi(uint32_t v) { return __uint_as_float(v & 0xffff0000u); }
__device__ __forceinline__ uint32_t hadd2(uint32_t a, uint32_t b) { uint32_t r; asm("add.rn.bf16x2 %0, %1, %2;" : "=r"(r) : "r"(a), "r"(b)); return r; }
__device__ __forceinline__ void str(uint32_t* p, uint32_t v) { asm volatile("st.relaxed.gpu.global.u32 [%0], %1;" ::"l"(p), "r"(v) : "memory"); }
__device__ __forceinline__ uint32_t tagf(float x, uint32_t tag) { return (__float_as_uint(x) & ~3u) | (tag & 3); }
template <int N> __device__ __forceinline__ float4 gather4(const uint32_t* p, int stride, uint32_t tag) {
  uint4 v[N];
  int it = 0;
  uint32_t bad;
  do {
#pragma unroll
    for (int i = 0; i < N; i++) v[i] = ldr4(p + i * stride);
    bad = 0;
#pragma unroll
    for (int i = 0; i < N; i++) bad |= (v[i].x ^ tag) | (v[i].y ^ tag) | (v[i].z ^ tag) | (v[i].w ^ tag);
  } while ((bad & 3) && ++it < 100000);
  float4 s = make_float4(__uint_as_float(v[0].x), __uint_as_float(v[0].y), __uint_as_float(v[0].z), __uint_as_float(v[0].w));
#pragma unroll
  for (int i = 1; i < N; i++) { s.x += __uint_as_float(v[i].x); s.y += __uint_as_float(v[i].y); s.z += __uint_as_float(v[i].z); s.w += __uint_as_float(v[i].w); }
  return s;
}
__device__ __forceinline__ float rbf(float x) { return blo(pack2(x, 0.f)); }
__device__ __forceinline__ uint64_t mkdesc(uint32_t addr, uint32_t lbo, uint32_t sbo, uint32_t swz) {
  return (uint64_t)((addr & 0x3FFFF) >> 4) | ((uint64_t)(lbo >> 4) << 16) | ((uint64_t)(sbo >> 4) << 32) | ((uint64_t)swz << 62);
}
template <int N> __device__ __forceinline__ void regfence(float* d) {
#pragma unroll
  for (int i = 0; i < N; i++) asm volatile("" : "+f"(d[i])::"memory");
}

__device__ __forceinline__ void wgmma_rs_32_0(float* d, uint32_t a0, uint32_t a1, uint32_t a2, uint32_t a3, uint64_t db, int sd) {
  asm volatile("{ .reg .pred p; setp.ne.b32 p, %21, 0; wgmma.mma_async.sync.aligned.m64n32k16.f32.bf16.bf16 {%0,%1,%2,%3,%4,%5,%6,%7,%8,%9,%10,%11,%12,%13,%14,%15}, {%16,%17,%18,%19}, %20, p, 1, 1, 0; }"
   : "+f"(d[0]), "+f"(d[1]), "+f"(d[2]), "+f"(d[3]), "+f"(d[4]), "+f"(d[5]), "+f"(d[6]), "+f"(d[7]), "+f"(d[8]), "+f"(d[9]), "+f"(d[10]), "+f"(d[11]), "+f"(d[12]), "+f"(d[13]), "+f"(d[14]), "+f"(d[15]) : "r"(a0), "r"(a1), "r"(a2), "r"(a3), "l"(db), "r"(sd));
}
__device__ __forceinline__ void wgmma_rs_64_1(float* d, uint32_t a0, uint32_t a1, uint32_t a2, uint32_t a3, uint64_t db, int sd) {
  asm volatile("{ .reg .pred p; setp.ne.b32 p, %37, 0; wgmma.mma_async.sync.aligned.m64n64k16.f32.bf16.bf16 {%0,%1,%2,%3,%4,%5,%6,%7,%8,%9,%10,%11,%12,%13,%14,%15,%16,%17,%18,%19,%20,%21,%22,%23,%24,%25,%26,%27,%28,%29,%30,%31}, {%32,%33,%34,%35}, %36, p, 1, 1, 1; }"
   : "+f"(d[0]), "+f"(d[1]), "+f"(d[2]), "+f"(d[3]), "+f"(d[4]), "+f"(d[5]), "+f"(d[6]), "+f"(d[7]), "+f"(d[8]), "+f"(d[9]), "+f"(d[10]), "+f"(d[11]), "+f"(d[12]), "+f"(d[13]), "+f"(d[14]), "+f"(d[15]), "+f"(d[16]), "+f"(d[17]), "+f"(d[18]), "+f"(d[19]), "+f"(d[20]), "+f"(d[21]), "+f"(d[22]), "+f"(d[23]), "+f"(d[24]), "+f"(d[25]), "+f"(d[26]), "+f"(d[27]), "+f"(d[28]), "+f"(d[29]), "+f"(d[30]), "+f"(d[31]) : "r"(a0), "r"(a1), "r"(a2), "r"(a3), "l"(db), "r"(sd));
}
__device__ __forceinline__ void wgmma_rs_192_0(float* d, uint32_t a0, uint32_t a1, uint32_t a2, uint32_t a3, uint64_t db, int sd) {
  asm volatile("{ .reg .pred p; setp.ne.b32 p, %101, 0; wgmma.mma_async.sync.aligned.m64n192k16.f32.bf16.bf16 {%0,%1,%2,%3,%4,%5,%6,%7,%8,%9,%10,%11,%12,%13,%14,%15,%16,%17,%18,%19,%20,%21,%22,%23,%24,%25,%26,%27,%28,%29,%30,%31,%32,%33,%34,%35,%36,%37,%38,%39,%40,%41,%42,%43,%44,%45,%46,%47,%48,%49,%50,%51,%52,%53,%54,%55,%56,%57,%58,%59,%60,%61,%62,%63,%64,%65,%66,%67,%68,%69,%70,%71,%72,%73,%74,%75,%76,%77,%78,%79,%80,%81,%82,%83,%84,%85,%86,%87,%88,%89,%90,%91,%92,%93,%94,%95}, {%96,%97,%98,%99}, %100, p, 1, 1, 0; }"
   : "+f"(d[0]), "+f"(d[1]), "+f"(d[2]), "+f"(d[3]), "+f"(d[4]), "+f"(d[5]), "+f"(d[6]), "+f"(d[7]), "+f"(d[8]), "+f"(d[9]), "+f"(d[10]), "+f"(d[11]), "+f"(d[12]), "+f"(d[13]), "+f"(d[14]), "+f"(d[15]), "+f"(d[16]), "+f"(d[17]), "+f"(d[18]), "+f"(d[19]), "+f"(d[20]), "+f"(d[21]), "+f"(d[22]), "+f"(d[23]), "+f"(d[24]), "+f"(d[25]), "+f"(d[26]), "+f"(d[27]), "+f"(d[28]), "+f"(d[29]), "+f"(d[30]), "+f"(d[31]), "+f"(d[32]), "+f"(d[33]), "+f"(d[34]), "+f"(d[35]), "+f"(d[36]), "+f"(d[37]), "+f"(d[38]), "+f"(d[39]), "+f"(d[40]), "+f"(d[41]), "+f"(d[42]), "+f"(d[43]), "+f"(d[44]), "+f"(d[45]), "+f"(d[46]), "+f"(d[47]), "+f"(d[48]), "+f"(d[49]), "+f"(d[50]), "+f"(d[51]), "+f"(d[52]), "+f"(d[53]), "+f"(d[54]), "+f"(d[55]), "+f"(d[56]), "+f"(d[57]), "+f"(d[58]), "+f"(d[59]), "+f"(d[60]), "+f"(d[61]), "+f"(d[62]), "+f"(d[63]), "+f"(d[64]), "+f"(d[65]), "+f"(d[66]), "+f"(d[67]), "+f"(d[68]), "+f"(d[69]), "+f"(d[70]), "+f"(d[71]), "+f"(d[72]), "+f"(d[73]), "+f"(d[74]), "+f"(d[75]), "+f"(d[76]), "+f"(d[77]), "+f"(d[78]), "+f"(d[79]), "+f"(d[80]), "+f"(d[81]), "+f"(d[82]), "+f"(d[83]), "+f"(d[84]), "+f"(d[85]), "+f"(d[86]), "+f"(d[87]), "+f"(d[88]), "+f"(d[89]), "+f"(d[90]), "+f"(d[91]), "+f"(d[92]), "+f"(d[93]), "+f"(d[94]), "+f"(d[95]) : "r"(a0), "r"(a1), "r"(a2), "r"(a3), "l"(db), "r"(sd));
}
__device__ __forceinline__ void wgmma_ss_8_00(float* d, uint64_t da, uint64_t db, int sd) {
  asm volatile("{ .reg .pred p; setp.ne.b32 p, %6, 0; wgmma.mma_async.sync.aligned.m64n8k16.f32.bf16.bf16 {%0,%1,%2,%3}, %4, %5, p, 1, 1, 0, 0; }"
   : "+f"(d[0]), "+f"(d[1]), "+f"(d[2]), "+f"(d[3]) : "l"(da), "l"(db), "r"(sd));
}
__device__ __forceinline__ void wgmma_ss_8_10(float* d, uint64_t da, uint64_t db, int sd) {
  asm volatile("{ .reg .pred p; setp.ne.b32 p, %6, 0; wgmma.mma_async.sync.aligned.m64n8k16.f32.bf16.bf16 {%0,%1,%2,%3}, %4, %5, p, 1, 1, 1, 0; }"
   : "+f"(d[0]), "+f"(d[1]), "+f"(d[2]), "+f"(d[3]) : "l"(da), "l"(db), "r"(sd));
}
__device__ __forceinline__ void wgmma_ss_64_00(float* d, uint64_t da, uint64_t db, int sd) {
  asm volatile("{ .reg .pred p; setp.ne.b32 p, %34, 0; wgmma.mma_async.sync.aligned.m64n64k16.f32.bf16.bf16 {%0,%1,%2,%3,%4,%5,%6,%7,%8,%9,%10,%11,%12,%13,%14,%15,%16,%17,%18,%19,%20,%21,%22,%23,%24,%25,%26,%27,%28,%29,%30,%31}, %32, %33, p, 1, 1, 0, 0; }"
   : "+f"(d[0]), "+f"(d[1]), "+f"(d[2]), "+f"(d[3]), "+f"(d[4]), "+f"(d[5]), "+f"(d[6]), "+f"(d[7]), "+f"(d[8]), "+f"(d[9]), "+f"(d[10]), "+f"(d[11]), "+f"(d[12]), "+f"(d[13]), "+f"(d[14]), "+f"(d[15]), "+f"(d[16]), "+f"(d[17]), "+f"(d[18]), "+f"(d[19]), "+f"(d[20]), "+f"(d[21]), "+f"(d[22]), "+f"(d[23]), "+f"(d[24]), "+f"(d[25]), "+f"(d[26]), "+f"(d[27]), "+f"(d[28]), "+f"(d[29]), "+f"(d[30]), "+f"(d[31]) : "l"(da), "l"(db), "r"(sd));
}
__device__ __forceinline__ void wgmma_ss_192_01(float* d, uint64_t da, uint64_t db, int sd) {
  asm volatile("{ .reg .pred p; setp.ne.b32 p, %98, 0; wgmma.mma_async.sync.aligned.m64n192k16.f32.bf16.bf16 {%0,%1,%2,%3,%4,%5,%6,%7,%8,%9,%10,%11,%12,%13,%14,%15,%16,%17,%18,%19,%20,%21,%22,%23,%24,%25,%26,%27,%28,%29,%30,%31,%32,%33,%34,%35,%36,%37,%38,%39,%40,%41,%42,%43,%44,%45,%46,%47,%48,%49,%50,%51,%52,%53,%54,%55,%56,%57,%58,%59,%60,%61,%62,%63,%64,%65,%66,%67,%68,%69,%70,%71,%72,%73,%74,%75,%76,%77,%78,%79,%80,%81,%82,%83,%84,%85,%86,%87,%88,%89,%90,%91,%92,%93,%94,%95}, %96, %97, p, 1, 1, 0, 1; }"
   : "+f"(d[0]), "+f"(d[1]), "+f"(d[2]), "+f"(d[3]), "+f"(d[4]), "+f"(d[5]), "+f"(d[6]), "+f"(d[7]), "+f"(d[8]), "+f"(d[9]), "+f"(d[10]), "+f"(d[11]), "+f"(d[12]), "+f"(d[13]), "+f"(d[14]), "+f"(d[15]), "+f"(d[16]), "+f"(d[17]), "+f"(d[18]), "+f"(d[19]), "+f"(d[20]), "+f"(d[21]), "+f"(d[22]), "+f"(d[23]), "+f"(d[24]), "+f"(d[25]), "+f"(d[26]), "+f"(d[27]), "+f"(d[28]), "+f"(d[29]), "+f"(d[30]), "+f"(d[31]), "+f"(d[32]), "+f"(d[33]), "+f"(d[34]), "+f"(d[35]), "+f"(d[36]), "+f"(d[37]), "+f"(d[38]), "+f"(d[39]), "+f"(d[40]), "+f"(d[41]), "+f"(d[42]), "+f"(d[43]), "+f"(d[44]), "+f"(d[45]), "+f"(d[46]), "+f"(d[47]), "+f"(d[48]), "+f"(d[49]), "+f"(d[50]), "+f"(d[51]), "+f"(d[52]), "+f"(d[53]), "+f"(d[54]), "+f"(d[55]), "+f"(d[56]), "+f"(d[57]), "+f"(d[58]), "+f"(d[59]), "+f"(d[60]), "+f"(d[61]), "+f"(d[62]), "+f"(d[63]), "+f"(d[64]), "+f"(d[65]), "+f"(d[66]), "+f"(d[67]), "+f"(d[68]), "+f"(d[69]), "+f"(d[70]), "+f"(d[71]), "+f"(d[72]), "+f"(d[73]), "+f"(d[74]), "+f"(d[75]), "+f"(d[76]), "+f"(d[77]), "+f"(d[78]), "+f"(d[79]), "+f"(d[80]), "+f"(d[81]), "+f"(d[82]), "+f"(d[83]), "+f"(d[84]), "+f"(d[85]), "+f"(d[86]), "+f"(d[87]), "+f"(d[88]), "+f"(d[89]), "+f"(d[90]), "+f"(d[91]), "+f"(d[92]), "+f"(d[93]), "+f"(d[94]), "+f"(d[95]) : "l"(da), "l"(db), "r"(sd));
}

#define HINT(x) x

__global__ void __cluster_dims__(2, 1, 1) __launch_bounds__(384, 1) fused_kernel(const __nv_bfloat16* __restrict__ pk, const __nv_bfloat16* __restrict__ pv,
    const __nv_bfloat16* __restrict__ pshift, const __nv_bfloat16* __restrict__ pssm, const __nv_bfloat16* __restrict__ pD, uint8_t* ps, const __grid_constant__ Params p) {
  extern __shared__ __align__(1024) uint8_t smem_raw[];
  const uint32_t t_start = clk();
  const uint32_t sb = smem_u32(smem_raw);
  const uint32_t bars = sb + O_BAR;
  const int tid = threadIdx.x, lane = tid & 31;
  const int warp = __shfl_sync(0xffffffffu, tid >> 5, 0);
  const int b = blockIdx.x, kh = b & 1;
  const int part = b / 20, grp = part < NE0 ? 0 : part < NE ? 1 : 2;
  auto loadwm = [&]() {
    const int x = b % 20, col = part < 5 ? (x >> 2) * D_ + part * 128 + (x & 3) * 32 : 5 * D_ + x * 32;
    mbar_expect(bars + 8 * B_WM, 40960);
    tma3d(sb + O_WM, &p.m_wm, col, 0, 0, bars + 8 * B_WM);
  };
  auto BAR = [&](int i) { return bars + 8 * i; };
#define ROLE const int rb = b >> 3, fs = b & 7, vr = min(rb, 14) / 3, vt = min(rb, 14) % 3; \
  const uint32_t ord = vr == 3 ? 0x42310 : vr == 4 ? 0x32410 : 0x43210; uint8_t* const misc = ps + rb * 4096; \
  (void)fs; (void)vt; (void)ord; (void)misc
  if (tid == 0) TSTAMP(63);
#define EPLOAD const uint32_t e0 = ldr(g_sync + Y_EP + b * 32 + (lane & (uint32_t)(uintptr_t)ps))
#define EPOCH const uint32_t ep = __shfl_sync(0xffffffffu, e0, 0) + 1
#define EPOCHU const uint32_t ep = __shfl_sync(0xffffffffu, lds32(sb + O_EP), 0)

  if (warp < 4) {
    asm volatile("setmaxnreg.dec.sync.aligned.u32 40;");
    const int hw = warp - 2;
    if (warp == 0) {
      EPLOAD;
      bar_sync(1, 384);
      asm volatile("barrier.cluster.arrive.relaxed.aligned;" ::: "memory");
      EPOCH;
      if (lane == 0) { sts32(sb + O_EP, ep); mbar_arrive(BAR(B_EP)); TSTAMP(0); }
      __syncwarp();
      ROLE;
      {
        const uint32_t* f = g_sync + Y_KV + (min(lane, 4) * 4 + (b >> 5)) * 32;
        const uint32_t tw = lane != 5 ? T_W0 : b * D_WM + T_WM2 - 20 * NE * D_WM;
        uint32_t pend = b < 120 && grp == 2 ? 127 : 95;
        int it = 0;
        do {
          uint32_t v = ep * 32;
          HINT(if (lane < 5 && (pend & 31)) v = ldr(f));
          uint32_t m = __ballot_sync(0xffffffffu, (lane < 5 ? (int)(v - ep * 32) >= 0 : clk() - t_start >= tw) || ++it > 100000) & pend;
          pend &= ~m;
          for (; m; m &= m - 1) {
            const int j = __ffs(m) - 1;
            if (elect()) {
              if (j < 5) {
                TSTAMP(2 + j);
                mbar_expect(BAR(B_KV + j), 4096);
                bulk_ld(sb + bnd(j) + U_KV, ps + page(G_KV + j, b), 4096, BAR(B_KV + j));
              } else if (j == 5) {
                loadwm();
                TSTAMP(109);
              } else {
                bulk_pf((kh ? p.wu : p.wg) + (b >> 1) * 2 * F_, 6144);
                TSTAMP(108);
              }
            }
          }
        } while (pend);
      }
      {
        const int rl = (ord >> (min(lane, 19) & 28)) & 7;
        const uint32_t* const cnt = (const uint32_t*)(misc + M_X) + rl * 2 + ((min(lane, 19) >> 1) & 1);
        sts32(sb + O_XT + lane * 4, tile(rb, rl * 4 + (lane & 3)));
        __syncwarp();
        uint32_t known = 0;
        int slot = 4;
#pragma unroll 1
        for (int i = -AH; i < 20; i++) {
          const int s = i < 0 ? i + AH : i, rd = (ord >> (s & 28)) & 7;
          const uint32_t dst = sb + slot * SLOT, full = BAR(B_FULL + slot);
          const uint8_t* const xs = ps + (tile(rb, rd * 4 + (s & 3)) + kh * 16384);
          auto loadx = [&]() {
            asm volatile("{ .reg .pred p; elect.sync _|p, 0xffffffff;\n @p cp.async.bulk.shared::cluster.global.mbarrier::complete_tx::bytes.multicast::cluster [%0], [%1], 4096, [%2], %3; }"
                         ::"r"(dst + 24576 + kh * 4096), "l"(xs), "r"(full), "h"((uint16_t)3) : "memory");
          };
          auto loadw = [&]() {
            mbar_wait(full + 8 * (B_EMPTY - B_FULL), (0xc0fc0 >> s) & 1);
            asm volatile("{ .reg .pred p; elect.sync _|p, 0xffffffff;\n @p mbarrier.arrive.expect_tx.shared::cta.b64 _, [%2], 32768;\n"
                         " @p cp.async.bulk.tensor.4d.shared::cluster.global.mbarrier::complete_tx::bytes [%0], [%1, {0, %3, %4, 0}], [%2]; }"
                         ::"r"(dst), "l"(&p.m_w1), "r"(full), "r"(rd * 128 + (s & 3) * 32), "r"(fs * 3) : "memory");
          };
          uint32_t v = ep * 16 - 1;
          HINT(if (i >= 0 && (~known >> s) & PD) v = ldr(cnt));
          if (i >= AH && (known >> s) & 1) {
            loadw();
            loadx();
          } else {
            if ((uint32_t)i >= AH) loadw();
            if (lane == 0) TS3(2, s);
            if (i >= 0) {
              HINT(if (!((known >> s) & 1)) poll_lane(v, cnt, ep * 16, s));
              loadx();
            }
          }
          if (i >= 0 && lane == 0) TS3(3, s);
          if (((PFW | PF2) << AH >> (i + AH)) & 1) {
            const int k = __popc((PFW | PF2) << (31 - s));
            if (elect()) bulk_pf(k < 5 ? (kh ? p.wu : p.wg) + (k * 128 + (b >> 1) * 2) * F_ : p.w2 + b * 7680 + (k - 5) * 2560, k < 5 ? 6144 : 5120);
          }
          if (lane == 0 && i == -1) TSTAMP(10);
          if (lane == 0 && i == 0) TSTAMP(19);
          if (lane == 0 && i == 16) TSTAMP(1);
          slot = i == -1 ? 4 : slot == 5 ? 0 : slot + 1;
          known |= __ballot_sync(0xffffffffu, (int)(v - ep * 16) >= 0);
        }
      }
      __syncwarp();
      asm volatile("barrier.cluster.wait.aligned;" ::: "memory");
#pragma unroll 1
      for (int s = 0; s < 10; s++) {
        const int e = s < 7 ? s : s - 7;
        const uint32_t d = sb + w2entry(e), st = e == 6 ? SLOT : 8192;
        const int k0 = (fs ^ (s < 4 ? s >> 1 : s & 1)) * 192, c0 = ocol(b, s < 4 ? s & 1 : s >> 1);
        mbar_wait(BAR(s >= 7 ? B_W2E + e : B_EMPTY + min(s, 5)), s < 4);
        if (elect()) {
          mbar_expect(BAR(B_W2F + e), 24576);
#pragma unroll
          for (int i = 0; i < 3; i++) tma2d(d + i * st, &p.m_w2, c0, k0 + i * 64, BAR(B_W2F + e));
        }
      }
    } else {
      if (warp == 1) {
        bar_sync(1, 384);
        asm volatile("barrier.cluster.arrive.relaxed.aligned;" ::: "memory");
        if (lane == 0) TSTAMP(112);
        if (lane < 5) asm volatile("mbarrier.expect_tx.relaxed.cta.shared::cta.b64 [%0], 4096;" ::"r"(BAR(B_PR + lane)) : "memory");
        unrolled<NLD>([&](auto I) {
          constexpr uint32_t e = nth_load(I.v), n = e & 15, kind = (e >> 4) & 15;
          while (clk() - t_start < (e >> 8) + (n == 5 ? (b >> 2) * D_Q : 0)) {}
          if (elect()) {
            if constexpr (kind == 0) {
              const uint32_t d = sb + kreg(n), bar = BAR(B_KIN + n);
              const int ch = n * 128 + (b & 3) * 32, tg = (b >> 2) * 8;
              mbar_expect(bar, 9984);
              tma3d(d, &p.m_k, ch, tg, 0, bar);
              tma3d(d + voff(n), &p.m_v, ch, tg, 0, bar);
              tma3d(d + 4096, &p.m_kh, ch, tg - 1, 5, bar);
              bulk_ld(d + 5632, pshift + ch * 4, 256, bar);
            } else if constexpr (kind == 2) {
              if (grp == n) loadwm();
            } else if constexpr (kind == 1 && n < 5) {
              mbar_expect(BAR(B_SSM + n), 4096);
              bulk_ld(sb + bnd(n) + U_RAW, pssm + (size_t)(n * 128 + b) * S_, 4096, BAR(B_SSM + n));
            } else {
              mbar_expect(BAR(B_QIN), 20480);
              tma3d(sb + O_REG, &p.m_q, 0, b * 16, 0, BAR(B_QIN));
            }
            TSTAMP(96 + I.v);
          }
        });
        ROLE;
        mbar_wait(BAR(B_EP), 0);
        EPOCHU;
        uint32_t known = 0;
        const uint32_t* const cnt = g_sync + Y_Y + min(lane, 10) * 32;
        const uint32_t target = ep * (lane < 5 ? 128 : 40);
        int ny = 0, nm = 0;
#pragma unroll 1
        for (int it = 0; ny < 5 || nm < 6; it++) {
          const int j = nm < 5 ? (ord >> (nm * 4)) & 7 : nm;
          uint32_t u = target;
          HINT(if (known != 2047) u = ldr(cnt));
          if ((known >> (5 + j)) & 1) {
            uint4 v[5];
            uint32_t bad = 0, lo[5], hi[5];
#pragma unroll
            for (int k = 0; k < 5; k++) v[k] = ldr4(g_mod + j * D_ + k * 128 + lane * 4);
#pragma unroll
            for (int k = 0; k < 5; k++) {
              bad |= (v[k].x ^ ep) | (v[k].y ^ ep) | (v[k].z ^ ep) | (v[k].w ^ ep);
              lo[k] = pack2(__uint_as_float(v[k].x), __uint_as_float(v[k].y));
              hi[k] = pack2(__uint_as_float(v[k].z), __uint_as_float(v[k].w));
            }
            if (!__any_sync(0xffffffffu, bad & 3) || it > 200000) {
              if (nm < 5) {
                const uint32_t ma = sb + O_MA + nm * 768 + lane * 8, one = 0x3F803F80u, c0 = hadd2(lo[4], one), c1 = hadd2(hi[4], one);
                sts64(ma, hmul2(lo[2], hadd2(lo[1], one)), hmul2(hi[2], hadd2(hi[1], one)));
                sts64(ma + 256, hmul2(lo[2], lo[0]), hmul2(hi[2], hi[0]));
                sts64(ma + 512, c0, c1);
                __syncwarp();
                if (lane == 0) { mbar_arrive(BAR(B_PR + nm)); if (nm < 3) TSTAMP(nm < 2 ? 7 + nm : 79); }
                if (j == vr) {
                  sts64(sb + O_CS + (lane >> 1) * 32 + (lane & 1) * 8, c0, c1);
                  sts64(sb + O_CS + (lane >> 1) * 32 + (lane & 1) * 8 + 16, lo[3], hi[3]);
                  fence_async_smem();
                  __syncwarp();
                  if (lane == 0) mbar_arrive(BAR(B_CS));
                }
              } else {
#pragma unroll
                for (int k = 0; k < 5; k++) if ((k * 32 + lane >= 80) == kh) sts128(sb + O_GB + k * 512 + lane * 16 - kh * 1280, lo[k] << 16, lo[k] & 0xffff0000u, hi[k] << 16, hi[k] & 0xffff0000u);
              }
              nm++;
            }
          }
          known |= __ballot_sync(0xffffffffu, (int)(u - target) >= 0 || it > 100000) & 2047;
          if (ny < 5) {
            const int y = (ord >> (ny * 4)) & 7;
            if (nm > 5 && ny >= 2) mbar_wait(BAR(B_YE + (ny & 1)), ny >> 2);
            if (((known >> y) & 1) && (ny < 2 || mbar_test(BAR(B_YE + (ny & 1)), ny >> 2) || it > 200000)) {
              if (elect()) {
                if (ny < 2) TSTAMP(47 + ny);
                bulk_ld(sb + (ny & 1 ? O_BP : O_Y), ps + page(G_Y + y, b), 4096, BAR(B_PR + ny));
              }
              ny++;
            }
          }
        }
        __syncwarp();
        if (lane < 6) mbar_expect(BAR(B_HF + lane), 8192);
        if (lane == 0) { sts128(sb + O_BP + 6144, 0, 0, 0, 0); mbar_arrive(BAR(B_VV)); }
        mbar_wait(BAR(B_YE + 1), 1);
      } else {
#pragma unroll
        for (int j = 0; j < 5; j++) {
          if (tid < 83) sts128(sb + bnd(j) + (lane < 17 ? U_KV + 4096 + lane * 16 : lane == 17 ? U_RAW - 16 : U_ODD - 16), 0, 0, 0, 0);
        }
        if (hw) sts32(sb + O_SX + lane * 4, 0x3F803F80u);
        bar_sync(1, 384);
        asm volatile("barrier.cluster.arrive.relaxed.aligned;" ::: "memory");
        fence_async_smem();
        if (elect()) {
#pragma unroll
          for (int i = 0; i < 4; i++) asm volatile("prefetch.tensormap [%0];" ::"l"(&p.m_k + hw * 4 + i) : "memory");
        }
        if (hw) {
          uint32_t x[10];
#pragma unroll
          for (int i = 0; i < 10; i++) x[i] = ldr((const uint32_t*)p.c + i * 32 + lane);
#pragma unroll
          for (int i = 0; i < 10; i++)
            sts32(sb + O_SILU + i % 5 * 256 + (lane >> 2) * 32 + i / 5 * 16 + (lane & 3) * 4, pack2(__fdividef(blo(x[i]), 1.f + __expf(-blo(x[i]))), __fdividef(bhi(x[i]), 1.f + __expf(-bhi(x[i])))));
          fence_async_smem();
          __syncwarp();
          if (lane < 5) mbar_arrive(BAR(B_PL + lane));
          mbar_wait(BAR(B_EP), 0);
          EPOCHU;
#pragma unroll 1
          for (int j = 0; j < 5; j++) {
            const uint32_t a = sb + bnd(j) + U_KV + lane * 32;
            mbar_wait(BAR(B_KV + j), 0);
#pragma unroll
            for (int i = 0; i < 4; i++) x[i] = lds32(a + i * 1024 + (lane & 28)) ^ ep;
            if ((x[0] | x[1] | x[2] | x[3]) & 1) {
#pragma unroll 1
              for (int i = 0; i < 4096; i += 1024) refetch(ps + (page(G_KV + j, b) + lane * 32 + i), lane & 28, a + i, ep);
            }
            __syncwarp();
            if (lane == 0) mbar_arrive(BAR(B_OK + j));
          }
        } else {
          uint32_t dv;
          asm volatile("ld.global.nc.u16 %0, [%1];" : "=r"(dv) : "l"(pD + min(lane, 4) * 128 + b) : "memory");
#pragma unroll 1
          for (int j = 0; j < 10; j++) {
            const uint32_t ra = sb + bnd(j >> 1) + U_RAW + (j & 1) * 2048 + lane * 16;
            const float dj = blo(__shfl_sync(0xffffffffu, dv, j >> 1));
            if (!(j & 1)) mbar_wait(BAR(B_SSM + (j >> 1)), 0);
            if (tid == 64 && j == 0) TSTAMP(77);
            uint4 w[4];
            uint32_t pv[4];
#pragma unroll
            for (int i = 0; i < 4; i++) { w[i] = lds128(ra + i * 512); pv[i] = lds32(ra + i * 512 - 4); }
            if (!((j & 1) | lane)) { w[0].x = prmt(pack2(blo(w[0].x) + dj, 0.f), w[0].x, 0x7610); sts32(ra, w[0].x); }
#pragma unroll
            for (int i = 0; i < 4; i++) sts128(ra + (U_ODD - U_RAW) + i * 512, prmt(pv[i], w[i].x, 0x5432), prmt(w[i].x, w[i].y, 0x5432), prmt(w[i].y, w[i].z, 0x5432), prmt(w[i].z, w[i].w, 0x5432));
            __syncwarp();
            if (lane == 0 && (j & 1)) { mbar_arrive(BAR(B_PL + (j >> 1))); TSTAMP(32 + (j >> 1)); }
          }
        }
        uint32_t ya = lane * 32 + (lane & 4) * 4, xl = (lane ^ lane >> 3) * 16, pl = (lane & 3) * 16;
        if (LNE) mbar_wait(BAR(B_LN), 0);
        else {
          float z[4] = {0.f, 0.f, 0.f, 0.f};
          auto acc = [&](uint32_t v) { const float f = blo(v), g = bhi(v); z[0] += f; z[1] = fmaf(f, f, z[1]); z[2] += g; z[3] = fmaf(g, g, z[3]); };
          mbar_wait(BAR(B_QIN), 0);
          if (tid == 64) TSTAMP(9);
          uint32_t a = sb + O_REG + hw * 512 + xl;
          uint4 x = lds128(a), y = lds128(a + 1024);
#pragma unroll 1
          for (int i = 0; i < 10; i++) {
            a += 2048;
            const uint4 u = lds128(a), v = lds128(a + 1024);
            acc(x.x); acc(x.y); acc(x.z); acc(x.w); acc(y.x); acc(y.y); acc(y.z); acc(y.w);
            x = u; y = v;
          }
          z[0] += z[2]; z[1] += z[3];
#pragma unroll
          for (int i = 1; i < 3; i++) { z[0] += __shfl_xor_sync(0xffffffffu, z[0], i); z[1] += __shfl_xor_sync(0xffffffffu, z[1], i); }
          const float mean = z[0] * (1.f / D_), rs = rbf(rsqrtf(fmaxf(z[1] * (1.f / D_) - mean * mean, 0.f) + 1e-5f));
          if (!(lane & 3)) sts32(sb + O_LN + hw * 32 + lane, pack2(rs, -mean * rs));
          bar_sync(4, 64);
          if (tid == 64) TSTAMP(59);
        }
        ROLE;
        const uint32_t tt = -(lds32(sb + O_EP) & 1);
        uint32_t ln[2];
#pragma unroll
        for (int h = 0; h < 2; h++) {
          if (LNE) {
            const float4 u = lds128f(sb + O_LN + h * 256 + (lane & 28) * 8), v = lds128f(sb + O_LN + h * 256 + (lane & 28) * 8 + 16);
            const float mean = ((u.x + u.z) + (v.x + v.z)) * (1.f / D_), rs = rbf(rsqrtf(fmaxf(((u.y + u.w) + (v.y + v.w)) * (1.f / D_) - mean * mean, 0.f) + 1e-5f));
            ln[h] = pack2(rs, -mean * rs);
          } else ln[h] = lds32(sb + O_LN + h * 32 + (lane & 28));
        }
        float sx[4] = {0.f, 0.f, 0.f, 0.f};
        keep(ya); keep(xl); keep(pl);
#pragma unroll 1
        for (int it = 0; it != 10;) {
          const int j = (ord >> (it * 2 & 28)) & 7, odd = (it >> 1) & 1, g = (it & 1) * 2 + hw;
          const uint32_t pm = sb + O_MA + (it & 14) * 384 + g * 64, yo = sb + (odd ? O_BP : O_Y) + g * 1024, qo = sb + O_REG + (j * 4 + g) * 1024;
          uint32_t q[8], y[8];
          if (!(it & 1)) mbar_wait(BAR(B_PR + ((it >> 1) & 7)), 0);
          if (!(xl | hw) && it < 6 && !(it & 1)) TSTAMP(it == 0 ? 49 : it == 2 ? 58 : 80);
          const uint4 q0 = lds128(addu(xl, qo)), a4 = lds128(addu(pl, pm)), b4 = lds128(addu(pl, pm) + 256);
          ldsm4t(addu(ya, yo), y[0], y[1], y[2], y[3]);
          const uint4 q1 = lds128(addu(xl, qo) + 512);
          ldsm4t(addu(ya, yo) ^ 16, y[4], y[5], y[6], y[7]);
          {
            const uint32_t ma[4] = {a4.x, a4.y, a4.z, a4.w}, mb[4] = {b4.x, b4.y, b4.z, b4.w};
            q[0] = q0.x; q[1] = q0.y; q[2] = q0.z; q[3] = q0.w; q[4] = q1.x; q[5] = q1.y; q[6] = q1.z; q[7] = q1.w;
#pragma unroll
            for (int i = 0; i < 8; i++) q[i] = hfma2(hfma2(hfma2lh(q[i], ln[i >> 2]), ma[i & 3], mb[i & 3]), y[i], q[i]);
          }
          if ((__ballot_sync(0xffffffffu, ((y[0] ^ tt) | (y[1] ^ tt) | (y[2] ^ tt) | (y[3] ^ tt) | (y[4] ^ tt) | (y[5] ^ tt) | (y[6] ^ tt) | (y[7] ^ tt)) & 0x00010001u) & 15) && it < 16) {
#pragma unroll 1
            for (int hf = 0; hf < 32; hf += 16) refetch16(ps + (page(G_Y + j, b) + g * 1024 + (ya ^ hf)), (ya ^ hf) + yo, tt);
            __syncwarp();
            it += 16;
            continue;
          }
          const uint4 c4 = lds128(addu(pl, pm) + 512);
          uint8_t* const xg = ps + addu(xl, tile(rb, j * 4 + g) + (b & 4) * 4096 + (b & 3) * 1024);
          stg128(xg, tag0(hmul2(q[0], c4.x), tt), hmul2(q[1], c4.y), hmul2(q[2], c4.z), hmul2(q[3], c4.w));
          stg128(xg + 512, tag0(hmul2(q[4], c4.x), tt), hmul2(q[5], c4.y), hmul2(q[6], c4.z), hmul2(q[7], c4.w));
          asm volatile("{ .reg .pred p; elect.sync _|p, 0xffffffff; @p red.relaxed.gpu.global.add.u32 [%0], 1; @p mbarrier.arrive.shared::cta.b64 _, [%1]; }"
                       ::"l"(misc + M_X + j * 8 + (it & 1) * 4), "r"(BAR(B_YE + odd)) : "memory");
          uint8_t* const og = p.out + addu((xl >> 6) * 1280 + pl, b * 20480 + (j * 4 + g) * 64);
          stg128(og, q[0], q[1], q[2], q[3]);
          stg128(og + 10240, q[4], q[5], q[6], q[7]);
#pragma unroll
          for (int i = 0; i < 8; i++) {
            const float f = blo(q[i]), h = bhi(q[i]);
            float &s1 = sx[(i >> 2) * 2], &s2 = sx[(i >> 2) * 2 + 1];
            s1 += f; s2 = fmaf(f, f, s2); s1 += h; s2 = fmaf(h, h, s2);
          }
          if (!(xl | hw) && (it & 1)) TSTAMP(12 + ((it & 15) >> 1));
          if (!(xl | hw) && it == 0) TSTAMP(116);
          it = (it & 15) + 1;
        }
        const int lane = ya >> 5, t = hw * 32 + lane;
        EPOCHU;
#pragma unroll
        for (int i = 0; i < 8; i++) sx[i & 3] += __shfl_xor_sync(0xffffffffu, sx[i & 3], (i >> 2) + 1);
        if (!(lane & 3)) sts64(sb + O_SX + t * 2, __float_as_uint(hw ? sx[0] : sx[2]), __float_as_uint(hw ? sx[1] : sx[3]));
        bar_sync(4, 64);
        const float2 so = lds64f(sb + O_SX + (hw ^ 1) * 64 + (xl >> 6) * 8);
        const float mean = ((hw ? sx[2] : sx[0]) + so.x) * (1.f / D_);
        const uint32_t pa = pack2(-mean, sqrtf(fmaxf(((hw ? sx[3] : sx[1]) + so.y) * (1.f / D_) - mean * mean, 0.f) + 1e-5f));
        if (!(lane & 3))
          asm volatile("st.relaxed.gpu.global.v2.u32 [%0], {%1,%2};" ::"l"(misc + M_ST + fs * 128 + t * 2), "r"(pa), "r"(tagf(__fdividef(1.f, bhi(pa) * bhi(pa)), ep)) : "memory");
        uint4 v;
        int it = 0;
        do v = ldr4((const uint32_t*)(misc + M_ST + t * 16)); while ((((v.y ^ ep) | (v.w ^ ep)) & 3) && ++it < 100000);
        sts128(sb + O_ST + t * 16, v.x, v.y, v.z, v.w);
        __syncwarp();
        if (lane == 0) mbar_arrive(BAR(B_ST + hw));
        if (t == 0) TSTAMP(52);
      }
      ROLE;
      EPOCHU;
      int lane;
      asm volatile("mov.u32 %0, %%laneid;" : "=r"(lane));
      {
        HINT(poll_ge(g_sync + Y_VV + fs * 32, ep * 128));
        uint32_t v[20], bad;
        int it = 0;
        const uint32_t* g = g_vv + fs * 1920 + (hw + 1) * 128 + lane;
        do {
          bad = 0;
#pragma unroll
          for (int k = 0; k < 20; k++) v[k] = ldr(g + ((k % 5) * 384 + (k / 5) * 32));
#pragma unroll
          for (int k = 0; k < 20; k++) bad |= v[k] ^ ep;
        } while (__any_sync(0xffffffffu, bad & 1) && ++it < 100000);
#pragma unroll
        for (int k = 0; k < 4; k++) sts128(sb + O_BP + ((hw + 1) * 128 + k * 32 + lane) * 16, v[5 * k], v[5 * k + 1], v[5 * k + 2], hadd2(v[5 * k + 3], v[5 * k + 4]));
        fence_async_smem();
        __syncwarp();
      }
      if (lane == 0) mbar_arrive(BAR(B_VV));
      if (warp == 1) {
        if (lane == 0) TSTAMP(37);
        uint32_t v;
        int it = 0;
        do asm volatile("ld.acquire.gpu.global.u32 %0, [%1];" : "=r"(v) : "l"(misc + M_O) : "memory"); while ((int)(v - ep * 16) < 0 && ++it < 100000);
        asm volatile("fence.proxy.async.global;" ::: "memory");
        if (lane == 0) { mbar_arrive(BAR(B_X1)); TSTAMP(30); }
      } else {
        asm volatile("fence.acq_rel.gpu;" ::: "memory");
        __syncwarp();
        if (lane == 0) hint_add((uint32_t*)(misc + M_O));
      }
      __syncwarp();
      asm volatile("barrier.cluster.wait.aligned;" ::: "memory");
    }
  } else {
    const int isE = warp >= 8 ? 1 : 0;
    const int w = warp & 3, r = lane >> 2, c = lane & 3;
    const bool lead = (tid & 127) == 0;
    const int tb = b >> 2;
    if (isE) {
      const int u = tid & 127, t = tb * 64 + r * 8 + w, th = t - (w == 3 ? 0 : 3);
      const uint32_t d = sb + kreg(0) + (u >> 2) * 64 + ((c ^ (r >> 1)) << 4);
      const int o = t * D_ + (b & 3) * 32 + c * 8;
      cpa16(d, pk + o, 16); cpa16(d + voff(0), pv + o, 16);
      cpa16(d + 2048, pk + o + 4 * D_, 16); cpa16(d + voff(0) + 2048, pv + o + 4 * D_, 16);
      if (u < 112) cpa16(w == 3 ? sb + kreg(0) + 5632 + lane * 16 : d + 4096, w == 3 ? pshift + (b & 3) * 128 + lane * 8 : pk + (th < 0 ? o : o - 3 * D_), th < 0 ? 0 : 16);
      if (lead) TSTAMP(74);
    } else {
      if (lane == 0) {
#pragma unroll
        for (int i = 0; i < 19; i++) mbar_init(BAR(w + 4 * i), i < 2 ? 2 : i < 5 ? 4 : 1);
        asm volatile("fence.mbarrier_init.release.cluster;" ::: "memory");
      }
      __syncwarp();
      if (lead) TSTAMP(76);
    }
    EPLOAD;
    bar_sync(1, 384);
    if (tid == 256) TSTAMP(75);
    asm volatile("setmaxnreg.inc.sync.aligned.u32 232;");
    asm volatile("barrier.cluster.arrive.relaxed.aligned;" ::: "memory");
    EPOCH;
    if (isE) {
      asm volatile("cp.async.wait_all;" ::: "memory");
      bar_sync(6, 128);
    }
    asm volatile("barrier.cluster.wait.aligned;" ::: "memory");
    uint64_t steps = isE ? sched(1) : sched(0);
    uint32_t A[64];
    auto release = [&](uint32_t m) { if (w == 3 && lane < 12 && ((m >> (lane >> 1)) & 1)) mbar_arrive_cl(mapa(BAR(B_EMPTY + (lane >> 1)), lane & 1)); __syncwarp(); };
#pragma unroll 1
    for (; steps; steps >>= 12) {
      const uint32_t todo = (uint32_t)steps;
      if (todo & 7) {
        const int n = (todo & 7) - 1, tg = lane & 7;
        const uint32_t a = sb + kreg(n) + tg * 64 + ((w ^ (tg >> 1)) << 4) + (lane >> 3) * 4;
        if (n) mbar_wait(BAR(B_KIN + n), 0);
        if (lead) TSTAMP(69 + n);
        if (EK == 2 && lead) hint_add(g_sync + Y_KV + (n * 4 + (b & 3)) * 32);
        uint32_t kk[11], x[8];
        const uint4 sw = lds128(sb + kreg(n) + 5632 + w * 64 + (lane & 24) * 2);
#pragma unroll
        for (int i = 0; i < 11; i++) kk[i] = lds32(a + (i < 3 ? 4096 + i * 512 : (i - 3) * 512));
#pragma unroll
        for (int i = 0; i < 8; i++) x[7 - i] = lds32(a + voff(n) + i * 512);
        const uint32_t w0 = prmt(sw.x, sw.z, 0x5410), w1 = prmt(sw.x, sw.z, 0x7632), w2 = prmt(sw.y, sw.w, 0x5410), w3 = prmt(sw.y, sw.w, 0x7632);
#pragma unroll
        for (int i = 0; i < 8; i++) x[7 - i] = hmul2(hfma2(kk[i + 3], w0, hfma2(kk[i + 2], w1, hfma2(kk[i + 1], w2, hmul2(kk[i], w3)))), x[7 - i]);
        if (EK == 1 && lead) hint_add(g_sync + Y_KV + (n * 4 + (b & 3)) * 32);
        const int tw = (~tb & 7) ^ ((~lane & 1) << 2);
#pragma unroll
        for (int i = 0; i < 4; i++) x[2 * i] = settag(x[2 * i], tw == i ? 0x00010001u : 0u, -(ep & 1));
        const uint32_t o = page(G_KV + n, (b & 3) * 32 + w * 8 + (lane >> 3) * 2) + 4080 - tb * 128 - tg * 16;
        stg128(ps + o, prmt(x[0], x[1], 0x5410), prmt(x[2], x[3], 0x5410), prmt(x[4], x[5], 0x5410), prmt(x[6], x[7], 0x5410));
        stg128(ps + o + 4096, prmt(x[0], x[1], 0x7632), prmt(x[2], x[3], 0x7632), prmt(x[4], x[5], 0x7632), prmt(x[6], x[7], 0x7632));
        bar_sync(5 + isE, 128);
        if (lead) { if (!EK) hint_add(g_sync + Y_KV + (n * 4 + (b & 3)) * 32); TSTAMP(64 + n); }
      }
      if (b < 120 && ((todo >> 3) & 3) == 1 + grp) {
        float d[16];
        const uint64_t db = mkdesc(sb + O_SILU, 32, 128, 0), da = mkdesc(sb + O_WM, 20480, 512, 2);
        mbar_wait(BAR(B_PL), 0);
        mbar_wait(BAR(B_WM), 0);
        if (lead) TSTAMP(81 + grp);
        if (EM == 2 && w < 2 && lane == 0) hint_add(g_sync + Y_MOD + part * 32);
        wg_fence();
#pragma unroll
        for (int kk = 0; kk < 20; kk++) wgmma_ss_8_10(d + (kk & 3) * 4, da + kk * 64, db + kk * 4, kk >> 2);
        wg_commit();
        wg_wait<0>();
        regfence<16>(d);
#pragma unroll
        for (int i = 0; i < 4; i++) d[i] = (d[i] + d[4 + i]) + (d[8 + i] + d[12 + i]);
        if (EM == 1 && w < 2 && lane == 0) hint_add(g_sync + Y_MOD + part * 32);
        const uint32_t xa = sb + O_SILU + 2048 + (w & 1) * 64 + r * 8;
        if (c == 0 && w >= 2) sts64(xa, __float_as_uint(d[1]), __float_as_uint(d[3]));
        bar_sync(5 + isE, 128);
        if (w < 2) {
          const float2 e = lds64f(xa);
          if (c == 0) { str(g_mod + b * 32 + w * 16 + r, tagf(d[0] + e.x, ep)); str(g_mod + b * 32 + w * 16 + r + 8, tagf(d[2] + e.y, ep)); }
          __syncwarp();
          if (!EM && lane == 0) hint_add(g_sync + Y_MOD + part * 32);
        }
        if (lead) TSTAMP(grp == 2 ? 60 : 20 + grp);
      }
      if (todo & 224) {
        const int j = ((todo >> 5) & 7) - 1, u = tid & 127;
        const uint32_t ub = sb + bnd(j), pb = sb + (bnd(j) | 16384);
        float d[128];
        mbar_wait(BAR(B_OK + j), 0);
        if (MX && j) bar_sync(9 - isE, 256);
        if (lead) TSTAMP(53 + j);
        const uint64_t db = mkdesc(ub + U_KV, 16, 128, 0);
        wg_fence();
        wgmma_rs_32_0(d + 0, A[0], A[1], A[2], A[3], db + 0, 0);
        wgmma_rs_32_0(d + 16, A[0], A[1], A[2], A[3], db + 32, 0);
        wgmma_rs_32_0(d + 32, A[0], A[1], A[2], A[3], db + 64, 0);
        wgmma_rs_32_0(d + 48, A[0], A[1], A[2], A[3], db + 96, 0);
        wgmma_rs_32_0(d + 0, A[4], A[5], A[6], A[7], db + 16, 1);
        wgmma_rs_32_0(d + 16, A[4], A[5], A[6], A[7], db + 48, 1);
        wgmma_rs_32_0(d + 32, A[4], A[5], A[6], A[7], db + 80, 1);
        wgmma_rs_32_0(d + 48, A[4], A[5], A[6], A[7], db + 112, 1);
        wgmma_rs_32_0(d + 0, A[8], A[9], A[10], A[11], db + 32, 1);
        wgmma_rs_32_0(d + 16, A[8], A[9], A[10], A[11], db + 64, 1);
        wgmma_rs_32_0(d + 32, A[8], A[9], A[10], A[11], db + 96, 1);
        wgmma_rs_32_0(d + 64, A[0], A[1], A[2], A[3], db + 128, 0);
        wgmma_rs_32_0(d + 0, A[12], A[13], A[14], A[15], db + 48, 1);
        wgmma_rs_32_0(d + 16, A[12], A[13], A[14], A[15], db + 80, 1);
        wgmma_rs_32_0(d + 32, A[12], A[13], A[14], A[15], db + 112, 1);
        wgmma_rs_32_0(d + 48, A[8], A[9], A[10], A[11], db + 128, 1);
        wgmma_rs_32_0(d + 0, A[16], A[17], A[18], A[19], db + 64, 1);
        wgmma_rs_32_0(d + 16, A[16], A[17], A[18], A[19], db + 96, 1);
        wgmma_rs_32_0(d + 32, A[16], A[17], A[18], A[19], db + 128, 1);
        wgmma_rs_32_0(d + 64, A[4], A[5], A[6], A[7], db + 144, 1);
        wgmma_rs_32_0(d + 0, A[20], A[21], A[22], A[23], db + 80, 1);
        wgmma_rs_32_0(d + 16, A[20], A[21], A[22], A[23], db + 112, 1);
        wgmma_rs_32_0(d + 48, A[12], A[13], A[14], A[15], db + 144, 1);
        wgmma_rs_32_0(d + 32, A[20], A[21], A[22], A[23], db + 144, 1);
        wgmma_rs_32_0(d + 0, A[24], A[25], A[26], A[27], db + 96, 1);
        wgmma_rs_32_0(d + 16, A[24], A[25], A[26], A[27], db + 128, 1);
        wgmma_rs_32_0(d + 80, A[0], A[1], A[2], A[3], db + 160, 0);
        wgmma_rs_32_0(d + 64, A[8], A[9], A[10], A[11], db + 160, 1);
        wgmma_rs_32_0(d + 0, A[28], A[29], A[30], A[31], db + 112, 1);
        wgmma_rs_32_0(d + 16, A[28], A[29], A[30], A[31], db + 144, 1);
        wgmma_rs_32_0(d + 48, A[16], A[17], A[18], A[19], db + 160, 1);
        wgmma_rs_32_0(d + 32, A[24], A[25], A[26], A[27], db + 160, 1);
        wgmma_rs_32_0(d + 0, A[32], A[33], A[34], A[35], db + 128, 1);
        wgmma_rs_32_0(d + 16, A[32], A[33], A[34], A[35], db + 160, 1);
        wgmma_rs_32_0(d + 80, A[4], A[5], A[6], A[7], db + 176, 1);
        wgmma_rs_32_0(d + 64, A[12], A[13], A[14], A[15], db + 176, 1);
        wgmma_rs_32_0(d + 0, A[36], A[37], A[38], A[39], db + 144, 1);
        wgmma_rs_32_0(d + 48, A[20], A[21], A[22], A[23], db + 176, 1);
        wgmma_rs_32_0(d + 32, A[28], A[29], A[30], A[31], db + 176, 1);
        wgmma_rs_32_0(d + 16, A[36], A[37], A[38], A[39], db + 176, 1);
        wgmma_rs_32_0(d + 0, A[40], A[41], A[42], A[43], db + 160, 1);
        wgmma_rs_32_0(d + 96, A[0], A[1], A[2], A[3], db + 192, 0);
        wgmma_rs_32_0(d + 80, A[8], A[9], A[10], A[11], db + 192, 1);
        wgmma_rs_32_0(d + 64, A[16], A[17], A[18], A[19], db + 192, 1);
        wgmma_rs_32_0(d + 0, A[44], A[45], A[46], A[47], db + 176, 1);
        wgmma_rs_32_0(d + 48, A[24], A[25], A[26], A[27], db + 192, 1);
        wgmma_rs_32_0(d + 32, A[32], A[33], A[34], A[35], db + 192, 1);
        wgmma_rs_32_0(d + 16, A[40], A[41], A[42], A[43], db + 192, 1);
        wgmma_rs_32_0(d + 0, A[48], A[49], A[50], A[51], db + 192, 1);
        wgmma_rs_32_0(d + 96, A[4], A[5], A[6], A[7], db + 208, 1);
        wgmma_rs_32_0(d + 80, A[12], A[13], A[14], A[15], db + 208, 1);
        wgmma_rs_32_0(d + 64, A[20], A[21], A[22], A[23], db + 208, 1);
        wgmma_rs_32_0(d + 48, A[28], A[29], A[30], A[31], db + 208, 1);
        wgmma_rs_32_0(d + 32, A[36], A[37], A[38], A[39], db + 208, 1);
        wgmma_rs_32_0(d + 16, A[44], A[45], A[46], A[47], db + 208, 1);
        wgmma_rs_32_0(d + 0, A[52], A[53], A[54], A[55], db + 208, 1);
        wgmma_rs_32_0(d + 112, A[0], A[1], A[2], A[3], db + 224, 0);
        wgmma_rs_32_0(d + 96, A[8], A[9], A[10], A[11], db + 224, 1);
        wgmma_rs_32_0(d + 80, A[16], A[17], A[18], A[19], db + 224, 1);
        wgmma_rs_32_0(d + 64, A[24], A[25], A[26], A[27], db + 224, 1);
        wgmma_rs_32_0(d + 48, A[32], A[33], A[34], A[35], db + 224, 1);
        wgmma_rs_32_0(d + 32, A[40], A[41], A[42], A[43], db + 224, 1);
        wgmma_rs_32_0(d + 16, A[48], A[49], A[50], A[51], db + 224, 1);
        wgmma_rs_32_0(d + 0, A[56], A[57], A[58], A[59], db + 224, 1);
        wgmma_rs_32_0(d + 112, A[4], A[5], A[6], A[7], db + 240, 1);
        wgmma_rs_32_0(d + 96, A[12], A[13], A[14], A[15], db + 240, 1);
        wgmma_rs_32_0(d + 80, A[20], A[21], A[22], A[23], db + 240, 1);
        wgmma_rs_32_0(d + 64, A[28], A[29], A[30], A[31], db + 240, 1);
        wgmma_rs_32_0(d + 48, A[36], A[37], A[38], A[39], db + 240, 1);
        wgmma_rs_32_0(d + 32, A[44], A[45], A[46], A[47], db + 240, 1);
        wgmma_rs_32_0(d + 16, A[52], A[53], A[54], A[55], db + 240, 1);
        wgmma_rs_32_0(d + 0, A[60], A[61], A[62], A[63], db + 240, 1);
        wg_commit();
        if (MX == 1) bar_arrive(8 + isE, 256);
        const uint32_t yoff = pb + w * 2048 + (127 + 2 * w - lane) * 16;
        const uint32_t yoff0 = yoff + (lane < 2 * w ? -2048 : 8192), yoff4 = yoff + (lane < 2 * w ? 6144 : 0);
        wg_wait<0>();
        regfence<128>(d);
        if (MX == 2 || j == 4 && !MX) bar_arrive(8 + isE, 256);
        if (j == 4) bar_sync(5, 128);
        if (lead) TSTAMP(42 + j);
        if (EY == 2 && lead) hint_add(g_sync + Y_Y + j * 32);
#pragma unroll
        for (int z = 0; z < 8; z++) {
          uint32_t e[4];
#pragma unroll
          for (int i = 0; i < 4; i++) {
            const int x = 4 * z + i;
            e[i] = x < 31 ? pack2(d[4 * x] + d[4 * x + 6], d[4 * x + 1] + d[4 * x + 7]) : pack2(d[4 * x], d[4 * x + 1]);
          }
          if (z == 0 && c < w) e[0] = 0;
          stsm4t(z == 0 ? yoff0 : z == 4 ? yoff4 : z < 4 ? yoff + 8192 - 512 * z : yoff - 512 * (z - 4), e[0], e[1], e[2], e[3]);
        }
        uint8_t* g = ps + page(G_Y + j, u >> 1) + ((b & 97) | (b & 6) << 2 | (b & 24) >> 2) * 32 + ((u ^ (b >> 4)) & 1) * 16;
        if (EY == 1 && lead) hint_add(g_sync + Y_Y + j * 32);
        bar_sync(5 + isE, 128);
#pragma unroll
        for (int i = 0; i < 2; i++) {
          const uint32_t pa = pb + u * 16 + i * 8192;
          const uint4 p0 = lds128(pa), p1 = lds128(pa + 2048), p2 = lds128(pa + 4096), p3 = lds128(pa + 6144);
          stg128(g + (i << 18), settag(hadd2(hadd2(p0.x, p1.x), hadd2(p2.x, p3.x)), 1, ep), hadd2(hadd2(p0.y, p1.y), hadd2(p2.y, p3.y)),
                 hadd2(hadd2(p0.z, p1.z), hadd2(p2.z, p3.z)), hadd2(hadd2(p0.w, p1.w), hadd2(p2.w, p3.w)));
        }
        if (lead) { if (!EY) hint_add(g_sync + Y_Y + j * 32); TSTAMP(84 + j); }
        release(0140202146 >> 6 * j);
      }
      if (todo & 0x700) {
        const int j = ((todo >> 8) & 7) - 1;
        const uint32_t sa = sb + bnd(j) + ((r & 1) ? U_RAW : U_ODD) + 4 * (8 * w + (r >> 1) - 3 + c);
        mbar_wait(BAR(B_PL + j), 0);
#pragma unroll
        for (int g = 0; g < 16; g++) { A[4 * g] = lds32(sa + g * 256); A[4 * g + 1] = lds32(sa + g * 256 + 128); A[4 * g + 2] = lds32(sa + g * 256 + 16); A[4 * g + 3] = lds32(sa + g * 256 + 144); }
        if (lead) TSTAMP(89 + j);
      }
      if (LNE && (todo & 0x800)) {
        float d[72];
        const uint64_t dq = mkdesc(sb + O_REG, 0, 512, 2);
        mbar_wait(BAR(B_QIN), 0);
        if (lead) TSTAMP(9);
        wg_fence();
#pragma unroll
        for (int i = 0; i < 10; i++) {
          wgmma_ss_64_00(d + (i & 1) * 32, dq + (i >> 1) * 256 + (i & 1) * 2, dq + (i >> 1) * 256 + (i & 1) * 2, i >> 1);
          wgmma_ss_8_00(d + 64 + (i & 1) * 4, dq + (i >> 1) * 256 + (i & 1) * 2, mkdesc(sb + O_SX, 0, 0, 0), i >> 1);
        }
        wg_commit();
        wg_wait<0>();
        regfence<72>(d);
#pragma unroll
        for (int h = 0; h < 2; h++) {
          float z[4];
#pragma unroll
          for (int i = 0; i < 4; i++) z[i] = r & 1 ? d[8 * i + 6 * h + 1] + d[8 * i + 6 * h + 33] : d[8 * i + 6 * h] + d[8 * i + 6 * h + 32];
          if (c == r >> 1) sts64(sb + O_LN + (h * 8 + r) * 32 + w * 8, __float_as_uint(d[64 + 2 * h] + d[68 + 2 * h]), __float_as_uint(w & 2 ? (w & 1 ? z[3] : z[2]) : w & 1 ? z[1] : z[0]));
        }
        __syncwarp();
        if (lane == 0) mbar_arrive(BAR(B_LN));
        if (lead) TSTAMP(59);
      }
      __syncwarp();
    }
    bar_sync(5 + isE, 128);
    release(isE ? 016 : 010);
    const int rh = isE;
    uint32_t hA[96];
    const uint32_t hb = sb + (isE ? O_REG : 24576) + w * 2048, hs = isE ? 8192 : SLOT;
    auto publish = [&](int kq) {
      asm volatile("st.async.weak.shared::cluster.mbarrier::complete_tx::bytes.v4.b32 [%0], {%1,%2,%3,%4}, [%5];" ::"r"(mapa(hb + lane * 16, kh ^ 1) + (kq >> 2) * hs + (kq & 3) * 512),
                   "r"(hA[4 * kq]), "r"(hA[4 * kq + 1]), "r"(hA[4 * kq + 2]), "r"(hA[4 * kq + 3]), "r"(mapa(BAR(B_HF + isE * 3), kh ^ 1) + (kq >> 2) * 8) : "memory");
      if (kq == 3 && tid == 256) TSTAMP(117);
    };
    {
      float ag[96], au[96], iv[2];
      int slot = 4, prev = 0, s = 0;
      int v0, vo;
      uint32_t vg;
      { ROLE; v0 = min(vr, 2) * 4; vo = (2 * vt + isE) * 256; vg = (fs * 5 + vr) * 384 + (2 * vt + isE) * 64 + 16 * w + r; }
      const uint32_t dbase = mkdesc(sb, 4096, 0, 0);
      uint32_t ck = sb + 24576 + rh * 4096 + w * 1024 + lane * 32 + (r & 1) * 16;
      keep(ck);
      const uint32_t emp = mapa(BAR(B_EMPTY), tid & 1);
      if (isE) bar_sync(8, 256);
      auto check = [&](uint32_t tag) {
        if ((tag ^ ep) & 1) refetch(ps + (lds32(sb + O_XT + s * 4) + rh * 16384 + (tid & 127) * 32), (r & 1) * 16, (ck + slot * SLOT) & ~31u, ep);
        __syncwarp();
        if (lead) TS3(isE, s);
        if (s && s < 20 && (s & 3) == 0 && tid == 128) TSTAMP(37 + (s >> 2));
        if (s == LH + LEAD * isE) { if (isE) bar_arrive(7, 256); else bar_sync(7, 256); }
      };
      auto stage = [&](float* vv) {
        const uint32_t dl = dbase + slot * (SLOT >> 4);
        const uint64_t dg = mkdesc(0, 0, 1024, 1) | dl, da = mkdesc(0, 0, 512, 2) | (dl + ((24576 + rh * 4096) >> 4));
        wg_wait<1>();
        wg_fence();
        if (vv) {
          wgmma_ss_8_10(vv, dg + vo, mkdesc(sb + O_CS, 32, 128, 0) + (s & 3) * 8, s & 3);
          wgmma_ss_8_10(vv, dg + vo + 128, mkdesc(sb + O_CS, 32, 128, 0) + (s & 3) * 8 + 4, 1);
          wg_commit();
        }
        const int sd = s, nx = s == 19 ? 5 : slot == 5 ? 0 : slot + 1;
        const uint32_t par = (0x1c0fc0 >> ++s) & 1;
        uint32_t in, tag;
        auto peek = [&]() { asm volatile("{ .reg .pred p; setp.ne.u32 p, %2, 0; @p ld.shared.u32 %0, [%1]; }" : "=r"(tag) : "r"(addu(ck, nx * SLOT)), "r"(in) : "memory"); };
        if (RP == 0) in = TW ? mbar_try(BAR(B_FULL + nx), par) : mbar_test(BAR(B_FULL + nx), par);
        wgmma_ss_192_01(ag, da, dg, sd);
        if (s > 2 && (tid & 126) == 0) mbar_arrive_cl(addu(emp, prev & 63));
        if (RP == 0) peek();
        if (RP == 1) in = TW ? mbar_try(BAR(B_FULL + nx), par) : mbar_test(BAR(B_FULL + nx), par);
        wgmma_ss_192_01(au, da, mkdesc(0, 0, 1024, 1) | (dl + 768), sd);
        if (RP == 1) peek();
        if (RP == 2) in = TW ? mbar_try(BAR(B_FULL + nx), par) : mbar_test(BAR(B_FULL + nx), par);
        wgmma_ss_192_01(ag, mkdesc(0, 0, 512, 2) | ((uint32_t)da + 2), mkdesc(0, 0, 1024, 1) | (dl + 128), 1);
        if (RP == 2) peek();
        wgmma_ss_192_01(au, mkdesc(0, 0, 512, 2) | ((uint32_t)da + 2), mkdesc(0, 0, 1024, 1) | (dl + 896), 1);
        wg_commit();
        prev = prev >> 8 | slot << 11;
        slot = nx;
        if (!in) { mbar_wait(BAR(B_FULL + nx), par); tag = lds32(addu(ck, nx * SLOT)); }
        check(tag);
      };
      mbar_wait(BAR(B_FULL + 4), 0);
      check(lds32(ck + 4 * SLOT));
      if (lead) TSTAMP(22 + isE);
#pragma unroll 1
      for (int end = v0, k = 0; k < 2; end = 20, k++) {
#pragma unroll 1
        while (s < end) stage(nullptr);
        if (k == 0) {
          float vv[4];
          mbar_wait(BAR(B_CS), 0);
#pragma unroll 1
          do stage(vv); while (s & 3);
          wg_wait<1>();
          regfence<4>(vv);
          if (c == 0) { str(g_vv + vg, settag(pack2(vv[0], vv[1]), 1, ep)); str(g_vv + vg + 8, settag(pack2(vv[2], vv[3]), 1, ep)); }
          __syncwarp();
          asm volatile("{ .reg .pred p; elect.sync _|p, 0xffffffff; @p red.relaxed.gpu.global.add.u32 [%0], 1; }" ::"l"(g_sync + Y_VV + vg / 1920 * 32) : "memory");
        }
      }
      {
        if (tid == 128) str(g_sync + Y_EP + b * 32, ep);
        wg_wait<1>();
        if ((tid & 126) == 0) mbar_arrive_cl(emp + 32);
        mbar_wait(BAR(B_ST + rh), 0);
        const float2 sa = lds64f(sb + O_ST + rh * 512 + w * 128 + r * 8), sc = lds64f(sb + O_ST + rh * 512 + w * 128 + r * 8 + 64);
        const uint32_t a0 = __float_as_uint(sa.x), a1 = __float_as_uint(sc.x);
        iv[0] = sa.y; iv[1] = sc.y;
        mbar_wait(BAR(B_VV), 0);
        const uint64_t dp = mkdesc(sb + O_BP, 16, 128, 0);
        wg_fence();
        wgmma_rs_192_0(ag, a0, a1, 0, 0, dp, 1);
        wgmma_rs_192_0(au, a0, a1, 0, 0, dp + 192, 1);
        wg_commit();
        wg_wait<1>();
        if ((tid & 126) == 0) mbar_arrive_cl(emp + 40);
        mbar_wait(BAR(isE ? B_ST : B_EMPTY + 2), !isE);
        wg_wait<0>();
      }
      regfence<96>(ag); regfence<96>(au);
      if (lead) TSTAMP(24 + isE);
#pragma unroll
      for (int kq = 0; kq < 12; kq++) {
#pragma unroll
        for (int i = 0; i < 4; i++) hA[4 * kq + i] = pack2(ag[8 * kq + 2 * i] * iv[i & 1] * au[8 * kq + 2 * i], ag[8 * kq + 2 * i + 1] * iv[i & 1] * au[8 * kq + 2 * i + 1]);
        if (kq < 4 * NPUB) publish(kq);
      }
      if (lead) TSTAMP(50 + isE);
    }
    float o[2][32];
    float2 gb[8];
    const uint32_t stg = hb + (lane & 15) * 128 + (((lane >> 4) ^ (lane & 7)) << 4);
    const int row = (b >> 3) * 128 + rh * 64 + 16 * w;
    auto ldgb = [&](int fin) {
#pragma unroll
      for (int u = 0; u < 8; u++) gb[u] = lds64f(sb + O_GB + (ocol(b & 6, fin) + 8 * u + 2 * c) * 4);
      if (fin >= 3) { if (elect()) bulk_wait_read<2>(); __syncwarp(); }
    };
    auto piece = [&](int fin, int u) {
      const float* x = o[fin & 1] + 8 * u;
      const float2 g0 = gb[2 * u], g1 = gb[2 * u + 1];
      stsm4((stg ^ u * 32) + fin % 3 * hs, pack2(x[0] * g0.x, x[1] * g0.y), pack2(x[2] * g0.x, x[3] * g0.y), pack2(x[4] * g1.x, x[5] * g1.y), pack2(x[6] * g1.x, x[7] * g1.y));
    };
    auto flush = [&](int fin) {
      fence_async_smem();
      __syncwarp();
      if (elect()) { tma2d_add(&p.m_out, hb + fin % 3 * hs, ocol(b, fin), row); bulk_commit(); }
    };
    unrolled<10>([&](auto I) {
      constexpr int s = I.v, e = s < 7 ? s : s - 7, src = s < 4 ? s >> 1 : s & 1, blk = s < 4 ? s & 1 : s >> 1;
      constexpr int fin = s == 3 ? 0 : blk - 1;
      const uint64_t dw = mkdesc(sb + w2entry(e), 1024 * s, 1024, 1);
      if (s == 3 || s >= 4 && !src) ldgb(fin);
      if (s == 4) mbar_wait(BAR(B_X1), 0);
      mbar_wait(BAR(B_W2F + e), s >= 7);
      if (s == 6 && tid == 256) TSTAMP(123);
      TS2(3 * s);
      unrolled<12>([&](auto J) {
        constexpr int kk = J.v, n = s < 4 ? kk : src * 12 + kk;
        if (s == 2 && !(kk & 3)) {
          mbar_wait_cluster(BAR(B_HF + isE * 3 + (kk >> 2)), 0);
          if (kk == 0 && lead) TSTAMP(26 + isE);
#pragma unroll
          for (int i = kk; i < kk + 4; i++) {
            const uint4 v = lds128(hb + lane * 16 + (i >> 2) * hs + (i & 3) * 512);
            hA[48 + 4 * i] = v.x; hA[49 + 4 * i] = v.y; hA[50 + 4 * i] = v.z; hA[51 + 4 * i] = v.w;
          }
        }
        if (kk == 0 || s == 2 && !(kk & 3)) wg_fence();
        const uint32_t* h = hA + src * 48 + 4 * kk;
        wgmma_rs_64_1(o[blk & 1], h[0], h[1], h[2], h[3], dw + (kk >> 2) * (e == 6 ? SLOT >> 4 : 512) + (kk & 3) * 128, (src | kk) ? 1 : 0);
        if (s < 2 && (s * 12 + kk) % PUBD == PUBD - 1 && 4 * NPUB + (s * 12 + kk) / PUBD < 12) publish(4 * NPUB + (s * 12 + kk) / PUBD);
        if (kk == QD - 1 && s >= 1 && (s < 4 || !src)) {
          wg_commit();
          wg_wait<1>();
          if (s < 4 && lead) mbar_arrive(BAR(B_W2E + s - 1));
          if (s >= 3) regfence<32>(o[fin & 1]);
          if (s == 4) flush(0);
          TS2(3 * s + 2);
        }
        if (s == 3 && kk >= QD - 1 && (kk - QD + 1) % 2 == 0 && (kk - QD + 1) / 2 < 4) piece(0, (kk - QD + 1) / 2);
        if (s >= 4 && n >= QD - 1 && (n - QD + 1) % 3 == 0 && (n - QD + 1) / 3 < 4) piece(fin, (n - QD + 1) / 3);
        if (s >= 4 && n == QD + 14) flush(fin);
      });
      wg_commit();
      TS2(3 * s + 1);
    });
    ldgb(4);
    mbar_wait(BAR(B_X1), 0);
    wg_wait<0>();
    regfence<32>(o[0]);
    if (lead) TSTAMP(28 + isE);
#pragma unroll
    for (int u = 0; u < 4; u++) piece(4, u);
    flush(4);
    if (tid == 128) TSTAMP(119);
    if (elect()) bulk_wait_read<0>();
    if (tid == 256) TSTAMP(121);
    if (!isE) {
      if (lead) TSTAMP(31);
    }
  }
}

#define L2PROMO CU_TENSOR_MAP_L2_PROMOTION_L2_128B
typedef CUresult (*EncodeFn)(CUtensorMap*, CUtensorMapDataType, cuuint32_t, void*, const cuuint64_t*, const cuuint64_t*, const cuuint32_t*,
                             const cuuint32_t*, CUtensorMapInterleave, CUtensorMapSwizzle, CUtensorMapL2promotion, CUtensorMapFloatOOBfill);

void make_map(EncodeFn enc, CUtensorMap* m, const void* ptr, uint64_t inner, uint64_t outer, uint32_t bi, uint32_t bo, CUtensorMapSwizzle sw) {
  cuuint64_t d[2] = {inner, outer};
  cuuint64_t s[1] = {inner * 2};
  cuuint32_t bx[2] = {bi, bo};
  cuuint32_t e[2] = {1, 1};
  enc(m, CU_TENSOR_MAP_DATA_TYPE_BFLOAT16, 2, const_cast<void*>(ptr), d, s, bx, e, CU_TENSOR_MAP_INTERLEAVE_NONE, sw, L2PROMO,
      CU_TENSOR_MAP_FLOAT_OOB_FILL_NONE);
}

void make_map3(EncodeFn enc, CUtensorMap* m, const void* ptr, uint64_t d0, uint64_t d1, uint64_t d2, uint64_t s1, uint64_t s2, uint32_t b0, uint32_t b1, uint32_t b2,
               CUtensorMapSwizzle sw, uint64_t s3 = 0) {
  cuuint64_t d[4] = {d0, d1, d2, 2};
  cuuint64_t s[3] = {s1, s2, s3};
  cuuint32_t bx[4] = {b0, b1, b2, 2};
  cuuint32_t e[4] = {1, 1, 1, 1};
  enc(m, CU_TENSOR_MAP_DATA_TYPE_BFLOAT16, s3 ? 4 : 3, const_cast<void*>(ptr), d, s, bx, e, CU_TENSOR_MAP_INTERLEAVE_NONE, sw, L2PROMO,
      CU_TENSOR_MAP_FLOAT_OOB_FILL_NONE);
}

}

extern "C" void kernel_launch(void* const* d_in, const int* in_sizes, int n_in, void* d_out, int out_size) {
  (void)in_sizes; (void)n_in; (void)out_size;
  void* f = nullptr;
  cudaDriverEntryPointQueryResult qr;
  cudaGetDriverEntryPoint("cuTensorMapEncodeTiled", &f, cudaEnableDefault, &qr);
  EncodeFn enc = (EncodeFn)f;
  void* s;
  cudaGetSymbolAddress(&s, g_s);
  Params p = {};
  uint8_t* ps = (uint8_t*)(((uintptr_t)s + (2 << 20) - 1) & ~(uintptr_t)((2 << 20) - 1));
  make_map3(enc, &p.m_k, d_in[1], D_, S_ / 8, 8, 8 * D_ * 2, D_ * 2, 32, 8, 8, CU_TENSOR_MAP_SWIZZLE_64B);
  make_map3(enc, &p.m_kh, d_in[1], D_, S_ / 8, 8, 8 * D_ * 2, D_ * 2, 32, 8, 3, CU_TENSOR_MAP_SWIZZLE_64B);
  make_map3(enc, &p.m_v, d_in[2], D_, S_ / 8, 8, 8 * D_ * 2, D_ * 2, 32, 8, 8, CU_TENSOR_MAP_SWIZZLE_64B);
  make_map3(enc, &p.m_q, d_in[0], 32, S_, D_ / 32, D_ * 2, 64, 32, 16, D_ / 32, CU_TENSOR_MAP_SWIZZLE_64B);
  make_map3(enc, &p.m_wm, d_in[11], 6 * D_, 160, 4, 12 * D_, 160 * 12 * D_, 32, 160, 4, CU_TENSOR_MAP_SWIZZLE_64B);
  const int lo = (uintptr_t)d_in[7] < (uintptr_t)d_in[8] ? 7 : 8;
  make_map3(enc, &p.m_w1, d_in[lo], 64, D_, F_ / 64, F_ * 2, 128, 64, 32, 3, CU_TENSOR_MAP_SWIZZLE_128B, (uintptr_t)d_in[15 - lo] - (uintptr_t)d_in[lo]);
  make_map(enc, &p.m_w2, d_in[9], D_, F_, 64, 64, CU_TENSOR_MAP_SWIZZLE_128B);
  make_map(enc, &p.m_out, d_out, D_, S_, 64, 16, CU_TENSOR_MAP_SWIZZLE_128B);
  p.c = (const __nv_bfloat16*)d_in[10];
  p.wg = (const __nv_bfloat16*)d_in[7];
  p.wu = (const __nv_bfloat16*)d_in[8];
  p.w2 = (const __nv_bfloat16*)d_in[9];
  p.out = (uint8_t*)d_out;
  cudaFuncSetAttribute(fused_kernel, cudaFuncAttributeMaxDynamicSharedMemorySize, SMEM_BYTES);
  fused_kernel<<<128, 384, SMEM_BYTES, cudaStreamPerThread>>>((const __nv_bfloat16*)d_in[1], (const __nv_bfloat16*)d_in[2], (const __nv_bfloat16*)d_in[3],
                                                              (const __nv_bfloat16*)d_in[4], (const __nv_bfloat16*)d_in[5], ps, p);
}
```

```cpp
#include <cuda_runtime.h>
#include <cuda.h>
#include <cuda_bf16.h>
#include <cstdint>

namespace {

constexpr int S_ = 2048, D_ = 640, F_ = 1536;

__device__ __align__(1024) uint8_t g_s[10 << 20];
#define g_sync ((uint32_t*)(ps + (1 << 16)))
#define g_mod ((uint32_t*)(ps + (2 << 16)))
#define g_vv ((uint32_t*)(ps + (3 << 16)))
#define TIMOFF (4 << 16)
enum { Y_KV = 0, Y_Y = 20 * 32, Y_MOD = 25 * 32, Y_VV = 31 * 32, Y_EP = 4 };
enum { G_KV = 1, G_Y = 6, G_X = 11 };
enum { M_X = 0, M_O = 40, M_ST = 512 };
#define TSTAMP(i) do { } while (0)
#define TS3(k, i) do { } while (0)
#define TS2(i) do { } while (0)
#define TS 6
#define SCH 1
#define T0 1000
#define TR 100
#define O6 0
#define T_K1 T0
#define T_K2 (T0 + 7 * TR)
#define T_S1 (T0 + 14 * TR)
#define T_K3 (T0 + 175 * TR / 10)
#define T_K4 (T0 + 245 * TR / 10)
#define T_S2 (T0 + 315 * TR / 10)
#define T_WM0 (T0 + (O6 ? 42 : 35) * TR)
#define T_S3 (T0 + (O6 ? 350 : 405) * TR / 10)
#define T_S4 (T0 + (O6 ? 385 : 440) * TR / 10)
#define T_Q (T0 + 47 * TR + TR / 2)
#define T_WM1 (T0 + 65 * TR)
#define T_W0 (T0 + 71 * TR)
#define T_WM2 (T0 + 76 * TR)
#define T_S0 600
#define D_Q 54
#define D_WM 27
#define NE0 1
#define NE 2
#define STEP(kv, gv, cv, fa) ((kv + 1) | (gv + 1) << 3 | (cv + 1) << 5 | (fa + 1) << 8)
#define EV 5
#define EV0 31
#define EV1 0ull
#define EV2 0x40141210ull
#define EV3 0x411311ull
#define SCHED_E STEP(0, -1, -1, 1), STEP(2, -1, -1, -1), STEP(4, -1, 1, 3), STEP(-1, 1, 3, -1), STEP(-1, 2, -1, -1)
#define SCHED_L STEP(-1, -1, -1, 0), STEP(1, 0, -1, -1), STEP(3, -1, 0, 2), STEP(-1, -1, 2, 4), STEP(-1, -1, 4, -1)
#define PFW 0x71u
#define PF2 0xc80u
#define AH 2
#define PD 3
#define ROT 1
#define QD 5
#define PUBD 2
#define NPUB 1
#define LH 17
#define MX 0
#define WARM 1
#define RS 2
#define GE 3
#define ER 1
#define VR 3
#define EVV 1
#define DM 1
#define PK 1
#define T_P 3800
#define EK 1
#define EY 4
#define EM 0
#define RP 2
#define TW 0
#define LEAD 2

struct Params {
  CUtensorMap m_k, m_kh, m_v, m_q, m_wm, m_w1, m_w2, m_out;
  const __nv_bfloat16 *c, *wg, *wu, *w2;
  uint8_t* out;
};
constexpr int NLD = 12;
__host__ __device__ constexpr uint32_t nth_load(int n) {
  const uint32_t when[NLD] = {T_K1 << 8 | 1, T_K2 << 8 | 2, T_K3 << 8 | 3, T_K4 << 8 | 4, T_S0 << 8 | 16, T_S1 << 8 | 17, T_S2 << 8 | 18, T_S3 << 8 | 19, T_S4 << 8 | 20,
                              T_Q << 8 | 21, T_WM0 << 8 | 32, T_WM1 << 8 | 33};
  for (int i = 0; i < NLD; i++) {
    int rank = 0;
    for (int k = 0; k < NLD; k++) rank += when[k] < when[i];
    if (rank == n) return when[i];
  }
  return 0;
}
__host__ __device__ constexpr uint64_t sched(int g) {
  const uint32_t t[2][5] = {{SCHED_L}, {SCHED_E}};
  uint64_t r = 0;
  for (int i = 0; i < 5; i++) r |= (uint64_t)t[g][i] << 12 * i;
  return r;
}
template <int I> struct IC { static constexpr int v = I; };
template <int N, class F> __device__ __forceinline__ void unrolled(F f) {
  if constexpr (N > 0) { unrolled<N - 1>(f); f(IC<N - 1>()); }
}

constexpr uint32_t SLOT = 32768;
constexpr uint32_t SD = 1024;
constexpr uint32_t U_RAW = 16, U_ODD = U_RAW + 4160, U_KV = 8448;
constexpr uint32_t O_WM = 2 * SLOT;
constexpr uint32_t O_SILU = O_WM + 40960;
constexpr uint32_t O_REG = 6 * SLOT;
constexpr uint32_t O_Y = O_REG + 20480;
constexpr uint32_t O_BP = O_Y + 4096;
constexpr uint32_t O_MA = O_BP + 4096;
constexpr uint32_t O_ST = O_BP + 7040;
constexpr uint32_t O_CS = O_ST + 1024;
constexpr uint32_t O_GB = O_CS + 640;
constexpr uint32_t O_LN = O_GB + 1280;
constexpr uint32_t O_EP = O_GB + 1280 + 64;
constexpr uint32_t O_BAR = O_EP + 192;
constexpr uint32_t O_XT = O_EP + 64;
constexpr uint32_t SMEM_BYTES = O_BAR + 1024;
static_assert(SMEM_BYTES <= 232448, "smem");
enum { B_W2E = 0, B_EMPTY = 4, B_LN = 10, B_VV = 11, B_YE = 12, B_OK = 16 - PK, B_FULL = 21, B_W2F = 27, B_HF = 34, B_KV = 40,
       B_CS = 45, B_X1 = 46, B_ST = 47, B_PR = 49, B_SSM = 56, B_QIN = 61, B_WM = 62, B_K = 62, B_PL = 67 };
__device__ __forceinline__ uint32_t kreg(int n) { return n < 4 ? (0x319b >> 4 * n & 15) << 14 : 5 * SLOT + 26624; }
__device__ __forceinline__ uint32_t voff(int n) { return n < 4 ? 6144 : -4 * SLOT; }
__device__ __forceinline__ uint32_t w2entry(int e) { return e == 6 ? 3 * SLOT + 24576 : e * SLOT; }
__device__ __forceinline__ int ocol(int ro, int i) { i += ROT * ((ro >> 1) & 3); return (ro & 1) * 320 + (i < 5 ? i : i - 5) * 64; }
__device__ __forceinline__ uint32_t bnd(int j) { return (0x720a8 >> 4 * j & 15) << 14; }
__device__ __forceinline__ uint32_t page(int g, int p) { return g << 19 | p << 12; }
__device__ __forceinline__ uint32_t tile(int rb, int x) { return page(G_X + (x >> 2), rb * 8 + (x & 3)); }

__device__ __forceinline__ uint32_t smem_u32(const void* p) { return (uint32_t)__cvta_generic_to_shared(p); }
__device__ __forceinline__ void mbar_init(uint32_t bar, uint32_t cnt) { asm volatile("mbarrier.init.shared::cta.b64 [%0], %1;" ::"r"(bar), "r"(cnt) : "memory"); }
__device__ __forceinline__ void mbar_expect(uint32_t bar, uint32_t bytes) { asm volatile("mbarrier.arrive.expect_tx.shared::cta.b64 _, [%0], %1;" ::"r"(bar), "r"(bytes) : "memory"); }
__device__ __forceinline__ void mbar_arrive(uint32_t bar) { asm volatile("mbarrier.arrive.shared::cta.b64 _, [%0];" ::"r"(bar) : "memory"); }
__device__ __forceinline__ void mbar_wait(uint32_t bar, uint32_t parity) {
  asm volatile("{\n .reg .pred p;\n .reg .u32 c;\n mov.u32 c, 0;\n LOOP:\n mbarrier.try_wait.parity.shared::cta.b64 p, [%0], %1;\n @p bra DONE;\n add.u32 c, c, 1;\n setp.lt.u32 p, c, 200000;\n @p bra LOOP;\n DONE:\n }" ::"r"(bar), "r"(parity) : "memory");
}
__device__ __forceinline__ void mbar_wait_cluster(uint32_t bar, uint32_t parity) {
  asm volatile("{\n .reg .pred p;\n .reg .u32 c;\n mov.u32 c, 0;\n LOOP:\n mbarrier.try_wait.parity.acquire.cluster.shared::cta.b64 p, [%0], %1;\n @p bra DONE;\n add.u32 c, c, 1;\n setp.lt.u32 p, c, 200000;\n @p bra LOOP;\n DONE:\n }" ::"r"(bar), "r"(parity) : "memory");
}
__device__ __forceinline__ bool mbar_test(uint32_t bar, uint32_t parity) {
  uint32_t r;
  asm volatile("{ .reg .pred p; mbarrier.test_wait.parity.shared::cta.b64 p, [%1], %2; selp.u32 %0, 1, 0, p; }" : "=r"(r) : "r"(bar), "r"(parity) : "memory");
  return r;
}
__device__ __forceinline__ bool mbar_try(uint32_t bar, uint32_t parity) {
  uint32_t r;
  asm volatile("{ .reg .pred p; mbarrier.try_wait.parity.shared::cta.b64 p, [%1], %2; selp.u32 %0, 1, 0, p; }" : "=r"(r) : "r"(bar), "r"(parity) : "memory");
  return r;
}
__device__ __forceinline__ uint32_t mapa(uint32_t a, uint32_t cta) { uint32_t r; asm("mapa.shared::cluster.u32 %0, %1, %2;" : "=r"(r) : "r"(a), "r"(cta)); return r; }
__device__ __forceinline__ void mbar_arrive_cl(uint32_t bar) { asm volatile("mbarrier.arrive.shared::cluster.b64 _, [%0];" ::"r"(bar) : "memory"); }
__device__ __forceinline__ bool elect() { uint32_t p; asm volatile("{ .reg .pred q; elect.sync _|q, 0xffffffff; selp.u32 %0, 1, 0, q; }" : "=r"(p)); return p; }
__device__ __forceinline__ uint32_t clk() { uint32_t c; asm volatile("mov.u32 %0, %%clock;" : "=r"(c)); return c; }
__device__ __forceinline__ uint32_t ldr(const uint32_t* p) { uint32_t v; asm volatile("ld.relaxed.gpu.global.u32 %0, [%1];" : "=r"(v) : "l"(p) : "memory"); return v; }
__device__ __forceinline__ uint4 ldr4(const uint32_t* p) {
  uint4 v; asm volatile("ld.relaxed.gpu.global.v4.u32 {%0,%1,%2,%3}, [%4];" : "=r"(v.x), "=r"(v.y), "=r"(v.z), "=r"(v.w) : "l"(p) : "memory"); return v;
}
__device__ __forceinline__ void poll_ge(const uint32_t* p, uint32_t target) {
  asm volatile("{\n .reg .pred p;\n .reg .u32 c, v;\n mov.u32 c, 0;\n LOOP:\n ld.relaxed.gpu.global.u32 v, [%0];\n sub.u32 v, v, %1;\n setp.ge.s32 p, v, 0;\n @p bra DONE;\n add.u32 c, c, 1;\n setp.lt.u32 p, c, 100000;\n @p bra LOOP;\n DONE:\n }" ::"l"(p), "r"(target) : "memory");
}
__device__ __forceinline__ void poll_lane(uint32_t& v, const void* p, uint32_t target, int l) {
  for (int it = 0; !((__ballot_sync(0xffffffffu, (int)(v - target) >= 0) >> l) & 1) && it < 100000; it++) v = ldr((const uint32_t*)p);
}
__device__ __forceinline__ void hint_add(uint32_t* p) { asm volatile("red.relaxed.gpu.global.add.u32 [%0], 1;" ::"l"(p) : "memory"); }
__device__ __forceinline__ void refetch(const void* g, uint32_t off, uint32_t a, uint32_t tag) {
  asm volatile("{\n .reg .pred p;\n .reg .u32 c, v, x, y, z;\n .reg .u64 q;\n mov.u32 c, 0;\n cvt.u64.u32 q, %1;\n add.u64 q, q, %0;\n"
               " LOOP:\n ld.relaxed.gpu.global.u32 v, [q];\n xor.b32 v, v, %3;\n and.b32 v, v, 1;\n setp.eq.u32 p, v, 0;\n @p bra DONE;\n add.u32 c, c, 1;\n setp.lt.u32 p, c, 100000;\n @p bra LOOP;\n"
               " DONE:\n ld.relaxed.gpu.global.v4.u32 {v, x, y, z}, [%0];\n st.shared.v4.u32 [%2], {v, x, y, z};\n ld.relaxed.gpu.global.v4.u32 {v, x, y, z}, [%0+16];\n xor.b32 c, %2, 16;\n"
               " st.shared.v4.u32 [c], {v, x, y, z};\n fence.proxy.async.shared::cta;\n }" ::"l"(g), "r"(off), "r"(a), "r"(tag) : "memory");
}
__device__ __forceinline__ void refetch_all(const void* g, uint32_t off, uint32_t a, uint32_t tag) {
  asm volatile("{\n .reg .pred p;\n .reg .u32 c, v, x, y, z;\n .reg .u64 q;\n mov.u32 c, 0;\n cvt.u64.u32 q, %1;\n add.u64 q, q, %0;\n"
               " LOOP:\n ld.relaxed.gpu.global.u32 v, [q];\n xor.b32 v, v, %3;\n and.b32 v, v, 1;\n setp.eq.u32 p, v, 0;\n vote.sync.all.pred p, p, 0xffffffff;\n @p bra DONE;\n add.u32 c, c, 1;\n setp.lt.u32 p, c, 100000;\n @p bra LOOP;\n"
               " DONE:\n ld.relaxed.gpu.global.v4.u32 {v, x, y, z}, [%0];\n st.shared.v4.u32 [%2], {v, x, y, z};\n ld.relaxed.gpu.global.v4.u32 {v, x, y, z}, [%0+16];\n xor.b32 c, %2, 16;\n"
               " st.shared.v4.u32 [c], {v, x, y, z};\n fence.proxy.async.shared::cta;\n }" ::"l"(g), "r"(off), "r"(a), "r"(tag) : "memory");
}
__device__ __forceinline__ void refetch16(const void* g, uint32_t a, uint32_t tag) {
  asm volatile("{\n .reg .pred p;\n .reg .u32 c, t, v, x, y, z;\n mov.u32 c, 0;\n"
               " LOOP:\n ld.relaxed.gpu.global.v4.u32 {v, x, y, z}, [%0];\n xor.b32 t, v, %2;\n and.b32 t, t, 1;\n setp.eq.u32 p, t, 0;\n vote.sync.all.pred p, p, 0xffffffff;\n @p bra DONE;\n add.u32 c, c, 1;\n setp.lt.u32 p, c, 100000;\n @p bra LOOP;\n"
               " DONE:\n st.shared.v4.u32 [%1], {v, x, y, z};\n }" ::"l"(g), "r"(a), "r"(tag) : "memory");
}
__device__ __forceinline__ uint2 ldr2(const uint32_t* p) {
  uint2 v; asm volatile("ld.relaxed.gpu.global.v2.u32 {%0,%1}, [%2];" : "=r"(v.x), "=r"(v.y) : "l"(p) : "memory"); return v;
}
__device__ __forceinline__ uint32_t settag(uint32_t x, uint32_t m, uint32_t t) { return (x & ~m) | (t & m); }
__device__ __forceinline__ void stg128(void* p, uint32_t x, uint32_t y, uint32_t z, uint32_t w) {
  asm volatile("st.global.v4.u32 [%0], {%1,%2,%3,%4};" ::"l"(p), "r"(x), "r"(y), "r"(z), "r"(w) : "memory");
}
__device__ __forceinline__ void stg128p(uint32_t on, void* p, uint32_t x, uint32_t y, uint32_t z, uint32_t w) {
  asm volatile("{ .reg .pred q; setp.ne.u32 q, %5, 0; @q st.global.v4.u32 [%0], {%1,%2,%3,%4}; }" ::"l"(p), "r"(x), "r"(y), "r"(z), "r"(w), "r"(on) : "memory");
}
__device__ __forceinline__ void hint_addp(uint32_t on, uint32_t* p) { asm volatile("{ .reg .pred p, q; elect.sync _|p, 0xffffffff; setp.ne.and.u32 q, %1, 0, p; @q red.relaxed.gpu.global.add.u32 [%0], 1; }" ::"l"(p), "r"(on) : "memory"); }
__device__ __forceinline__ void cpa16(uint32_t dst, const void* src, uint32_t n) { asm volatile("cp.async.cg.shared.global [%0], [%1], 16, %2;" ::"r"(dst), "l"(src), "r"(n) : "memory"); }
__device__ __forceinline__ void tma3d(uint32_t dst, const CUtensorMap* m, int x, int y, int z, uint32_t bar) {
  asm volatile("cp.async.bulk.tensor.3d.shared::cluster.global.mbarrier::complete_tx::bytes [%0], [%1, {%3, %4, %5}], [%2];" ::"r"(dst), "l"(m), "r"(bar), "r"(x), "r"(y), "r"(z) : "memory");
}
__device__ __forceinline__ void tma4d(uint32_t dst, const CUtensorMap* m, int x, int y, int z, int u, uint32_t bar) {
  asm volatile("cp.async.bulk.tensor.4d.shared::cluster.global.mbarrier::complete_tx::bytes [%0], [%1, {%3, %4, %5, %6}], [%2];" ::"r"(dst), "l"(m), "r"(bar), "r"(x), "r"(y), "r"(z), "r"(u) : "memory");
}
__device__ __forceinline__ void bulk_st(void* dst, uint32_t src, uint32_t bytes) {
  asm volatile("cp.async.bulk.global.shared::cta.bulk_group [%0], [%1], %2;" ::"l"(dst), "r"(src), "r"(bytes) : "memory");
}
__device__ __forceinline__ void bulk_pf(const void* src, uint32_t bytes) { asm volatile("cp.async.bulk.prefetch.L2.global [%0], %1;" ::"l"(src), "r"(bytes) : "memory"); }
__device__ __forceinline__ void tma2d(uint32_t dst, const CUtensorMap* m, int x, int y, uint32_t bar) {
  asm volatile("cp.async.bulk.tensor.2d.shared::cluster.global.mbarrier::complete_tx::bytes [%0], [%1, {%3, %4}], [%2];" ::"r"(dst), "l"(m), "r"(bar), "r"(x), "r"(y) : "memory");
}
__device__ __forceinline__ void tma2d_add(const CUtensorMap* m, uint32_t src, int x, int y) {
  asm volatile("cp.reduce.async.bulk.tensor.2d.global.shared::cta.add.tile.bulk_group [%0, {%2, %3}], [%1];" ::"l"(m), "r"(src), "r"(x), "r"(y) : "memory");
}
__device__ __forceinline__ void bulk_ld(uint32_t dst, const void* src, uint32_t bytes, uint32_t bar) {
  asm volatile("cp.async.bulk.shared::cluster.global.mbarrier::complete_tx::bytes [%0], [%1], %2, [%3];" ::"r"(dst), "l"(src), "r"(bytes), "r"(bar) : "memory");
}
__device__ __forceinline__ void bulk_commit() { asm volatile("cp.async.bulk.commit_group;" ::: "memory"); }
template <int N> __device__ __forceinline__ void bulk_wait() { asm volatile("cp.async.bulk.wait_group %0;" ::"n"(N) : "memory"); }
template <int N> __device__ __forceinline__ void bulk_wait_read() { asm volatile("cp.async.bulk.wait_group.read %0;" ::"n"(N) : "memory"); }
__device__ __forceinline__ void fence_async_smem() { asm volatile("fence.proxy.async.shared::cta;" ::: "memory"); }
__device__ __forceinline__ void bar_sync(int id, int n) { asm volatile("bar.sync %0, %1;" ::"r"(id), "r"(n) : "memory"); }
__device__ __forceinline__ void bar_arrive(int id, int n) { asm volatile("bar.arrive %0, %1;" ::"r"(id), "r"(n) : "memory"); }
__device__ __forceinline__ void wg_fence() { asm volatile("wgmma.fence.sync.aligned;" ::: "memory"); }
__device__ __forceinline__ void wg_commit() { asm volatile("wgmma.commit_group.sync.aligned;" ::: "memory"); }
template <int N> __device__ __forceinline__ void wg_wait() { asm volatile("wgmma.wait_group.sync.aligned %0;" ::"n"(N) : "memory"); }
__device__ __forceinline__ void ldsm4(uint32_t a, uint32_t& r0, uint32_t& r1, uint32_t& r2, uint32_t& r3) {
  asm volatile("ldmatrix.sync.aligned.m8n8.x4.shared.b16 {%0,%1,%2,%3}, [%4];" : "=r"(r0), "=r"(r1), "=r"(r2), "=r"(r3) : "r"(a) : "memory");
}
__device__ __forceinline__ void ldsm4t(uint32_t a, uint32_t& r0, uint32_t& r1, uint32_t& r2, uint32_t& r3) {
  asm volatile("ldmatrix.sync.aligned.m8n8.x4.trans.shared.b16 {%0,%1,%2,%3}, [%4];" : "=r"(r0), "=r"(r1), "=r"(r2), "=r"(r3) : "r"(a) : "memory");
}
__device__ __forceinline__ void stsm4t(uint32_t a, uint32_t r0, uint32_t r1, uint32_t r2, uint32_t r3) {
  asm volatile("stmatrix.sync.aligned.m8n8.x4.trans.shared.b16 [%0], {%1,%2,%3,%4};" ::"r"(a), "r"(r0), "r"(r1), "r"(r2), "r"(r3) : "memory");
}
__device__ __forceinline__ void stsm4(uint32_t a, uint32_t r0, uint32_t r1, uint32_t r2, uint32_t r3) {
  asm volatile("stmatrix.sync.aligned.m8n8.x4.shared.b16 [%0], {%1,%2,%3,%4};" ::"r"(a), "r"(r0), "r"(r1), "r"(r2), "r"(r3) : "memory");
}
__device__ __forceinline__ uint32_t lds32(uint32_t a) { uint32_t v; asm volatile("ld.shared.u32 %0, [%1];" : "=r"(v) : "r"(a) : "memory"); return v; }
__device__ __forceinline__ uint4 lds128(uint32_t a) { uint4 v; asm volatile("ld.shared.v4.u32 {%0,%1,%2,%3}, [%4];" : "=r"(v.x), "=r"(v.y), "=r"(v.z), "=r"(v.w) : "r"(a) : "memory"); return v; }
__device__ __forceinline__ float4 lds128f(uint32_t a) { float4 v; asm volatile("ld.shared.v4.f32 {%0,%1,%2,%3}, [%4];" : "=f"(v.x), "=f"(v.y), "=f"(v.z), "=f"(v.w) : "r"(a) : "memory"); return v; }
__device__ __forceinline__ float2 lds64f(uint32_t a) { float2 v; asm volatile("ld.shared.v2.f32 {%0,%1}, [%2];" : "=f"(v.x), "=f"(v.y) : "r"(a) : "memory"); return v; }
__device__ __forceinline__ void sts32(uint32_t a, uint32_t v) { asm volatile("st.shared.u32 [%0], %1;" ::"r"(a), "r"(v) : "memory"); }
__device__ __forceinline__ void sts64(uint32_t a, uint32_t x, uint32_t y) { asm volatile("st.shared.v2.u32 [%0], {%1,%2};" ::"r"(a), "r"(x), "r"(y) : "memory"); }
__device__ __forceinline__ void sts128(uint32_t a, uint32_t x, uint32_t y, uint32_t z, uint32_t w) { asm volatile("st.shared.v4.u32 [%0], {%1,%2,%3,%4};" ::"r"(a), "r"(x), "r"(y), "r"(z), "r"(w) : "memory"); }
__device__ __forceinline__ void sts16(uint32_t a, uint16_t v) { asm volatile("st.shared.u16 [%0], %1;" ::"r"(a), "h"(v) : "memory"); }
__device__ __forceinline__ uint32_t prmt(uint32_t a, uint32_t b, uint32_t s) { uint32_t r; asm("prmt.b32 %0, %1, %2, %3;" : "=r"(r) : "r"(a), "r"(b), "r"(s)); return r; }
__device__ __forceinline__ uint32_t hfma2(uint32_t a, uint32_t b, uint32_t c) { uint32_t r; asm("fma.rn.bf16x2 %0, %1, %2, %3;" : "=r"(r) : "r"(a), "r"(b), "r"(c)); return r; }
__device__ __forceinline__ uint32_t hfma2lh(uint32_t a, uint32_t l) {
  uint32_t r;
  asm("{ .reg .b16 x, y; .reg .b32 u, v; mov.b32 {x, y}, %2; mov.b32 u, {x, x}; mov.b32 v, {y, y}; fma.rn.bf16x2 %0, %1, u, v; }" : "=r"(r) : "r"(a), "r"(l));
  return r;
}
__device__ __forceinline__ uint32_t addu(uint32_t a, uint32_t u) { uint32_t r; asm("add.u32 %0, %1, %2;" : "=r"(r) : "r"(a), "r"(u)); return r; }
__device__ __forceinline__ uint32_t tag0(uint32_t x, uint32_t t) { uint32_t r; asm("lop3.b32 %0, %1, 1, %2, 0xb8;" : "=r"(r) : "r"(x), "r"(t)); return r; }
__device__ __forceinline__ void keep(uint32_t& x) { x = __shfl_xor_sync(0xffffffffu, x, 0); }
__device__ __forceinline__ uint32_t hmul2(uint32_t a, uint32_t b) { uint32_t r; asm("mul.rn.bf16x2 %0, %1, %2;" : "=r"(r) : "r"(a), "r"(b)); return r; }
__device__ __forceinline__ uint32_t pack2(float lo, float hi) { uint32_t r; asm("cvt.rn.bf16x2.f32 %0, %1, %2;" : "=r"(r) : "f"(hi), "f"(lo)); return r; }
__device__ __forceinline__ float blo(uint32_t v) { return __uint_as_float(v << 16); }
__device__ __forceinline__ float bhi(uint32_t v) { return __uint_as_float(v & 0xffff0000u); }
__device__ __forceinline__ uint32_t hadd2(uint32_t a, uint32_t b) { uint32_t r; asm("add.rn.bf16x2 %0, %1, %2;" : "=r"(r) : "r"(a), "r"(b)); return r; }
__device__ __forceinline__ void str(uint32_t* p, uint32_t v) { asm volatile("st.relaxed.gpu.global.u32 [%0], %1;" ::"l"(p), "r"(v) : "memory"); }
__device__ __forceinline__ uint32_t tagf(float x, uint32_t tag) { return (__float_as_uint(x) & ~3u) | (tag & 3); }
template <int N> __device__ __forceinline__ float4 gather4(const uint32_t* p, int stride, uint32_t tag) {
  uint4 v[N];
  int it = 0;
  uint32_t bad;
  do {
#pragma unroll
    for (int i = 0; i < N; i++) v[i] = ldr4(p + i * stride);
    bad = 0;
#pragma unroll
    for (int i = 0; i < N; i++) bad |= (v[i].x ^ tag) | (v[i].y ^ tag) | (v[i].z ^ tag) | (v[i].w ^ tag);
  } while ((bad & 3) && ++it < 100000);
  float4 s = make_float4(__uint_as_float(v[0].x), __uint_as_float(v[0].y), __uint_as_float(v[0].z), __uint_as_float(v[0].w));
#pragma unroll
  for (int i = 1; i < N; i++) { s.x += __uint_as_float(v[i].x); s.y += __uint_as_float(v[i].y); s.z += __uint_as_float(v[i].z); s.w += __uint_as_float(v[i].w); }
  return s;
}
__device__ __forceinline__ float rbf(float x) { return blo(pack2(x, 0.f)); }
__device__ __forceinline__ uint64_t mkdesc(uint32_t addr, uint32_t lbo, uint32_t sbo, uint32_t swz) {
  return (uint64_t)((addr & 0x3FFFF) >> 4) | ((uint64_t)(lbo >> 4) << 16) | ((uint64_t)(sbo >> 4) << 32) | ((uint64_t)swz << 62);
}
template <int N> __device__ __forceinline__ void regfence(float* d) {
#pragma unroll
  for (int i = 0; i < N; i++) asm volatile("" : "+f"(d[i])::"memory");
}

__device__ __forceinline__ void wgmma_rs_32_0(float* d, uint32_t a0, uint32_t a1, uint32_t a2, uint32_t a3, uint64_t db, int sd) {
  asm volatile("{ .reg .pred p; setp.ne.b32 p, %21, 0; wgmma.mma_async.sync.aligned.m64n32k16.f32.bf16.bf16 {%0,%1,%2,%3,%4,%5,%6,%7,%8,%9,%10,%11,%12,%13,%14,%15}, {%16,%17,%18,%19}, %20, p, 1, 1, 0; }"
   : "+f"(d[0]), "+f"(d[1]), "+f"(d[2]), "+f"(d[3]), "+f"(d[4]), "+f"(d[5]), "+f"(d[6]), "+f"(d[7]), "+f"(d[8]), "+f"(d[9]), "+f"(d[10]), "+f"(d[11]), "+f"(d[12]), "+f"(d[13]), "+f"(d[14]), "+f"(d[15]) : "r"(a0), "r"(a1), "r"(a2), "r"(a3), "l"(db), "r"(sd));
}
__device__ __forceinline__ void wgmma_rs_64_1(float* d, uint32_t a0, uint32_t a1, uint32_t a2, uint32_t a3, uint64_t db, int sd) {
  asm volatile("{ .reg .pred p; setp.ne.b32 p, %37, 0; wgmma.mma_async.sync.aligned.m64n64k16.f32.bf16.bf16 {%0,%1,%2,%3,%4,%5,%6,%7,%8,%9,%10,%11,%12,%13,%14,%15,%16,%17,%18,%19,%20,%21,%22,%23,%24,%25,%26,%27,%28,%29,%30,%31}, {%32,%33,%34,%35}, %36, p, 1, 1, 1; }"
   : "+f"(d[0]), "+f"(d[1]), "+f"(d[2]), "+f"(d[3]), "+f"(d[4]), "+f"(d[5]), "+f"(d[6]), "+f"(d[7]), "+f"(d[8]), "+f"(d[9]), "+f"(d[10]), "+f"(d[11]), "+f"(d[12]), "+f"(d[13]), "+f"(d[14]), "+f"(d[15]), "+f"(d[16]), "+f"(d[17]), "+f"(d[18]), "+f"(d[19]), "+f"(d[20]), "+f"(d[21]), "+f"(d[22]), "+f"(d[23]), "+f"(d[24]), "+f"(d[25]), "+f"(d[26]), "+f"(d[27]), "+f"(d[28]), "+f"(d[29]), "+f"(d[30]), "+f"(d[31]) : "r"(a0), "r"(a1), "r"(a2), "r"(a3), "l"(db), "r"(sd));
}
__device__ __forceinline__ void wgmma_rs_192_0(float* d, uint32_t a0, uint32_t a1, uint32_t a2, uint32_t a3, uint64_t db, int sd) {
  asm volatile("{ .reg .pred p; setp.ne.b32 p, %101, 0; wgmma.mma_async.sync.aligned.m64n192k16.f32.bf16.bf16 {%0,%1,%2,%3,%4,%5,%6,%7,%8,%9,%10,%11,%12,%13,%14,%15,%16,%17,%18,%19,%20,%21,%22,%23,%24,%25,%26,%27,%28,%29,%30,%31,%32,%33,%34,%35,%36,%37,%38,%39,%40,%41,%42,%43,%44,%45,%46,%47,%48,%49,%50,%51,%52,%53,%54,%55,%56,%57,%58,%59,%60,%61,%62,%63,%64,%65,%66,%67,%68,%69,%70,%71,%72,%73,%74,%75,%76,%77,%78,%79,%80,%81,%82,%83,%84,%85,%86,%87,%88,%89,%90,%91,%92,%93,%94,%95}, {%96,%97,%98,%99}, %100, p, 1, 1, 0; }"
   : "+f"(d[0]), "+f"(d[1]), "+f"(d[2]), "+f"(d[3]), "+f"(d[4]), "+f"(d[5]), "+f"(d[6]), "+f"(d[7]), "+f"(d[8]), "+f"(d[9]), "+f"(d[10]), "+f"(d[11]), "+f"(d[12]), "+f"(d[13]), "+f"(d[14]), "+f"(d[15]), "+f"(d[16]), "+f"(d[17]), "+f"(d[18]), "+f"(d[19]), "+f"(d[20]), "+f"(d[21]), "+f"(d[22]), "+f"(d[23]), "+f"(d[24]), "+f"(d[25]), "+f"(d[26]), "+f"(d[27]), "+f"(d[28]), "+f"(d[29]), "+f"(d[30]), "+f"(d[31]), "+f"(d[32]), "+f"(d[33]), "+f"(d[34]), "+f"(d[35]), "+f"(d[36]), "+f"(d[37]), "+f"(d[38]), "+f"(d[39]), "+f"(d[40]), "+f"(d[41]), "+f"(d[42]), "+f"(d[43]), "+f"(d[44]), "+f"(d[45]), "+f"(d[46]), "+f"(d[47]), "+f"(d[48]), "+f"(d[49]), "+f"(d[50]), "+f"(d[51]), "+f"(d[52]), "+f"(d[53]), "+f"(d[54]), "+f"(d[55]), "+f"(d[56]), "+f"(d[57]), "+f"(d[58]), "+f"(d[59]), "+f"(d[60]), "+f"(d[61]), "+f"(d[62]), "+f"(d[63]), "+f"(d[64]), "+f"(d[65]), "+f"(d[66]), "+f"(d[67]), "+f"(d[68]), "+f"(d[69]), "+f"(d[70]), "+f"(d[71]), "+f"(d[72]), "+f"(d[73]), "+f"(d[74]), "+f"(d[75]), "+f"(d[76]), "+f"(d[77]), "+f"(d[78]), "+f"(d[79]), "+f"(d[80]), "+f"(d[81]), "+f"(d[82]), "+f"(d[83]), "+f"(d[84]), "+f"(d[85]), "+f"(d[86]), "+f"(d[87]), "+f"(d[88]), "+f"(d[89]), "+f"(d[90]), "+f"(d[91]), "+f"(d[92]), "+f"(d[93]), "+f"(d[94]), "+f"(d[95]) : "r"(a0), "r"(a1), "r"(a2), "r"(a3), "l"(db), "r"(sd));
}
__device__ __forceinline__ void wgmma_ss_8_10(float* d, uint64_t da, uint64_t db, int sd) {
  asm volatile("{ .reg .pred p; setp.ne.b32 p, %6, 0; wgmma.mma_async.sync.aligned.m64n8k16.f32.bf16.bf16 {%0,%1,%2,%3}, %4, %5, p, 1, 1, 1, 0; }"
   : "+f"(d[0]), "+f"(d[1]), "+f"(d[2]), "+f"(d[3]) : "l"(da), "l"(db), "r"(sd));
}
__device__ __forceinline__ void wgmma_ss_192_01(float* d, uint64_t da, uint64_t db, int sd) {
  asm volatile("{ .reg .pred p; setp.ne.b32 p, %98, 0; wgmma.mma_async.sync.aligned.m64n192k16.f32.bf16.bf16 {%0,%1,%2,%3,%4,%5,%6,%7,%8,%9,%10,%11,%12,%13,%14,%15,%16,%17,%18,%19,%20,%21,%22,%23,%24,%25,%26,%27,%28,%29,%30,%31,%32,%33,%34,%35,%36,%37,%38,%39,%40,%41,%42,%43,%44,%45,%46,%47,%48,%49,%50,%51,%52,%53,%54,%55,%56,%57,%58,%59,%60,%61,%62,%63,%64,%65,%66,%67,%68,%69,%70,%71,%72,%73,%74,%75,%76,%77,%78,%79,%80,%81,%82,%83,%84,%85,%86,%87,%88,%89,%90,%91,%92,%93,%94,%95}, %96, %97, p, 1, 1, 0, 1; }"
   : "+f"(d[0]), "+f"(d[1]), "+f"(d[2]), "+f"(d[3]), "+f"(d[4]), "+f"(d[5]), "+f"(d[6]), "+f"(d[7]), "+f"(d[8]), "+f"(d[9]), "+f"(d[10]), "+f"(d[11]), "+f"(d[12]), "+f"(d[13]), "+f"(d[14]), "+f"(d[15]), "+f"(d[16]), "+f"(d[17]), "+f"(d[18]), "+f"(d[19]), "+f"(d[20]), "+f"(d[21]), "+f"(d[22]), "+f"(d[23]), "+f"(d[24]), "+f"(d[25]), "+f"(d[26]), "+f"(d[27]), "+f"(d[28]), "+f"(d[29]), "+f"(d[30]), "+f"(d[31]), "+f"(d[32]), "+f"(d[33]), "+f"(d[34]), "+f"(d[35]), "+f"(d[36]), "+f"(d[37]), "+f"(d[38]), "+f"(d[39]), "+f"(d[40]), "+f"(d[41]), "+f"(d[42]), "+f"(d[43]), "+f"(d[44]), "+f"(d[45]), "+f"(d[46]), "+f"(d[47]), "+f"(d[48]), "+f"(d[49]), "+f"(d[50]), "+f"(d[51]), "+f"(d[52]), "+f"(d[53]), "+f"(d[54]), "+f"(d[55]), "+f"(d[56]), "+f"(d[57]), "+f"(d[58]), "+f"(d[59]), "+f"(d[60]), "+f"(d[61]), "+f"(d[62]), "+f"(d[63]), "+f"(d[64]), "+f"(d[65]), "+f"(d[66]), "+f"(d[67]), "+f"(d[68]), "+f"(d[69]), "+f"(d[70]), "+f"(d[71]), "+f"(d[72]), "+f"(d[73]), "+f"(d[74]), "+f"(d[75]), "+f"(d[76]), "+f"(d[77]), "+f"(d[78]), "+f"(d[79]), "+f"(d[80]), "+f"(d[81]), "+f"(d[82]), "+f"(d[83]), "+f"(d[84]), "+f"(d[85]), "+f"(d[86]), "+f"(d[87]), "+f"(d[88]), "+f"(d[89]), "+f"(d[90]), "+f"(d[91]), "+f"(d[92]), "+f"(d[93]), "+f"(d[94]), "+f"(d[95]) : "l"(da), "l"(db), "r"(sd));
}

#define HINT(x) x

__global__ void __cluster_dims__(2, 1, 1) __launch_bounds__(384, 1) fused_kernel(const uint8_t* __restrict__ pk, uint64_t dv,
    uint64_t dsh, const __nv_bfloat16* __restrict__ pssm, const __nv_bfloat16* __restrict__ pD, uint8_t* ps, const __grid_constant__ Params p) {
  extern __shared__ __align__(1024) uint8_t smem_raw[];
  const uint32_t t_start = clk();
  const uint32_t sb = smem_u32(smem_raw);
  const uint32_t bars = sb + O_BAR;
  const int tid = threadIdx.x, lane = tid & 31;
  const int warp = __shfl_sync(0xffffffffu, tid >> 5, 0);
  {
    const int b = blockIdx.x, w = (tid >> 5) & 3, r = lane >> 2, c = lane & 3, g = tid >> 7, t = (b >> 2) * 64 + r * 8;
    const uint32_t x = r * 64 + ((c ^ (r >> 1)) << 4), o = t * (D_ * 2) + (b & 3) * 64 + c * 16, mv = tid << 24 >> 31, ms = tid >= 352 ? -1 : 0;
    auto pick = [&](uint64_t d, uint32_t m) { return (uint64_t)((uint32_t)(d >> 32) & m) << 32 | (uint32_t)d & m; };
    const uint32_t d = sb + kreg(0) + x + w * 1024 + (2 >> g) * voff(0);
    const uint8_t* const a = pk + pick(dv, mv) + (o + w * (D_ * 4));
    cpa16(d, a, g ? 16 : 0);
    cpa16(d + 512, a + D_ * 2, g ? 16 : 0);
    cpa16(settag(d - w * 512, mv, sb + O_EP - 4096) + 4096,
          pk + (pick(dsh, ms) | pick((uint8_t*)(g_sync + Y_EP + b * 32) - pk, mv)) + (settag(max((int)o + (w - 3) * (D_ * 2), 0), ms, (b & 3) * 256 + x) & ~mv), g && (t | mv | ms) ? 16 : 0);
    if (tid == 256) TSTAMP(74);
  }
  const int b = blockIdx.x, kh = b & 1;
  const int part = b / 20, grp = part < NE0 ? 0 : part < NE ? 1 : 2;
  auto loadwm = [&]() {
    const int x = b % 20, col = part < 5 ? (x >> 2) * D_ + part * 128 + (x & 3) * 32 : 5 * D_ + x * 32;
    mbar_expect(bars + 8 * B_WM, 40960);
    tma3d(sb + O_WM, &p.m_wm, col, 0, 0, bars + 8 * B_WM);
  };
  auto BAR = [&](int i) { return bars + 8 * i; };
#define ROLE const int rb = b >> 3, fs = b & 7, vr = min(rb, 14) / 3, vt = min(rb, 14) % 3; \
  const uint32_t ord = VR == 3 ? (vr == 4 ? 0x34210 : 0x43210) : vr == 3 ? 0x42310 : vr == 4 ? 0x32410 : 0x43210; uint8_t* const misc = ps + rb * 4096; \
  (void)fs; (void)vt; (void)ord; (void)misc
  if (tid == 0) TSTAMP(63);
#define EPOCHU const uint32_t ep = __shfl_sync(0xffffffffu, lds32(sb + O_EP), 0) + 1

  if (warp < 4) {
    if (tid == 32) TSTAMP(118);
    asm volatile("setmaxnreg.dec.sync.aligned.u32 40;");
    if (tid == 32) TSTAMP(120);
    asm volatile("barrier.cluster.arrive.relaxed.aligned;" ::: "memory");
    const int hw = warp - 2;
    auto kvcheck = [&](int j, uint32_t ep) {
      const uint32_t a = sb + bnd(j) + U_KV + lane * 32;
      uint32_t x[4];
      mbar_wait(BAR(B_KV + j), 0);
#pragma unroll
      for (int i = 0; i < 4; i++) x[i] = lds32(a + i * 1024 + (lane & 28)) ^ ep;
      if (__any_sync(0xffffffffu, (x[0] | x[1] | x[2] | x[3]) & 1)) {
#pragma unroll 1
        for (int i = 0; i < 4096; i += 1024) refetch_all(ps + (page(G_KV + j, b) + lane * 32 + i), lane & 28, a + i, ep);
      }
      __syncwarp();
      if (lane == 0) mbar_arrive(BAR(B_OK + j));
    };
    if (warp == 0) {
      bar_sync(1, 384);
      EPOCHU;
      if (lane == 0) TSTAMP(0);
      __syncwarp();
      ROLE;
      {
        const uint32_t* f = g_sync + Y_KV + (min(lane, 4) * 4 + (b >> 5)) * 32;
        const uint32_t tw = lane != 5 ? T_W0 : b * D_WM + T_WM2 - 20 * NE * D_WM;
        uint32_t pend = (b < 120 && grp == 2 ? 127 : 95) - PK;
        int it = 0;
        do {
          uint32_t v = ep * 32;
          HINT(if (lane < 5 && (pend & 31)) v = ldr(f));
          uint32_t m = __ballot_sync(0xffffffffu, (lane < 5 ? (int)(v - ep * 32) >= 0 : clk() - t_start >= tw) || ++it > 100000) & pend;
          pend &= ~m;
          uint32_t ck = m & EV0;
          for (; m; m &= m - 1) {
            const int j = __ffs(m) - 1;
            if (elect()) {
              if (j < 5) {
                TSTAMP(2 + j);
                mbar_expect(BAR(B_KV + j), 4096);
                bulk_ld(sb + bnd(j) + U_KV, ps + page(G_KV + j, b), 4096, BAR(B_KV + j));
              } else if (j == 5) {
                loadwm();
                TSTAMP(109);
              } else {
                bulk_pf((kh ? p.wu : p.wg) + (b >> 1) * 2 * F_, 6144);
                TSTAMP(108);
              }
            }
          }
          for (; ck; ck &= ck - 1) kvcheck(__ffs(ck) - 1, ep);
        } while (pend);
      }
      {
        const int rl = (ord >> (min(lane, 19) & 28)) & 7;
        const uint32_t* const cnt = (const uint32_t*)(misc + M_X) + rl * 2 + ((min(lane, 19) >> 1) & 1);
        sts32(sb + O_XT + lane * 4, tile(rb, rl * 4 + (lane & 3)));
        __syncwarp();
        uint32_t known = 0;
        int slot = 4;
#pragma unroll 1
        for (int i = -AH; i < 20; i++) {
          const int s = i < 0 ? i + AH : i, rd = (ord >> (s & 28)) & 7;
          const uint32_t dst = sb + slot * SLOT, full = BAR(B_FULL + slot);
          const uint8_t* const xs = ps + (tile(rb, rd * 4 + (s & 3)) + kh * 16384);
          auto loadx = [&]() {
            asm volatile("{ .reg .pred p; elect.sync _|p, 0xffffffff;\n @p cp.async.bulk.shared::cluster.global.mbarrier::complete_tx::bytes.multicast::cluster [%0], [%1], 4096, [%2], %3; }"
                         ::"r"(dst + 24576 + kh * 4096), "l"(xs), "r"(full), "h"((uint16_t)3) : "memory");
          };
          auto loadw = [&]() {
            mbar_wait(full + 8 * (B_EMPTY - B_FULL), (0xc0fc0 >> s) & 1);
            asm volatile("{ .reg .pred p; elect.sync _|p, 0xffffffff;\n @p mbarrier.arrive.expect_tx.shared::cta.b64 _, [%2], 32768;\n"
                         " @p cp.async.bulk.tensor.4d.shared::cluster.global.mbarrier::complete_tx::bytes [%0], [%1, {0, %3, %4, 0}], [%2]; }"
                         ::"r"(dst), "l"(&p.m_w1), "r"(full), "r"(rd * 128 + (s & 3) * 32), "r"(fs * 3) : "memory");
          };
          uint32_t v = ep * 16 - 1;
          HINT(if (i >= 0 && (~known >> s) & PD) v = ldr(cnt));
          if (i >= AH && (known >> s) & 1) {
            loadw();
            loadx();
          } else {
            if ((uint32_t)i >= AH) loadw();
            if (lane == 0) TS3(2, s);
            if (i >= 0) {
              HINT(if (!((known >> s) & 1)) poll_lane(v, cnt, ep * 16, s));
              loadx();
            }
          }
          if (i >= 0 && lane == 0) TS3(3, s);
          if (((PFW | PF2) << AH >> (i + AH)) & 1) {
            const int k = __popc((PFW | PF2) << (31 - s));
            if (elect()) bulk_pf(k < 5 ? (kh ? p.wu : p.wg) + (k * 128 + (b >> 1) * 2) * F_ : p.w2 + b * 7680 + (k - 5) * 2560, k < 5 ? 6144 : 5120);
          }
          if (lane == 0 && i == -1) TSTAMP(10);
          if (lane == 0 && i == 0) TSTAMP(19);
          if (lane == 0 && i == 16) TSTAMP(1);
          slot = i == -1 ? 4 : slot == 5 ? 0 : slot + 1;
          known |= __ballot_sync(0xffffffffu, (int)(v - ep * 16) >= 0);
        }
      }
      __syncwarp();
      asm volatile("barrier.cluster.wait.aligned;" ::: "memory");
      if ((sb & 0xffffff) != SD) __trap();
#pragma unroll 1
      for (int s = 0; s < 10; s++) {
        const int e = s < 7 ? s : s - 7;
        const uint32_t d = sb + w2entry(e), st = e == 6 ? SLOT : 8192;
        const int k0 = (fs ^ (s < 4 ? s >> 1 : s & 1)) * 192, c0 = ocol(b, s < 4 ? s & 1 : s >> 1);
        mbar_wait(BAR(s >= 7 ? B_W2E + e : B_EMPTY + min(s, 5)), s < 4);
        if (elect()) {
          mbar_expect(BAR(B_W2F + e), 24576);
#pragma unroll
          for (int i = 0; i < 3; i++) tma2d(d + i * st, &p.m_w2, c0, k0 + i * 64, BAR(B_W2F + e));
        }
      }
    } else {
      uint32_t dd = 0;
      if (warp == 1) {
        mbar_init(BAR(B_SSM), 1);
        unrolled<NLD>([&](auto I) {
          constexpr uint32_t e = nth_load(I.v), n = e & 15, kind = (e >> 4) & 15;
          while (clk() - t_start < (e >> 8) + (n == 5 ? (b >> 2) * D_Q : 0)) {}
          if (elect()) {
            if constexpr (kind == 0) {
              const uint32_t d = sb + kreg(n), bar = BAR(B_K + n);
              const int ch = n * 128 + (b & 3) * 32, tg = (b >> 2) * 8;
              mbar_expect(bar, 9984);
              tma3d(d, &p.m_k, ch, tg, 0, bar);
              tma3d(d + voff(n), &p.m_v, ch, tg, 0, bar);
              tma3d(d + 4096, &p.m_kh, ch, tg - 1, 5, bar);
              bulk_ld(d + 5632, pk + dsh + ch * 8, 256, bar);
            } else if constexpr (kind == 2) {
              if (grp == n) loadwm();
            } else if constexpr (kind == 1 && n < 5) {
              mbar_expect(BAR(B_SSM + n), 4096);
              bulk_ld(sb + bnd(n) + U_RAW, pssm + (size_t)(n * 128 + b) * S_, 4096, BAR(B_SSM + n));
            } else {
              mbar_expect(BAR(B_QIN), 20480);
              tma3d(sb + O_REG, &p.m_q, 0, b * 16, 0, BAR(B_QIN));
            }
            TSTAMP(96 + I.v);
          }
          if constexpr (I.v == 0) {
            static_assert(e % 256 == 16, "first load");
#pragma unroll
            for (int i = B_SSM + 1; i < B_PL + 5; i++) mbar_init(BAR(i), i < B_PL ? 1 : 2);
            bar_arrive(1, 384);
            if (lane == 0) TSTAMP(112);
          }
        });
        mbar_wait(BAR(B_PL), 0);
        if (lane < 5) asm volatile("mbarrier.expect_tx.relaxed.cta.shared::cta.b64 [%0], 4096;" ::"r"(BAR(B_PR + lane)) : "memory");
      } else {
        uint32_t x[10];
        asm volatile("ld.global.nc.u16 %0, [%1];" : "=r"(dd) : "l"(pD + min(lane, 4) * 128 + b) : "memory");
#pragma unroll
        for (int i = 0; i < 10; i++) x[i] = ldr((const uint32_t*)p.c + lane + i * 32);
#pragma unroll
        for (int j = 0; j < 5; j++) {
          if (hw && lane < 19) sts128(sb + bnd(j) + (lane < 17 ? U_KV + 4096 + lane * 16 : lane == 17 ? U_RAW - 16 : U_ODD - 16), 0, 0, 0, 0);
        }
        if (tid == 96) TSTAMP(122);
        if (elect()) {
#pragma unroll
          for (int i = 0; i < 4; i++) asm volatile("prefetch.tensormap [%0];" ::"l"(&p.m_k + hw * 4 + i) : "memory");
        }
        bar_sync(1, 384);
        if (hw) {
#pragma unroll
          for (int i = 0; i < 10; i++)
            sts32(sb + O_SILU + i % 5 * 256 + (lane >> 2) * 32 + i / 5 * 16 + (lane & 3) * 4, pack2(__fdividef(blo(x[i]), 1.f + __expf(-blo(x[i]))), __fdividef(bhi(x[i]), 1.f + __expf(-bhi(x[i])))));
          fence_async_smem();
          __syncwarp();
          if (lane < 5) mbar_arrive(BAR(B_PL + lane));
        }
      }
      uint32_t xl = (lane ^ lane >> 3) * 16;
      auto rowsum = [&](int h, uint8_t* og) {
        float z[4] = {0.f, 0.f, 0.f, 0.f};
        auto acc = [&](uint32_t v) { const float f = blo(v), g = bhi(v); z[0] += f; z[1] = fmaf(f, f, z[1]); z[2] += g; z[3] = fmaf(g, g, z[3]); };
        uint32_t a = sb + O_REG + h * 512 + xl;
        uint4 x = lds128(a), y = lds128(a + 1024);
#pragma unroll 1
        for (int i = 0; i < 10; i++) {
          a += 2048;
          const uint4 u = lds128(a), v = lds128(a + 1024);
          if (og) { stg128(og, x.x, x.y, x.z, x.w); stg128(og + 64, y.x, y.y, y.z, y.w); og += 128; }
          acc(x.x); acc(x.y); acc(x.z); acc(x.w); acc(y.x); acc(y.y); acc(y.z); acc(y.w);
          x = u; y = v;
        }
        z[0] += z[2]; z[1] += z[3];
#pragma unroll
        for (int i = 1; i < 3; i++) { z[0] += __shfl_xor_sync(0xffffffffu, z[0], i); z[1] += __shfl_xor_sync(0xffffffffu, z[1], i); }
        z[0] *= 1.f / D_;
        return make_float2(z[0], fmaxf(z[1] * (1.f / D_) - z[0] * z[0], 0.f) + 1e-5f);
      };
      {
        EPOCHU;
#pragma unroll 1
        for (uint64_t ev = warp == 1 ? EV1 : hw ? EV3 : EV2; ev; ev >>= 8) {
          const int j = ev & 7;
          if (ev & 16) {
            const float dj = blo(__shfl_sync(0xffffffffu, dd, j));
            mbar_wait(BAR(B_SSM + j), 0);
            if (lane == 0 && j == 0) TSTAMP(77);
#pragma unroll 1
            for (int h = 0; h < 4096; h += 2048) {
              const uint32_t ra = sb + bnd(j) + U_RAW + h + lane * 16;
              uint4 w[4];
              uint32_t pv[4];
#pragma unroll
              for (int i = 0; i < 4; i++) { w[i] = lds128(ra + i * 512); pv[i] = lds32(ra + i * 512 - 4); }
              if (!(h | lane)) { w[0].x = prmt(pack2(blo(w[0].x) + dj, 0.f), w[0].x, 0x7610); sts32(ra, w[0].x); }
#pragma unroll
              for (int i = 0; i < 4; i++) sts128(ra + (U_ODD - U_RAW) + i * 512, prmt(pv[i], w[i].x, 0x5432), prmt(w[i].x, w[i].y, 0x5432), prmt(w[i].y, w[i].z, 0x5432), prmt(w[i].z, w[i].w, 0x5432));
            }
            __syncwarp();
            if (lane == 0) { mbar_arrive(BAR(B_PL + j)); TSTAMP(32 + j); }
          } else if (ev & 32) {
            kvcheck(j, ep);
          } else {
            mbar_wait(BAR(B_QIN), 0);
            if (lane == 0 && j == 0) TSTAMP(9);
            const float2 z = rowsum(j, nullptr);
            const float rs = rbf(rsqrtf(z.y));
            if (!(xl & 48)) sts32(sb + O_LN + j * 32 + (xl >> 4), pack2(rs, -z.x * rs));
            __syncwarp();
            if (lane < 2) mbar_arrive(BAR(B_LN));
            if (lane == 0) TSTAMP(59 + 2 * j);
          }
        }
      }
      if (warp == 1) {
        EPOCHU;
        ROLE;
        uint32_t known = 0;
        const uint32_t* const cnt = g_sync + Y_Y + min(lane, 10) * 32;
        const uint32_t target = ep * (lane < 5 ? 128 : 40);
        int ny = 0, nm = 0;
#pragma unroll 1
        for (int it = 0; ny < 5 || nm < 6; it++) {
          const int j = nm < 5 ? (ord >> (nm * 4)) & 7 : nm;
          uint32_t u = target;
          HINT(if (DM ? ~known & 31 : known != 2047) u = ldr(cnt));
          if (DM ? nm < 6 : (known >> (5 + j)) & 1) {
            uint4 v[5];
            uint32_t bad = 0, lo[5], hi[5];
#pragma unroll
            for (int k = 0; k < 5; k++) v[k] = ldr4(g_mod + j * D_ + k * 128 + lane * 4);
#pragma unroll
            for (int k = 0; k < 5; k++) {
              bad |= (v[k].x ^ ep) | (v[k].y ^ ep) | (v[k].z ^ ep) | (v[k].w ^ ep);
              lo[k] = pack2(__uint_as_float(v[k].x), __uint_as_float(v[k].y));
              hi[k] = pack2(__uint_as_float(v[k].z), __uint_as_float(v[k].w));
            }
            if (!__any_sync(0xffffffffu, bad & 3) || it > 200000) {
              if (nm < 5) {
                const uint32_t ma = sb + O_MA + nm * 768 + lane * 8, one = 0x3F803F80u, c0 = hadd2(lo[4], one), c1 = hadd2(hi[4], one);
                sts64(ma, hmul2(lo[2], hadd2(lo[1], one)), hmul2(hi[2], hadd2(hi[1], one)));
                sts64(ma + 256, hmul2(lo[2], lo[0]), hmul2(hi[2], hi[0]));
                sts64(ma + 512, c0, c1);
                __syncwarp();
                if (lane == 0) { mbar_arrive(BAR(B_PR + nm)); if (nm < 3) TSTAMP(nm < 2 ? 7 + nm : 79); }
                if (j == vr) {
                  sts64(sb + O_CS + (lane >> 1) * 32 + (lane & 1) * 8, c0, c1);
                  sts64(sb + O_CS + (lane >> 1) * 32 + (lane & 1) * 8 + 16, lo[3], hi[3]);
                  fence_async_smem();
                  __syncwarp();
                  if (lane == 0) mbar_arrive(BAR(B_CS));
                }
              } else {
#pragma unroll
                for (int k = 0; k < 5; k++) if ((k * 32 + lane >= 80) == kh) sts128(sb + O_GB + k * 512 + lane * 16 - kh * 1280, lo[k] << 16, lo[k] & 0xffff0000u, hi[k] << 16, hi[k] & 0xffff0000u);
              }
              nm++;
            }
          }
          known |= __ballot_sync(0xffffffffu, (int)(u - target) >= 0 || it > 100000) & 2047;
          if (ny < 5) {
            const int y = (ord >> (ny * 4)) & 7;
            if (nm > 5 && ny >= 2) mbar_wait(BAR(B_YE + (ny & 1)), ny >> 2);
            if (((known >> y) & 1) && (ny < 2 || mbar_test(BAR(B_YE + (ny & 1)), ny >> 2) || it > 200000)) {
              if (elect()) {
                if (ny < 2) TSTAMP(47 + ny);
                bulk_ld(sb + (ny & 1 ? O_BP : O_Y), ps + page(G_Y + y, b), 4096, BAR(B_PR + ny));
              }
              ny++;
            }
          }
        }
        __syncwarp();
        if (lane < 6) mbar_expect(BAR(B_HF + lane), 8192);
        if (lane == 0) { sts128(sb + O_BP + 6144, 0, 0, 0, 0); mbar_arrive(BAR(B_VV)); }
        mbar_wait(BAR(B_YE + 1), 1);
      } else {
        uint32_t ya = lane * 32 + (lane & 4) * 4, pl = (lane & 3) * 16;
        keep(ya); keep(xl); keep(pl);
        mbar_wait(BAR(B_LN), 0);
        ROLE;
        const uint32_t tt = (lds32(sb + O_EP) & 1) - 1, ln[2] = {lds32(sb + O_LN + (lane & 28)), lds32(sb + O_LN + 32 + (lane & 28))};
#pragma unroll 1
        for (int it = 0; it != 10;) {
          const int j = (ord >> (it * 2 & 28)) & 7, odd = (it >> 1) & 1, g = (it & 1) * 2 + hw;
          const uint32_t pm = sb + O_MA + (it & 14) * 384 + g * 64, yo = sb + (odd ? O_BP : O_Y) + g * 1024, qo = sb + O_REG + (j * 4 + g) * 1024;
          uint32_t y[8];
          if (!(it & 1)) mbar_wait(BAR(B_PR + ((it >> 1) & 7)), 0);
          if (!(xl | hw) && it < 6 && !(it & 1)) TSTAMP(it == 0 ? 49 : it == 2 ? 58 : 80);
          ldsm4t(addu(ya, yo), y[0], y[1], y[2], y[3]);
          ldsm4t(addu(ya, yo) ^ 16, y[4], y[5], y[6], y[7]);
          const uint4 q0 = lds128(addu(xl, qo)), a4 = lds128(addu(pl, pm)), b4 = lds128(addu(pl, pm) + 256), q1 = lds128(addu(xl, qo) + 512), c4 = lds128(addu(pl, pm) + 512);
          if ((__ballot_sync(0xffffffffu, ((y[0] ^ tt) | (y[1] ^ tt) | (y[2] ^ tt) | (y[3] ^ tt) | (y[4] ^ tt) | (y[5] ^ tt) | (y[6] ^ tt) | (y[7] ^ tt)) & 0x00010001u) & 15) && it < 16) {
#pragma unroll 1
            for (int hf = 0; hf < 32; hf += 16) refetch16(ps + (page(G_Y + j, b) + g * 1024 + (ya ^ hf)), (ya ^ hf) + yo, tt);
            __syncwarp();
            it += 16;
            continue;
          }
          const uint32_t ma[4] = {a4.x, a4.y, a4.z, a4.w}, mb[4] = {b4.x, b4.y, b4.z, b4.w};
          uint32_t q[8] = {q0.x, q0.y, q0.z, q0.w, q1.x, q1.y, q1.z, q1.w};
#pragma unroll
          for (int i = 0; i < 8; i++) q[i] = hfma2(hfma2(hfma2lh(q[i], ln[i >> 2]), ma[i & 3], mb[i & 3]), y[i], q[i]);
          uint8_t* const xg = ps + addu(xl, tile(rb, j * 4 + g) + (b & 4) * 4096 + (b & 3) * 1024);
          stg128(xg, tag0(hmul2(q[0], c4.x), tt), hmul2(q[1], c4.y), hmul2(q[2], c4.z), hmul2(q[3], c4.w));
          stg128(xg + 512, tag0(hmul2(q[4], c4.x), tt), hmul2(q[5], c4.y), hmul2(q[6], c4.z), hmul2(q[7], c4.w));
          asm volatile("{ .reg .pred p; elect.sync _|p, 0xffffffff; @p red.relaxed.gpu.global.add.u32 [%0], 1; @p mbarrier.arrive.shared::cta.b64 _, [%1]; }"
                       ::"l"(misc + M_X + j * 8 + (it & 1) * 4), "r"(BAR(B_YE + odd)) : "memory");
          sts128(addu(xl, qo), q[0], q[1], q[2], q[3]);
          sts128(addu(xl, qo) + 512, q[4], q[5], q[6], q[7]);
          if (!(xl | hw) && (it & 1)) TSTAMP(12 + ((it & 15) >> 1));
          if (!(xl | hw) && it == 0) TSTAMP(116);
          it = (it & 15) + 1;
        }
        const int lane = ya >> 5, t = hw * 32 + lane;
        EPOCHU;
        bar_sync(4, 64);
        const float2 z = rowsum(hw, p.out + ((t >> 2) * 1280 + pl + b * 20480));
        const uint32_t pa = pack2(-z.x, sqrtf(z.y));
        if (!(xl & 48))
          asm volatile("st.relaxed.gpu.global.v2.u32 [%0], {%1,%2};" ::"l"(misc + M_ST + fs * 128 + hw * 64 + (xl >> 3)), "r"(pa), "r"(tagf(__fdividef(1.f, bhi(pa) * bhi(pa)), ep)) : "memory");
        uint4 v;
        int it = 0;
        do v = ldr4((const uint32_t*)(misc + M_ST + t * 16)); while ((((v.y ^ ep) | (v.w ^ ep)) & 3) && ++it < 100000);
        sts128(sb + O_ST + t * 16, v.x, v.y, v.z, v.w);
        __syncwarp();
        if (lane == 0) mbar_arrive(BAR(B_ST + hw));
        if (t == 0) TSTAMP(52);
      }
      ROLE;
      EPOCHU;
      int lane;
      asm volatile("mov.u32 %0, %%laneid;" : "=r"(lane));
      {
        HINT(poll_ge(g_sync + Y_VV + fs * 32, ep * 128));
        uint32_t v[20], bad;
        int it = 0;
        const uint32_t* g = g_vv + fs * 1920 + (hw + 1) * 128 + lane;
        do {
          bad = 0;
#pragma unroll
          for (int k = 0; k < 20; k++) v[k] = ldr(g + ((k % 5) * 384 + (k / 5) * 32));
#pragma unroll
          for (int k = 0; k < 20; k++) bad |= v[k] ^ ep;
        } while (__any_sync(0xffffffffu, bad & 1) && ++it < 100000);
#pragma unroll
        for (int k = 0; k < 4; k++) sts128(sb + O_BP + ((hw + 1) * 128 + k * 32 + lane) * 16, v[5 * k], v[5 * k + 1], v[5 * k + 2], hadd2(v[5 * k + 3], v[5 * k + 4]));
        fence_async_smem();
        __syncwarp();
      }
      if (lane == 0) mbar_arrive(BAR(B_VV));
      if (warp == 1) {
        if (lane == 0) TSTAMP(37);
        uint32_t v;
        int it = 0;
        do asm volatile("ld.acquire.gpu.global.u32 %0, [%1];" : "=r"(v) : "l"(misc + M_O) : "memory"); while ((int)(v - ep * 16) < 0 && ++it < 100000);
        asm volatile("fence.proxy.async.global;" ::: "memory");
        if (lane == 0) { mbar_arrive(BAR(B_X1)); TSTAMP(30); }
      } else {
        asm volatile("fence.acq_rel.gpu;" ::: "memory");
        __syncwarp();
        if (lane == 0) hint_add((uint32_t*)(misc + M_O));
      }
      __syncwarp();
      asm volatile("barrier.cluster.wait.aligned;" ::: "memory");
    }
  } else {
    const int isE = warp >= 8 ? 1 : 0;
    const int w = warp & 3, r = lane >> 2, c = lane & 3;
    const bool lead = (tid & 127) == 0;
    const int tb = b >> 2;
    if (tid == 256) TSTAMP(75);
    asm volatile("setmaxnreg.inc.sync.aligned.u32 232;");
    const uint32_t sb = __shfl_sync(0xffffffffu, smem_u32(smem_raw), 0);
    auto BAR = [&](int i) { return sb + O_BAR + 8 * i; };
    uint32_t ep;
#pragma unroll
    for (int i = 0; i < 7; i++) mbar_init(BAR(warp - 4 + 8 * i), i == 0 ? 2 << isE : i == 1 ? 4 : 1);
    asm volatile("fence.mbarrier_init.release.cluster;" ::: "memory");
    asm volatile("barrier.cluster.arrive.relaxed.aligned;" ::: "memory");
    if (lead) TSTAMP(76);
    auto first = [&]() { asm volatile("cp.async.wait_all;" ::: "memory"); bar_sync(1, 384); };
    uint32_t A[64];
    auto release = [&](uint32_t m) { if (w == 3 && lane < 12 && ((m >> (lane >> 1)) & 1)) mbar_arrive_cl(mapa(BAR(B_EMPTY + (lane >> 1)), lane & 1)); __syncwarp(); };
    auto aload = [&](int j) {
      const uint32_t sa = sb + bnd(j) + ((r & 1) ? U_RAW : U_ODD) + 4 * (8 * w + (r >> 1) - 3 + c);
#pragma unroll
      for (int g = 0; g < 16; g++) { A[4 * g] = lds32(sa + g * 256); A[4 * g + 1] = lds32(sa + g * 256 + 128); A[4 * g + 2] = lds32(sa + g * 256 + 16); A[4 * g + 3] = lds32(sa + g * 256 + 144); }
      if (lead) TSTAMP(89 + j);
    };
    auto gemv = [&]() {
      float d[16];
      const uint64_t db = mkdesc(SD + O_SILU, 32, 128, 0), da = mkdesc(SD + O_WM, 20480, 512, 2);
      mbar_wait(BAR(B_PL), 0);
      mbar_wait(BAR(B_WM), 0);
      if (lead) TSTAMP(81 + grp);
      if (EM == 2 && w < 2 && lane == 0) hint_add(g_sync + Y_MOD + part * 32);
      wg_fence();
#pragma unroll
      for (int kk = 0; kk < 20; kk++) wgmma_ss_8_10(d + (kk & 3) * 4, da + kk * 64, db + kk * 4, kk >> 2);
      wg_commit();
      wg_wait<0>();
      regfence<16>(d);
#pragma unroll
      for (int i = 0; i < 4; i++) d[i] = (d[i] + d[4 + i]) + (d[8 + i] + d[12 + i]);
      if (EM == 1 && w < 2 && lane == 0) hint_add(g_sync + Y_MOD + part * 32);
      const uint32_t xa = sb + O_SILU + 2048 + (w & 1) * 64 + r * 8;
      if (c == 0 && w >= 2) sts64(xa, __float_as_uint(d[1]), __float_as_uint(d[3]));
      bar_sync(5 + isE, 128);
      if (w < 2) {
        const float2 e = lds64f(xa);
        if (c == 0) { str(g_mod + b * 32 + w * 16 + r, tagf(d[0] + e.x, ep)); str(g_mod + b * 32 + w * 16 + r + 8, tagf(d[2] + e.y, ep)); }
        __syncwarp();
        if (!DM && !EM && lane == 0) hint_add(g_sync + Y_MOD + part * 32);
      }
      if (lead) TSTAMP(grp == 2 ? 60 : 20 + grp);
    };
#pragma unroll 1
    for (int it = 0; it < 3; it++) {
      const int n = it ? it + 2 * isE : 0, tg = lane & 7;
      const bool real = it | isE;
      const uint32_t a = sb + kreg(n) + tg * 64 + ((w ^ (tg >> 1)) << 4) + (lane >> 3) * 4;
      if (it) mbar_wait(BAR(B_K + n), 0); else if (isE) first();
      if (lead && real) TSTAMP(69 + n);
      uint32_t kk[11], x[8];
      ep = lds32(sb + O_EP) + 1;
      const uint4 sw = lds128(sb + kreg(n) + 5632 + w * 64 + (lane & 24) * 2);
#pragma unroll
      for (int i = 0; i < 11; i++) kk[i] = lds32(a + (i < 3 ? 4096 + i * 512 : (i - 3) * 512));
#pragma unroll
      for (int i = 0; i < 8; i++) x[7 - i] = lds32(a + voff(n) + i * 512);
      const uint32_t w0 = prmt(sw.x, sw.z, 0x5410), w1 = prmt(sw.x, sw.z, 0x7632), w2 = prmt(sw.y, sw.w, 0x5410), w3 = prmt(sw.y, sw.w, 0x7632);
#pragma unroll
      for (int i = 0; i < 8; i++) x[7 - i] = hmul2(hfma2(kk[i + 3], w0, hfma2(kk[i + 2], w1, hfma2(kk[i + 1], w2, hmul2(kk[i], w3)))), x[7 - i]);
      hint_addp(!w && (PK ? it : real), g_sync + Y_KV + (n * 4 + (b & 3)) * 32);
      const int tw = (~tb & 7) ^ ((~lane & 1) << 2);
#pragma unroll
      for (int i = 0; i < 4; i++) x[2 * i] = settag(x[2 * i], tw == i ? 0x00010001u : 0u, -(ep & 1));
      const uint32_t o = page(G_KV + n, (b & 3) * 32 + w * 8 + (lane >> 3) * 2) + 4080 - tb * 128 - tg * 16;
      stg128p(real, ps + o, prmt(x[0], x[1], 0x5410), prmt(x[2], x[3], 0x5410), prmt(x[4], x[5], 0x5410), prmt(x[6], x[7], 0x5410));
      stg128p(real, ps + o + 4096, prmt(x[0], x[1], 0x7632), prmt(x[2], x[3], 0x7632), prmt(x[4], x[5], 0x7632), prmt(x[6], x[7], 0x7632));
      if (lead) TSTAMP(real ? 64 + n : 62);
      if (it == 0) {
        if (!isE) first();
        if (PK && isE) {
          const uint32_t o = (tid & 127) * 32 + (lane & 16);
          uint4 u, v;
          int k = 0;
          while (clk() - t_start < T_P) {}
          do { u = ldr4((const uint32_t*)(ps + (page(G_KV, b) + o))); v = ldr4((const uint32_t*)(ps + (page(G_KV, b) + (o ^ 16)))); }
          while (__any_sync(0xffffffffu, ((r & 2 ? r & 1 ? u.w : u.z : r & 1 ? u.y : u.x) ^ ep) & 1) && ++k < 100000);
          sts128(sb + bnd(0) + U_KV + o, u.x, u.y, u.z, u.w);
          sts128(sb + bnd(0) + U_KV + (o ^ 16), v.x, v.y, v.z, v.w);
          fence_async_smem();
          __syncwarp();
          if (lane == 0) mbar_arrive(BAR(B_OK));
          if (lead) TSTAMP(2);
        }
        asm volatile("barrier.cluster.wait.aligned;" ::: "memory");
        if (GE == 1 && isE > grp) gemv();
        mbar_wait(BAR(B_PL + isE), 0);
        aload(isE);
      }
      if (GE == 2 && it == 0 && isE > grp) gemv();
      if (!GE && it == 1 && !(isE | grp)) gemv();
    }
    if (MX && isE) bar_sync(8, 256);
#pragma unroll 1
    for (int j = isE; j < 5; j += 2) {
      const int u = tid & 127;
      const uint32_t pb = sb + (bnd(j) | 16384);
      float d[128];
      mbar_wait(BAR(B_OK + j), 0);
      if (lead) TSTAMP(53 + j);
      const uint64_t db = mkdesc(SD + U_KV, 16, 128, 0) | bnd(j) >> 4;
      wg_fence();
        wgmma_rs_32_0(d + 0, A[0], A[1], A[2], A[3], db + 0, 0);
        wgmma_rs_32_0(d + 16, A[0], A[1], A[2], A[3], db + 32, 0);
        wgmma_rs_32_0(d + 32, A[0], A[1], A[2], A[3], db + 64, 0);
        wgmma_rs_32_0(d + 48, A[0], A[1], A[2], A[3], db + 96, 0);
        wgmma_rs_32_0(d + 0, A[4], A[5], A[6], A[7], db + 16, 1);
        wgmma_rs_32_0(d + 16, A[4], A[5], A[6], A[7], db + 48, 1);
        wgmma_rs_32_0(d + 32, A[4], A[5], A[6], A[7], db + 80, 1);
        wgmma_rs_32_0(d + 48, A[4], A[5], A[6], A[7], db + 112, 1);
        wgmma_rs_32_0(d + 0, A[8], A[9], A[10], A[11], db + 32, 1);
        wgmma_rs_32_0(d + 16, A[8], A[9], A[10], A[11], db + 64, 1);
        wgmma_rs_32_0(d + 32, A[8], A[9], A[10], A[11], db + 96, 1);
        wgmma_rs_32_0(d + 64, A[0], A[1], A[2], A[3], db + 128, 0);
        wgmma_rs_32_0(d + 0, A[12], A[13], A[14], A[15], db + 48, 1);
        wgmma_rs_32_0(d + 16, A[12], A[13], A[14], A[15], db + 80, 1);
        wgmma_rs_32_0(d + 32, A[12], A[13], A[14], A[15], db + 112, 1);
        wgmma_rs_32_0(d + 48, A[8], A[9], A[10], A[11], db + 128, 1);
        wgmma_rs_32_0(d + 0, A[16], A[17], A[18], A[19], db + 64, 1);
        wgmma_rs_32_0(d + 16, A[16], A[17], A[18], A[19], db + 96, 1);
        wgmma_rs_32_0(d + 32, A[16], A[17], A[18], A[19], db + 128, 1);
        wgmma_rs_32_0(d + 64, A[4], A[5], A[6], A[7], db + 144, 1);
        wgmma_rs_32_0(d + 0, A[20], A[21], A[22], A[23], db + 80, 1);
        wgmma_rs_32_0(d + 16, A[20], A[21], A[22], A[23], db + 112, 1);
        wgmma_rs_32_0(d + 48, A[12], A[13], A[14], A[15], db + 144, 1);
        wgmma_rs_32_0(d + 32, A[20], A[21], A[22], A[23], db + 144, 1);
        wgmma_rs_32_0(d + 0, A[24], A[25], A[26], A[27], db + 96, 1);
        wgmma_rs_32_0(d + 16, A[24], A[25], A[26], A[27], db + 128, 1);
        wgmma_rs_32_0(d + 80, A[0], A[1], A[2], A[3], db + 160, 0);
        wgmma_rs_32_0(d + 64, A[8], A[9], A[10], A[11], db + 160, 1);
        wgmma_rs_32_0(d + 0, A[28], A[29], A[30], A[31], db + 112, 1);
        wgmma_rs_32_0(d + 16, A[28], A[29], A[30], A[31], db + 144, 1);
        wgmma_rs_32_0(d + 48, A[16], A[17], A[18], A[19], db + 160, 1);
        wgmma_rs_32_0(d + 32, A[24], A[25], A[26], A[27], db + 160, 1);
        wgmma_rs_32_0(d + 0, A[32], A[33], A[34], A[35], db + 128, 1);
        wgmma_rs_32_0(d + 16, A[32], A[33], A[34], A[35], db + 160, 1);
        wgmma_rs_32_0(d + 80, A[4], A[5], A[6], A[7], db + 176, 1);
        wgmma_rs_32_0(d + 64, A[12], A[13], A[14], A[15], db + 176, 1);
        wgmma_rs_32_0(d + 0, A[36], A[37], A[38], A[39], db + 144, 1);
        wgmma_rs_32_0(d + 48, A[20], A[21], A[22], A[23], db + 176, 1);
        wgmma_rs_32_0(d + 32, A[28], A[29], A[30], A[31], db + 176, 1);
        wgmma_rs_32_0(d + 16, A[36], A[37], A[38], A[39], db + 176, 1);
        wgmma_rs_32_0(d + 0, A[40], A[41], A[42], A[43], db + 160, 1);
        wgmma_rs_32_0(d + 96, A[0], A[1], A[2], A[3], db + 192, 0);
        wgmma_rs_32_0(d + 80, A[8], A[9], A[10], A[11], db + 192, 1);
        wgmma_rs_32_0(d + 64, A[16], A[17], A[18], A[19], db + 192, 1);
        wgmma_rs_32_0(d + 0, A[44], A[45], A[46], A[47], db + 176, 1);
        wgmma_rs_32_0(d + 48, A[24], A[25], A[26], A[27], db + 192, 1);
        wgmma_rs_32_0(d + 32, A[32], A[33], A[34], A[35], db + 192, 1);
        wgmma_rs_32_0(d + 16, A[40], A[41], A[42], A[43], db + 192, 1);
        wgmma_rs_32_0(d + 0, A[48], A[49], A[50], A[51], db + 192, 1);
        wgmma_rs_32_0(d + 96, A[4], A[5], A[6], A[7], db + 208, 1);
        wgmma_rs_32_0(d + 80, A[12], A[13], A[14], A[15], db + 208, 1);
        wgmma_rs_32_0(d + 64, A[20], A[21], A[22], A[23], db + 208, 1);
        wgmma_rs_32_0(d + 48, A[28], A[29], A[30], A[31], db + 208, 1);
        wgmma_rs_32_0(d + 32, A[36], A[37], A[38], A[39], db + 208, 1);
        wgmma_rs_32_0(d + 16, A[44], A[45], A[46], A[47], db + 208, 1);
        wgmma_rs_32_0(d + 0, A[52], A[53], A[54], A[55], db + 208, 1);
        wgmma_rs_32_0(d + 112, A[0], A[1], A[2], A[3], db + 224, 0);
        wgmma_rs_32_0(d + 96, A[8], A[9], A[10], A[11], db + 224, 1);
        wgmma_rs_32_0(d + 80, A[16], A[17], A[18], A[19], db + 224, 1);
        wgmma_rs_32_0(d + 64, A[24], A[25], A[26], A[27], db + 224, 1);
        wgmma_rs_32_0(d + 48, A[32], A[33], A[34], A[35], db + 224, 1);
        wgmma_rs_32_0(d + 32, A[40], A[41], A[42], A[43], db + 224, 1);
        wgmma_rs_32_0(d + 16, A[48], A[49], A[50], A[51], db + 224, 1);
        wgmma_rs_32_0(d + 0, A[56], A[57], A[58], A[59], db + 224, 1);
        wgmma_rs_32_0(d + 112, A[4], A[5], A[6], A[7], db + 240, 1);
        wgmma_rs_32_0(d + 96, A[12], A[13], A[14], A[15], db + 240, 1);
        wgmma_rs_32_0(d + 80, A[20], A[21], A[22], A[23], db + 240, 1);
        wgmma_rs_32_0(d + 64, A[28], A[29], A[30], A[31], db + 240, 1);
        wgmma_rs_32_0(d + 48, A[36], A[37], A[38], A[39], db + 240, 1);
        wgmma_rs_32_0(d + 32, A[44], A[45], A[46], A[47], db + 240, 1);
        wgmma_rs_32_0(d + 16, A[52], A[53], A[54], A[55], db + 240, 1);
        wgmma_rs_32_0(d + 0, A[60], A[61], A[62], A[63], db + 240, 1);
      wg_commit();
      bar_sync(5 + isE, 128);
      if (ER) release(0140242142 >> 6 * j);
      if (j < 3) mbar_wait(BAR(B_PL + 2 + j), 0);
      const uint32_t yoff = pb + w * 2048 + (127 + 2 * w - lane) * 16;
      const uint32_t yoff0 = yoff + (lane < 2 * w ? -2048 : 8192), yoff4 = yoff + (lane < 2 * w ? 6144 : 0);
      wg_wait<0>();
      regfence<128>(d);
      if (j == 4 || MX && j == 0) bar_arrive(8, 256);
      if (j == 4) bar_sync(5, 128);
      if (lead) TSTAMP(42 + j);
      if (EY == 2 && lead) hint_add(g_sync + Y_Y + j * 32);
#pragma unroll
      for (int z = 0; z < 8; z++) {
        uint32_t e[4];
#pragma unroll
        for (int i = 0; i < 4; i++) {
          const int x = 4 * z + i;
          e[i] = x < 31 ? pack2(d[4 * x] + d[4 * x + 6], d[4 * x + 1] + d[4 * x + 7]) : pack2(d[4 * x], d[4 * x + 1]);
        }
        if (z == 0 && c < w) e[0] = 0;
        stsm4t(z == 0 ? yoff0 : z == 4 ? yoff4 : z < 4 ? yoff + 8192 - 512 * z : yoff - 512 * (z - 4), e[0], e[1], e[2], e[3]);
      }
      uint8_t* g = ps + page(G_Y + j, u >> 1) + ((b & 97) | (b & 6) << 2 | (b & 24) >> 2) * 32 + ((u ^ (b >> 4)) & 1) * 16;
      if (EY & 1) hint_addp(!w && (EY == 1 || !j), g_sync + Y_Y + j * 32);
      bar_sync(5 + isE, 128);
      if (EY >= 4) hint_addp(!w && (EY == 4 || j), g_sync + Y_Y + j * 32);
#pragma unroll
      for (int i = 0; i < 2; i++) {
        const uint32_t pa = pb + u * 16 + i * 8192;
        const uint4 p0 = lds128(pa), p1 = lds128(pa + 2048), p2 = lds128(pa + 4096), p3 = lds128(pa + 6144);
        stg128(g + (i << 18), settag(hadd2(hadd2(p0.x, p1.x), hadd2(p2.x, p3.x)), 1, ep), hadd2(hadd2(p0.y, p1.y), hadd2(p2.y, p3.y)),
               hadd2(hadd2(p0.z, p1.z), hadd2(p2.z, p3.z)), hadd2(hadd2(p0.w, p1.w), hadd2(p2.w, p3.w)));
      }
      if (EY % 3 == 0) hint_addp(w == 3 && (!EY || j), g_sync + Y_Y + j * 32);
      if (lead) TSTAMP(84 + j);
      if (!ER) release(0140242142 >> 6 * j);
      if (j < 3) aload(j + 2);
      if (b < 120 && j == (GE == 3 ? max(2 * grp - 1, 0) : 2 * grp - 1)) gemv();
    }
    bar_sync(5 + isE, 128);
    release(isE ? 016 : 010);
    const int rh = isE;
    uint32_t hA[96];
    const uint32_t hb = sb + (isE ? O_REG : 24576) + w * 2048, hs = isE ? 8192 : SLOT;
    auto publish = [&](int kq) {
      asm volatile("st.async.weak.shared::cluster.mbarrier::complete_tx::bytes.v4.b32 [%0], {%1,%2,%3,%4}, [%5];" ::"r"(mapa(hb + lane * 16, kh ^ 1) + (kq >> 2) * hs + (kq & 3) * 512),
                   "r"(hA[4 * kq]), "r"(hA[4 * kq + 1]), "r"(hA[4 * kq + 2]), "r"(hA[4 * kq + 3]), "r"(mapa(BAR(B_HF + isE * 3), kh ^ 1) + (kq >> 2) * 8) : "memory");
      if (kq == 3 && tid == 256) TSTAMP(117);
    };
    {
      float ag[96], au[96], iv[2];
      int slot = 4, prev = 0, s = 0;
      int v0, vo;
      uint32_t vg;
      { ROLE; v0 = min(vr, VR) * 4; vo = (2 * vt + isE) * 256; vg = (fs * 5 + vr) * 384 + (2 * vt + isE) * 64 + 16 * w + r; }
      const uint32_t dbase = mkdesc(sb, 4096, 0, 0);
      uint32_t ck = sb + 24576 + rh * 4096 + w * 1024 + lane * 32 + (r & 1) * 16;
      keep(ck);
      const uint32_t emp = mapa(BAR(B_EMPTY), tid & 1);
      if (isE) bar_sync(8, 256);
      auto check = [&](uint32_t tag) {
        if ((tag ^ ep) & 1) refetch(ps + (lds32(sb + O_XT + s * 4) + rh * 16384 + (tid & 127) * 32), (r & 1) * 16, (ck + slot * SLOT) & ~31u, ep);
        __syncwarp();
        if (lead) TS3(isE, s);
        if (s && s < 20 && (s & 3) == 0 && tid == 128) TSTAMP(37 + (s >> 2));
        if (s == LH + LEAD * isE) { if (isE) bar_arrive(7, 256); else bar_sync(7, 256); }
      };
      auto stage = [&](float* vv) {
        const uint32_t dl = dbase + slot * (SLOT >> 4);
        const uint64_t dg = mkdesc(0, 0, 1024, 1) | dl, da = mkdesc(0, 0, 512, 2) | (dl + ((24576 + rh * 4096) >> 4));
        wg_wait<1>();
        wg_fence();
        if (vv) {
          wgmma_ss_8_10(vv, dg + vo, mkdesc(sb + O_CS, 32, 128, 0) + (s & 3) * 8, s & 3);
          wgmma_ss_8_10(vv, dg + vo + 128, mkdesc(sb + O_CS, 32, 128, 0) + (s & 3) * 8 + 4, 1);
          wg_commit();
        }
        const int sd = s, nx = s == 19 ? 5 : slot == 5 ? 0 : slot + 1;
        const uint32_t par = (0x1c0fc0 >> ++s) & 1;
        uint32_t in, tag;
        auto peek = [&]() { asm volatile("{ .reg .pred p; setp.ne.u32 p, %2, 0; @p ld.shared.u32 %0, [%1]; }" : "=r"(tag) : "r"(addu(ck, nx * SLOT)), "r"(in) : "memory"); };
        if (RP == 0) in = TW ? mbar_try(BAR(B_FULL + nx), par) : mbar_test(BAR(B_FULL + nx), par);
        wgmma_ss_192_01(ag, da, dg, sd);
        if (s > 2 && (tid & 126) == 0) mbar_arrive_cl(addu(emp, prev & 63));
        if (RP == 0) peek();
        if (RP == 1) in = TW ? mbar_try(BAR(B_FULL + nx), par) : mbar_test(BAR(B_FULL + nx), par);
        wgmma_ss_192_01(au, da, mkdesc(0, 0, 1024, 1) | (dl + 768), sd);
        if (RP == 1) peek();
        if (RP == 2) in = TW ? mbar_try(BAR(B_FULL + nx), par) : mbar_test(BAR(B_FULL + nx), par);
        wgmma_ss_192_01(ag, mkdesc(0, 0, 512, 2) | ((uint32_t)da + 2), mkdesc(0, 0, 1024, 1) | (dl + 128), 1);
        if (RP == 2) peek();
        wgmma_ss_192_01(au, mkdesc(0, 0, 512, 2) | ((uint32_t)da + 2), mkdesc(0, 0, 1024, 1) | (dl + 896), 1);
        wg_commit();
        prev = prev >> 8 | slot << 11;
        slot = nx;
        if (!in) { mbar_wait(BAR(B_FULL + nx), par); tag = lds32(addu(ck, nx * SLOT)); }
        check(tag);
      };
      mbar_wait(BAR(B_FULL + 4), 0);
      check(lds32(ck + 4 * SLOT));
      if (lead) TSTAMP(22 + isE);
#pragma unroll 1
      for (int end = v0, k = 0; k < 2; end = 20, k++) {
#pragma unroll 1
        while (s < end) stage(nullptr);
        if (k == 0) {
          float vv[4];
          mbar_wait(BAR(B_CS), 0);
          if (EVV) hint_addp(1, g_sync + Y_VV + vg / 1920 * 32);
#pragma unroll 1
          do stage(vv); while (s & 3);
          wg_wait<1>();
          regfence<4>(vv);
          if (c == 0) { str(g_vv + vg, settag(pack2(vv[0], vv[1]), 1, ep)); str(g_vv + vg + 8, settag(pack2(vv[2], vv[3]), 1, ep)); }
          __syncwarp();
          if (!EVV) hint_addp(1, g_sync + Y_VV + vg / 1920 * 32);
        }
      }
      {
        if (tid == 128) str(g_sync + Y_EP + b * 32, ep);
        wg_wait<1>();
        if ((tid & 126) == 0) mbar_arrive_cl(emp + 32);
        mbar_wait(BAR(B_ST + rh), 0);
        const float2 sa = lds64f(sb + O_ST + rh * 512 + w * 128 + r * 8), sc = lds64f(sb + O_ST + rh * 512 + w * 128 + r * 8 + 64);
        const uint32_t a0 = __float_as_uint(sa.x), a1 = __float_as_uint(sc.x);
        iv[0] = sa.y; iv[1] = sc.y;
        mbar_wait(BAR(B_VV), 0);
        const uint64_t dp = mkdesc(sb + O_BP, 16, 128, 0);
        wg_fence();
        wgmma_rs_192_0(ag, a0, a1, 0, 0, dp, 1);
        wgmma_rs_192_0(au, a0, a1, 0, 0, dp + 192, 1);
        wg_commit();
        wg_wait<1>();
        if ((tid & 126) == 0) mbar_arrive_cl(emp + 40);
        mbar_wait(BAR(isE ? B_ST : B_EMPTY + 2), !isE);
        wg_wait<0>();
      }
      regfence<96>(ag); regfence<96>(au);
      if (lead) TSTAMP(24 + isE);
#pragma unroll
      for (int kq = 0; kq < 12; kq++) {
#pragma unroll
        for (int i = 0; i < 4; i++) hA[4 * kq + i] = pack2(ag[8 * kq + 2 * i] * iv[i & 1] * au[8 * kq + 2 * i], ag[8 * kq + 2 * i + 1] * iv[i & 1] * au[8 * kq + 2 * i + 1]);
        if (kq < 4 * NPUB) publish(kq);
      }
      if (lead) TSTAMP(50 + isE);
    }
    float o[2][32];
    float2 gb[8];
    const uint32_t stg = hb + (lane & 15) * 128 + (((lane >> 4) ^ (lane & 7)) << 4);
    const int row = (b >> 3) * 128 + rh * 64 + 16 * w;
    auto ldgb = [&](int fin) {
#pragma unroll
      for (int u = 0; u < 8; u++) gb[u] = lds64f(sb + O_GB + (ocol(b & 6, fin) + 8 * u + 2 * c) * 4);
      if (fin >= 3) { if (elect()) bulk_wait_read<2>(); __syncwarp(); }
    };
    auto piece = [&](int fin, int u) {
      const float* x = o[fin & 1] + 8 * u;
      const float2 g0 = gb[2 * u], g1 = gb[2 * u + 1];
      stsm4((stg ^ u * 32) + fin % 3 * hs, pack2(x[0] * g0.x, x[1] * g0.y), pack2(x[2] * g0.x, x[3] * g0.y), pack2(x[4] * g1.x, x[5] * g1.y), pack2(x[6] * g1.x, x[7] * g1.y));
    };
    auto flush = [&](int fin) {
      fence_async_smem();
      __syncwarp();
      if (elect()) { tma2d_add(&p.m_out, hb + fin % 3 * hs, ocol(b, fin), row); bulk_commit(); }
    };
    unrolled<10>([&](auto I) {
      constexpr int s = I.v, e = s < 7 ? s : s - 7, src = s < 4 ? s >> 1 : s & 1, blk = s < 4 ? s & 1 : s >> 1;
      constexpr int fin = s == 3 ? 0 : blk - 1;
      const uint64_t dw = mkdesc(sb + w2entry(e), 1024 * s, 1024, 1);
      if (s == 3 || s >= 4 && !src) ldgb(fin);
      if (s == 4) mbar_wait(BAR(B_X1), 0);
      mbar_wait(BAR(B_W2F + e), s >= 7);
      if (s == 6 && tid == 256) TSTAMP(123);
      TS2(3 * s);
      unrolled<12>([&](auto J) {
        constexpr int kk = J.v, n = s < 4 ? kk : src * 12 + kk;
        if (s == 2 && !(kk & 3)) {
          mbar_wait_cluster(BAR(B_HF + isE * 3 + (kk >> 2)), 0);
          if (kk == 0 && lead) TSTAMP(26 + isE);
#pragma unroll
          for (int i = kk; i < kk + 4; i++) {
            const uint4 v = lds128(hb + lane * 16 + (i >> 2) * hs + (i & 3) * 512);
            hA[48 + 4 * i] = v.x; hA[49 + 4 * i] = v.y; hA[50 + 4 * i] = v.z; hA[51 + 4 * i] = v.w;
          }
        }
        if (kk == 0 || s == 2 && !(kk & 3)) wg_fence();
        const uint32_t* h = hA + src * 48 + 4 * kk;
        wgmma_rs_64_1(o[blk & 1], h[0], h[1], h[2], h[3], dw + (kk >> 2) * (e == 6 ? SLOT >> 4 : 512) + (kk & 3) * 128, (src | kk) ? 1 : 0);
        if (s < 2 && (s * 12 + kk) % PUBD == PUBD - 1 && 4 * NPUB + (s * 12 + kk) / PUBD < 12) publish(4 * NPUB + (s * 12 + kk) / PUBD);
        if (kk == QD - 1 && s >= 1 && (s < 4 || !src)) {
          wg_commit();
          wg_wait<1>();
          if (s < 4 && lead) mbar_arrive(BAR(B_W2E + s - 1));
          if (s >= 3) regfence<32>(o[fin & 1]);
          if (s == 4) flush(0);
          TS2(3 * s + 2);
        }
        if (s == 3 && kk >= QD - 1 && (kk - QD + 1) % 2 == 0 && (kk - QD + 1) / 2 < 4) piece(0, (kk - QD + 1) / 2);
        if (s >= 4 && n >= QD - 1 && (n - QD + 1) % 3 == 0 && (n - QD + 1) / 3 < 4) piece(fin, (n - QD + 1) / 3);
        if (s >= 4 && n == QD + 14) flush(fin);
      });
      wg_commit();
      TS2(3 * s + 1);
    });
    ldgb(4);
    mbar_wait(BAR(B_X1), 0);
    wg_wait<0>();
    regfence<32>(o[0]);
    if (lead) TSTAMP(28 + isE);
#pragma unroll
    for (int u = 0; u < 4; u++) piece(4, u);
    flush(4);
    if (tid == 128) TSTAMP(119);
    if (elect()) bulk_wait_read<0>();
    if (tid == 256) TSTAMP(121);
    if (!isE) {
      if (lead) TSTAMP(31);
    }
  }
}

#define L2PROMO CU_TENSOR_MAP_L2_PROMOTION_L2_128B
typedef CUresult (*EncodeFn)(CUtensorMap*, CUtensorMapDataType, cuuint32_t, void*, const cuuint64_t*, const cuuint64_t*, const cuuint32_t*,
                             const cuuint32_t*, CUtensorMapInterleave, CUtensorMapSwizzle, CUtensorMapL2promotion, CUtensorMapFloatOOBfill);

void make_map(EncodeFn enc, CUtensorMap* m, const void* ptr, uint64_t inner, uint64_t outer, uint32_t bi, uint32_t bo, CUtensorMapSwizzle sw) {
  cuuint64_t d[2] = {inner, outer};
  cuuint64_t s[1] = {inner * 2};
  cuuint32_t bx[2] = {bi, bo};
  cuuint32_t e[2] = {1, 1};
  enc(m, CU_TENSOR_MAP_DATA_TYPE_BFLOAT16, 2, const_cast<void*>(ptr), d, s, bx, e, CU_TENSOR_MAP_INTERLEAVE_NONE, sw, L2PROMO,
      CU_TENSOR_MAP_FLOAT_OOB_FILL_NONE);
}

void make_map3(EncodeFn enc, CUtensorMap* m, const void* ptr, uint64_t d0, uint64_t d1, uint64_t d2, uint64_t s1, uint64_t s2, uint32_t b0, uint32_t b1, uint32_t b2,
               CUtensorMapSwizzle sw, uint64_t s3 = 0) {
  cuuint64_t d[4] = {d0, d1, d2, 2};
  cuuint64_t s[3] = {s1, s2, s3};
  cuuint32_t bx[4] = {b0, b1, b2, 2};
  cuuint32_t e[4] = {1, 1, 1, 1};
  enc(m, CU_TENSOR_MAP_DATA_TYPE_BFLOAT16, s3 ? 4 : 3, const_cast<void*>(ptr), d, s, bx, e, CU_TENSOR_MAP_INTERLEAVE_NONE, sw, L2PROMO,
      CU_TENSOR_MAP_FLOAT_OOB_FILL_NONE);
}

}

extern "C" void kernel_launch(void* const* d_in, const int* in_sizes, int n_in, void* d_out, int out_size) {
  (void)in_sizes; (void)n_in; (void)out_size;
  void* f = nullptr;
  cudaDriverEntryPointQueryResult qr;
  cudaGetDriverEntryPoint("cuTensorMapEncodeTiled", &f, cudaEnableDefault, &qr);
  EncodeFn enc = (EncodeFn)f;
  void* s;
  cudaGetSymbolAddress(&s, g_s);
  Params p = {};
  uint8_t* ps = (uint8_t*)(((uintptr_t)s + (2 << 20) - 1) & ~(uintptr_t)((2 << 20) - 1));
  make_map3(enc, &p.m_k, d_in[1], D_, S_ / 8, 8, 8 * D_ * 2, D_ * 2, 32, 8, 8, CU_TENSOR_MAP_SWIZZLE_64B);
  make_map3(enc, &p.m_kh, d_in[1], D_, S_ / 8, 8, 8 * D_ * 2, D_ * 2, 32, 8, 3, CU_TENSOR_MAP_SWIZZLE_64B);
  make_map3(enc, &p.m_v, d_in[2], D_, S_ / 8, 8, 8 * D_ * 2, D_ * 2, 32, 8, 8, CU_TENSOR_MAP_SWIZZLE_64B);
  make_map3(enc, &p.m_q, d_in[0], 32, S_, D_ / 32, D_ * 2, 64, 32, 16, D_ / 32, CU_TENSOR_MAP_SWIZZLE_64B);
  make_map3(enc, &p.m_wm, d_in[11], 6 * D_, 160, 4, 12 * D_, 160 * 12 * D_, 32, 160, 4, CU_TENSOR_MAP_SWIZZLE_64B);
  const int lo = (uintptr_t)d_in[7] < (uintptr_t)d_in[8] ? 7 : 8;
  make_map3(enc, &p.m_w1, d_in[lo], 64, D_, F_ / 64, F_ * 2, 128, 64, 32, 3, CU_TENSOR_MAP_SWIZZLE_128B, (uintptr_t)d_in[15 - lo] - (uintptr_t)d_in[lo]);
  make_map(enc, &p.m_w2, d_in[9], D_, F_, 64, 64, CU_TENSOR_MAP_SWIZZLE_128B);
  make_map(enc, &p.m_out, d_out, D_, S_, 64, 16, CU_TENSOR_MAP_SWIZZLE_128B);
  p.c = (const __nv_bfloat16*)d_in[10];
  p.wg = (const __nv_bfloat16*)d_in[7];
  p.wu = (const __nv_bfloat16*)d_in[8];
  p.w2 = (const __nv_bfloat16*)d_in[9];
  p.out = (uint8_t*)d_out;
  cudaFuncSetAttribute(fused_kernel, cudaFuncAttributeMaxDynamicSharedMemorySize, SMEM_BYTES);
  fused_kernel<<<128, 384, SMEM_BYTES, cudaStreamPerThread>>>((const uint8_t*)d_in[1], (uintptr_t)d_in[2] - (uintptr_t)d_in[1], (uintptr_t)d_in[3] - (uintptr_t)d_in[1],
                                                              (const __nv_bfloat16*)d_in[4], (const __nv_bfloat16*)d_in[5], ps, p);
}
```

```cpp
#include <cuda_runtime.h>
#include <cuda.h>
#include <cuda_bf16.h>
#include <cstdint>

namespace {

constexpr int S_ = 2048, D_ = 640, F_ = 1536;

__device__ __align__(1024) uint8_t g_s[10 << 20];
#define g_sync ((uint32_t*)(ps + (1 << 16)))
#define g_mod ((uint32_t*)(ps + (2 << 16)))
#define g_vv ((uint32_t*)(ps + (3 << 16)))
#define TIMOFF (4 << 16)
enum { Y_KV = 0, Y_Y = 20 * 32, Y_MOD = 25 * 32, Y_VV = 31 * 32, Y_EP = 4 };
enum { G_KV = 1, G_Y = 6, G_X = 11 };
enum { M_X = 0, M_O = 40, M_ST = 512 };
#define TSTAMP(i) do { } while (0)
#define TS3(k, i) do { } while (0)
#define TS2(i) do { } while (0)
#define TS 5
#define SCH 1
#define T0 1000
#define TR 100
#define T_K1 T0
#define WF 1
#define T_K2 (T0 + (WF ? 125 : 70) * TR / 10)
#define T_WM0 (T0 + (WF ? 7 : 14) * TR)
#define T_S1 (T0 + 19 * TR + TR / 2)
#define T_K3 (T0 + 23 * TR)
#define T_K4 (T0 + 30 * TR)
#define T_S2 (T0 + 37 * TR)
#define T_S3 (T0 + 40 * TR + TR / 2)
#define T_S4 (T0 + 44 * TR)
#define T_Q (T0 + 47 * TR + TR / 2)
#define T_WM1 (T0 + 65 * TR)
#define T_W0 (T0 + 71 * TR)
#define T_WM2 (T0 + 76 * TR)
#define T_S0 600
#define D_Q 54
#define D_WM 27
#define NE0 1
#define NE 2
#define STEP(kv, gv, cv, fa) ((kv + 1) | (gv + 1) << 3 | (cv + 1) << 5 | (fa + 1) << 8)
#define EV 5
#define EV0 31
#define EV1 0ull
#define EV2 0x40141210ull
#define EV3 0x411311ull
#define SCHED_E STEP(0, -1, -1, 1), STEP(2, -1, -1, -1), STEP(4, -1, 1, 3), STEP(-1, 1, 3, -1), STEP(-1, 2, -1, -1)
#define SCHED_L STEP(-1, -1, -1, 0), STEP(1, 0, -1, -1), STEP(3, -1, 0, 2), STEP(-1, -1, 2, 4), STEP(-1, -1, 4, -1)
#define PFW 0x71u
#define PF2 0xc80u
#define AH 2
#define PD 3
#define ROT 1
#define QD 5
#define PUBD 2
#define NPUB 1
#define LH 17
#define MX 0
#define WARM 1
#define RS 2
#define GE 1
#define ER 1
#define VR 3
#define EVV 1
#define DM 1
#define PK 0
#define T_P 3800
#define EK 1
#define EY 4
#define EM 0
#define RP 2
#define TW 0
#define LEAD 2

struct Params {
  CUtensorMap m_k, m_kh, m_v, m_q, m_wm, m_w1, m_w2, m_out;
  const __nv_bfloat16 *c, *wg, *wu, *w2;
  uint8_t* out;
};
constexpr int NLD = 12;
__host__ __device__ constexpr uint32_t nth_load(int n) {
  const uint32_t when[NLD] = {T_K1 << 8 | 1, T_K2 << 8 | 2, T_K3 << 8 | 3, T_K4 << 8 | 4, T_S0 << 8 | 16, T_S1 << 8 | 17, T_S2 << 8 | 18, T_S3 << 8 | 19, T_S4 << 8 | 20,
                              T_Q << 8 | 21, T_WM0 << 8 | 32, T_WM1 << 8 | 33};
  for (int i = 0; i < NLD; i++) {
    int rank = 0;
    for (int k = 0; k < NLD; k++) rank += when[k] < when[i];
    if (rank == n) return when[i];
  }
  return 0;
}
__host__ __device__ constexpr uint64_t sched(int g) {
  const uint32_t t[2][5] = {{SCHED_L}, {SCHED_E}};
  uint64_t r = 0;
  for (int i = 0; i < 5; i++) r |= (uint64_t)t[g][i] << 12 * i;
  return r;
}
template <int I> struct IC { static constexpr int v = I; };
template <int N, class F> __device__ __forceinline__ void unrolled(F f) {
  if constexpr (N > 0) { unrolled<N - 1>(f); f(IC<N - 1>()); }
}

constexpr uint32_t SLOT = 32768;
constexpr uint32_t SD = 1024;
constexpr uint32_t U_RAW = 16, U_ODD = U_RAW + 4160, U_KV = 8448;
constexpr uint32_t O_WM = 2 * SLOT;
constexpr uint32_t O_SILU = O_WM + 40960;
constexpr uint32_t O_REG = 6 * SLOT;
constexpr uint32_t O_Y = O_REG + 20480;
constexpr uint32_t O_BP = O_Y + 4096;
constexpr uint32_t O_MA = O_BP + 4096;
constexpr uint32_t O_ST = O_BP + 7040;
constexpr uint32_t O_CS = O_ST + 1024;
constexpr uint32_t O_GB = O_CS + 640;
constexpr uint32_t O_LN = O_GB + 1280;
constexpr uint32_t O_EP = O_GB + 1280 + 64;
constexpr uint32_t O_BAR = O_EP + 192;
constexpr uint32_t O_XT = O_EP + 64;
constexpr uint32_t SMEM_BYTES = O_BAR + 1024;
static_assert(SMEM_BYTES <= 232448, "smem");
enum { B_W2E = 0, B_EMPTY = 4, B_LN = 10, B_VV = 11, B_YE = 12, B_OK = 16 - PK, B_FULL = 21, B_W2F = 27, B_HF = 34, B_KV = 40,
       B_CS = 45, B_X1 = 46, B_ST = 47, B_PR = 49, B_SSM = 56, B_QIN = 61, B_WM = 62, B_K = 62, B_PL = 67 };
__device__ __forceinline__ uint32_t kreg(int n) { return n < 4 ? (0x319b >> 4 * n & 15) << 14 : 5 * SLOT + 26624; }
__device__ __forceinline__ uint32_t voff(int n) { return n < 4 ? 6144 : -4 * SLOT; }
__device__ __forceinline__ uint32_t w2entry(int e) { return e == 6 ? 3 * SLOT + 24576 : e * SLOT; }
__device__ __forceinline__ int ocol(int ro, int i) { i += ROT * ((ro >> 1) & 3); return (ro & 1) * 320 + (i < 5 ? i : i - 5) * 64; }
__device__ __forceinline__ uint32_t bnd(int j) { return (0x720a8 >> 4 * j & 15) << 14; }
__device__ __forceinline__ uint32_t page(int g, int p) { return g << 19 | p << 12; }
__device__ __forceinline__ uint32_t tile(int rb, int x) { return page(G_X + (x >> 2), rb * 8 + (x & 3)); }

__device__ __forceinline__ uint32_t smem_u32(const void* p) { return (uint32_t)__cvta_generic_to_shared(p); }
__device__ __forceinline__ void mbar_init(uint32_t bar, uint32_t cnt) { asm volatile("mbarrier.init.shared::cta.b64 [%0], %1;" ::"r"(bar), "r"(cnt) : "memory"); }
__device__ __forceinline__ void mbar_expect(uint32_t bar, uint32_t bytes) { asm volatile("mbarrier.arrive.expect_tx.shared::cta.b64 _, [%0], %1;" ::"r"(bar), "r"(bytes) : "memory"); }
__device__ __forceinline__ void mbar_arrive(uint32_t bar) { asm volatile("mbarrier.arrive.shared::cta.b64 _, [%0];" ::"r"(bar) : "memory"); }
__device__ __forceinline__ void mbar_wait(uint32_t bar, uint32_t parity) {
  asm volatile("{\n .reg .pred p;\n .reg .u32 c;\n mov.u32 c, 0;\n LOOP:\n mbarrier.try_wait.parity.shared::cta.b64 p, [%0], %1;\n @p bra DONE;\n add.u32 c, c, 1;\n setp.lt.u32 p, c, 200000;\n @p bra LOOP;\n DONE:\n }" ::"r"(bar), "r"(parity) : "memory");
}
__device__ __forceinline__ void mbar_wait_cluster(uint32_t bar, uint32_t parity) {
  asm volatile("{\n .reg .pred p;\n .reg .u32 c;\n mov.u32 c, 0;\n LOOP:\n mbarrier.try_wait.parity.acquire.cluster.shared::cta.b64 p, [%0], %1;\n @p bra DONE;\n add.u32 c, c, 1;\n setp.lt.u32 p, c, 200000;\n @p bra LOOP;\n DONE:\n }" ::"r"(bar), "r"(parity) : "memory");
}
__device__ __forceinline__ bool mbar_test(uint32_t bar, uint32_t parity) {
  uint32_t r;
  asm volatile("{ .reg .pred p; mbarrier.test_wait.parity.shared::cta.b64 p, [%1], %2; selp.u32 %0, 1, 0, p; }" : "=r"(r) : "r"(bar), "r"(parity) : "memory");
  return r;
}
__device__ __forceinline__ bool mbar_try(uint32_t bar, uint32_t parity) {
  uint32_t r;
  asm volatile("{ .reg .pred p; mbarrier.try_wait.parity.shared::cta.b64 p, [%1], %2; selp.u32 %0, 1, 0, p; }" : "=r"(r) : "r"(bar), "r"(parity) : "memory");
  return r;
}
__device__ __forceinline__ uint32_t mapa(uint32_t a, uint32_t cta) { uint32_t r; asm("mapa.shared::cluster.u32 %0, %1, %2;" : "=r"(r) : "r"(a), "r"(cta)); return r; }
__device__ __forceinline__ void mbar_arrive_cl(uint32_t bar) { asm volatile("mbarrier.arrive.shared::cluster.b64 _, [%0];" ::"r"(bar) : "memory"); }
__device__ __forceinline__ bool elect() { uint32_t p; asm volatile("{ .reg .pred q; elect.sync _|q, 0xffffffff; selp.u32 %0, 1, 0, q; }" : "=r"(p)); return p; }
__device__ __forceinline__ uint32_t clk() { uint32_t c; asm volatile("mov.u32 %0, %%clock;" : "=r"(c)); return c; }
__device__ __forceinline__ uint32_t ldr(const uint32_t* p) { uint32_t v; asm volatile("ld.relaxed.gpu.global.u32 %0, [%1];" : "=r"(v) : "l"(p) : "memory"); return v; }
__device__ __forceinline__ uint4 ldr4(const uint32_t* p) {
  uint4 v; asm volatile("ld.relaxed.gpu.global.v4.u32 {%0,%1,%2,%3}, [%4];" : "=r"(v.x), "=r"(v.y), "=r"(v.z), "=r"(v.w) : "l"(p) : "memory"); return v;
}
__device__ __forceinline__ void poll_ge(const uint32_t* p, uint32_t target) {
  asm volatile("{\n .reg .pred p;\n .reg .u32 c, v;\n mov.u32 c, 0;\n LOOP:\n ld.relaxed.gpu.global.u32 v, [%0];\n sub.u32 v, v, %1;\n setp.ge.s32 p, v, 0;\n @p bra DONE;\n add.u32 c, c, 1;\n setp.lt.u32 p, c, 100000;\n @p bra LOOP;\n DONE:\n }" ::"l"(p), "r"(target) : "memory");
}
__device__ __forceinline__ void poll_lane(uint32_t& v, const void* p, uint32_t target, int l) {
  for (int it = 0; !((__ballot_sync(0xffffffffu, (int)(v - target) >= 0) >> l) & 1) && it < 100000; it++) v = ldr((const uint32_t*)p);
}
__device__ __forceinline__ void hint_add(uint32_t* p) { asm volatile("red.relaxed.gpu.global.add.u32 [%0], 1;" ::"l"(p) : "memory"); }
__device__ __forceinline__ void refetch(const void* g, uint32_t off, uint32_t a, uint32_t tag) {
  asm volatile("{\n .reg .pred p;\n .reg .u32 c, v, x, y, z;\n .reg .u64 q;\n mov.u32 c, 0;\n cvt.u64.u32 q, %1;\n add.u64 q, q, %0;\n"
               " LOOP:\n ld.relaxed.gpu.global.u32 v, [q];\n xor.b32 v, v, %3;\n and.b32 v, v, 1;\n setp.eq.u32 p, v, 0;\n @p bra DONE;\n add.u32 c, c, 1;\n setp.lt.u32 p, c, 100000;\n @p bra LOOP;\n"
               " DONE:\n ld.relaxed.gpu.global.v4.u32 {v, x, y, z}, [%0];\n st.shared.v4.u32 [%2], {v, x, y, z};\n ld.relaxed.gpu.global.v4.u32 {v, x, y, z}, [%0+16];\n xor.b32 c, %2, 16;\n"
               " st.shared.v4.u32 [c], {v, x, y, z};\n fence.proxy.async.shared::cta;\n }" ::"l"(g), "r"(off), "r"(a), "r"(tag) : "memory");
}
__device__ __forceinline__ void refetch_all(const void* g, uint32_t off, uint32_t a, uint32_t tag) {
  asm volatile("{\n .reg .pred p;\n .reg .u32 c, v, x, y, z;\n .reg .u64 q;\n mov.u32 c, 0;\n cvt.u64.u32 q, %1;\n add.u64 q, q, %0;\n"
               " LOOP:\n ld.relaxed.gpu.global.u32 v, [q];\n xor.b32 v, v, %3;\n and.b32 v, v, 1;\n setp.eq.u32 p, v, 0;\n vote.sync.all.pred p, p, 0xffffffff;\n @p bra DONE;\n add.u32 c, c, 1;\n setp.lt.u32 p, c, 100000;\n @p bra LOOP;\n"
               " DONE:\n ld.relaxed.gpu.global.v4.u32 {v, x, y, z}, [%0];\n st.shared.v4.u32 [%2], {v, x, y, z};\n ld.relaxed.gpu.global.v4.u32 {v, x, y, z}, [%0+16];\n xor.b32 c, %2, 16;\n"
               " st.shared.v4.u32 [c], {v, x, y, z};\n fence.proxy.async.shared::cta;\n }" ::"l"(g), "r"(off), "r"(a), "r"(tag) : "memory");
}
__device__ __forceinline__ void refetch16(const void* g, uint32_t a, uint32_t tag) {
  asm volatile("{\n .reg .pred p;\n .reg .u32 c, t, v, x, y, z;\n mov.u32 c, 0;\n"
               " LOOP:\n ld.relaxed.gpu.global.v4.u32 {v, x, y, z}, [%0];\n xor.b32 t, v, %2;\n and.b32 t, t, 1;\n setp.eq.u32 p, t, 0;\n vote.sync.all.pred p, p, 0xffffffff;\n @p bra DONE;\n add.u32 c, c, 1;\n setp.lt.u32 p, c, 100000;\n @p bra LOOP;\n"
               " DONE:\n st.shared.v4.u32 [%1], {v, x, y, z};\n }" ::"l"(g), "r"(a), "r"(tag) : "memory");
}
__device__ __forceinline__ uint2 ldr2(const uint32_t* p) {
  uint2 v; asm volatile("ld.relaxed.gpu.global.v2.u32 {%0,%1}, [%2];" : "=r"(v.x), "=r"(v.y) : "l"(p) : "memory"); return v;
}
__device__ __forceinline__ uint32_t settag(uint32_t x, uint32_t m, uint32_t t) { return (x & ~m) | (t & m); }
__device__ __forceinline__ void stg128(void* p, uint32_t x, uint32_t y, uint32_t z, uint32_t w) {
  asm volatile("st.global.v4.u32 [%0], {%1,%2,%3,%4};" ::"l"(p), "r"(x), "r"(y), "r"(z), "r"(w) : "memory");
}
__device__ __forceinline__ void stg128p(uint32_t on, void* p, uint32_t x, uint32_t y, uint32_t z, uint32_t w) {
  asm volatile("{ .reg .pred q; setp.ne.u32 q, %5, 0; @q st.global.v4.u32 [%0], {%1,%2,%3,%4}; }" ::"l"(p), "r"(x), "r"(y), "r"(z), "r"(w), "r"(on) : "memory");
}
__device__ __forceinline__ void hint_addp(uint32_t on, uint32_t* p) { asm volatile("{ .reg .pred p, q; elect.sync _|p, 0xffffffff; setp.ne.and.u32 q, %1, 0, p; @q red.relaxed.gpu.global.add.u32 [%0], 1; }" ::"l"(p), "r"(on) : "memory"); }
__device__ __forceinline__ void cpa16(uint32_t dst, const void* src, uint32_t n) { asm volatile("cp.async.cg.shared.global [%0], [%1], 16, %2;" ::"r"(dst), "l"(src), "r"(n) : "memory"); }
__device__ __forceinline__ void tma3d(uint32_t dst, const CUtensorMap* m, int x, int y, int z, uint32_t bar) {
  asm volatile("cp.async.bulk.tensor.3d.shared::cluster.global.mbarrier::complete_tx::bytes [%0], [%1, {%3, %4, %5}], [%2];" ::"r"(dst), "l"(m), "r"(bar), "r"(x), "r"(y), "r"(z) : "memory");
}
__device__ __forceinline__ void tma4d(uint32_t dst, const CUtensorMap* m, int x, int y, int z, int u, uint32_t bar) {
  asm volatile("cp.async.bulk.tensor.4d.shared::cluster.global.mbarrier::complete_tx::bytes [%0], [%1, {%3, %4, %5, %6}], [%2];" ::"r"(dst), "l"(m), "r"(bar), "r"(x), "r"(y), "r"(z), "r"(u) : "memory");
}
__device__ __forceinline__ void bulk_st(void* dst, uint32_t src, uint32_t bytes) {
  asm volatile("cp.async.bulk.global.shared::cta.bulk_group [%0], [%1], %2;" ::"l"(dst), "r"(src), "r"(bytes) : "memory");
}
__device__ __forceinline__ void bulk_pf(const void* src, uint32_t bytes) { asm volatile("cp.async.bulk.prefetch.L2.global [%0], %1;" ::"l"(src), "r"(bytes) : "memory"); }
__device__ __forceinline__ void tma2d(uint32_t dst, const CUtensorMap* m, int x, int y, uint32_t bar) {
  asm volatile("cp.async.bulk.tensor.2d.shared::cluster.global.mbarrier::complete_tx::bytes [%0], [%1, {%3, %4}], [%2];" ::"r"(dst), "l"(m), "r"(bar), "r"(x), "r"(y) : "memory");
}
__device__ __forceinline__ void tma2d_add(const CUtensorMap* m, uint32_t src, int x, int y) {
  asm volatile("cp.reduce.async.bulk.tensor.2d.global.shared::cta.add.tile.bulk_group [%0, {%2, %3}], [%1];" ::"l"(m), "r"(src), "r"(x), "r"(y) : "memory");
}
__device__ __forceinline__ void bulk_ld(uint32_t dst, const void* src, uint32_t bytes, uint32_t bar) {
  asm volatile("cp.async.bulk.shared::cluster.global.mbarrier::complete_tx::bytes [%0], [%1], %2, [%3];" ::"r"(dst), "l"(src), "r"(bytes), "r"(bar) : "memory");
}
__device__ __forceinline__ void bulk_commit() { asm volatile("cp.async.bulk.commit_group;" ::: "memory"); }
template <int N> __device__ __forceinline__ void bulk_wait() { asm volatile("cp.async.bulk.wait_group %0;" ::"n"(N) : "memory"); }
template <int N> __device__ __forceinline__ void bulk_wait_read() { asm volatile("cp.async.bulk.wait_group.read %0;" ::"n"(N) : "memory"); }
__device__ __forceinline__ void fence_async_smem() { asm volatile("fence.proxy.async.shared::cta;" ::: "memory"); }
__device__ __forceinline__ void bar_sync(int id, int n) { asm volatile("bar.sync %0, %1;" ::"r"(id), "r"(n) : "memory"); }
__device__ __forceinline__ void bar_arrive(int id, int n) { asm volatile("bar.arrive %0, %1;" ::"r"(id), "r"(n) : "memory"); }
__device__ __forceinline__ void wg_fence() { asm volatile("wgmma.fence.sync.aligned;" ::: "memory"); }
__device__ __forceinline__ void wg_commit() { asm volatile("wgmma.commit_group.sync.aligned;" ::: "memory"); }
template <int N> __device__ __forceinline__ void wg_wait() { asm volatile("wgmma.wait_group.sync.aligned %0;" ::"n"(N) : "memory"); }
__device__ __forceinline__ void ldsm4(uint32_t a, uint32_t& r0, uint32_t& r1, uint32_t& r2, uint32_t& r3) {
  asm volatile("ldmatrix.sync.aligned.m8n8.x4.shared.b16 {%0,%1,%2,%3}, [%4];" : "=r"(r0), "=r"(r1), "=r"(r2), "=r"(r3) : "r"(a) : "memory");
}
__device__ __forceinline__ void ldsm4t(uint32_t a, uint32_t& r0, uint32_t& r1, uint32_t& r2, uint32_t& r3) {
  asm volatile("ldmatrix.sync.aligned.m8n8.x4.trans.shared.b16 {%0,%1,%2,%3}, [%4];" : "=r"(r0), "=r"(r1), "=r"(r2), "=r"(r3) : "r"(a) : "memory");
}
__device__ __forceinline__ void stsm4t(uint32_t a, uint32_t r0, uint32_t r1, uint32_t r2, uint32_t r3) {
  asm volatile("stmatrix.sync.aligned.m8n8.x4.trans.shared.b16 [%0], {%1,%2,%3,%4};" ::"r"(a), "r"(r0), "r"(r1), "r"(r2), "r"(r3) : "memory");
}
__device__ __forceinline__ void stsm4(uint32_t a, uint32_t r0, uint32_t r1, uint32_t r2, uint32_t r3) {
  asm volatile("stmatrix.sync.aligned.m8n8.x4.shared.b16 [%0], {%1,%2,%3,%4};" ::"r"(a), "r"(r0), "r"(r1), "r"(r2), "r"(r3) : "memory");
}
__device__ __forceinline__ uint32_t lds32(uint32_t a) { uint32_t v; asm volatile("ld.shared.u32 %0, [%1];" : "=r"(v) : "r"(a) : "memory"); return v; }
__device__ __forceinline__ uint4 lds128(uint32_t a) { uint4 v; asm volatile("ld.shared.v4.u32 {%0,%1,%2,%3}, [%4];" : "=r"(v.x), "=r"(v.y), "=r"(v.z), "=r"(v.w) : "r"(a) : "memory"); return v; }
__device__ __forceinline__ float4 lds128f(uint32_t a) { float4 v; asm volatile("ld.shared.v4.f32 {%0,%1,%2,%3}, [%4];" : "=f"(v.x), "=f"(v.y), "=f"(v.z), "=f"(v.w) : "r"(a) : "memory"); return v; }
__device__ __forceinline__ float2 lds64f(uint32_t a) { float2 v; asm volatile("ld.shared.v2.f32 {%0,%1}, [%2];" : "=f"(v.x), "=f"(v.y) : "r"(a) : "memory"); return v; }
__device__ __forceinline__ void sts32(uint32_t a, uint32_t v) { asm volatile("st.shared.u32 [%0], %1;" ::"r"(a), "r"(v) : "memory"); }
__device__ __forceinline__ void sts64(uint32_t a, uint32_t x, uint32_t y) { asm volatile("st.shared.v2.u32 [%0], {%1,%2};" ::"r"(a), "r"(x), "r"(y) : "memory"); }
__device__ __forceinline__ void sts128(uint32_t a, uint32_t x, uint32_t y, uint32_t z, uint32_t w) { asm volatile("st.shared.v4.u32 [%0], {%1,%2,%3,%4};" ::"r"(a), "r"(x), "r"(y), "r"(z), "r"(w) : "memory"); }
__device__ __forceinline__ void sts16(uint32_t a, uint16_t v) { asm volatile("st.shared.u16 [%0], %1;" ::"r"(a), "h"(v) : "memory"); }
__device__ __forceinline__ uint32_t prmt(uint32_t a, uint32_t b, uint32_t s) { uint32_t r; asm("prmt.b32 %0, %1, %2, %3;" : "=r"(r) : "r"(a), "r"(b), "r"(s)); return r; }
__device__ __forceinline__ uint32_t hfma2(uint32_t a, uint32_t b, uint32_t c) { uint32_t r; asm("fma.rn.bf16x2 %0, %1, %2, %3;" : "=r"(r) : "r"(a), "r"(b), "r"(c)); return r; }
__device__ __forceinline__ uint32_t hfma2lh(uint32_t a, uint32_t l) {
  uint32_t r;
  asm("{ .reg .b16 x, y; .reg .b32 u, v; mov.b32 {x, y}, %2; mov.b32 u, {x, x}; mov.b32 v, {y, y}; fma.rn.bf16x2 %0, %1, u, v; }" : "=r"(r) : "r"(a), "r"(l));
  return r;
}
__device__ __forceinline__ uint32_t addu(uint32_t a, uint32_t u) { uint32_t r; asm("add.u32 %0, %1, %2;" : "=r"(r) : "r"(a), "r"(u)); return r; }
__device__ __forceinline__ uint32_t tag0(uint32_t x, uint32_t t) { uint32_t r; asm("lop3.b32 %0, %1, 1, %2, 0xb8;" : "=r"(r) : "r"(x), "r"(t)); return r; }
__device__ __forceinline__ void keep(uint32_t& x) { x = __shfl_xor_sync(0xffffffffu, x, 0); }
__device__ __forceinline__ uint32_t hmul2(uint32_t a, uint32_t b) { uint32_t r; asm("mul.rn.bf16x2 %0, %1, %2;" : "=r"(r) : "r"(a), "r"(b)); return r; }
__device__ __forceinline__ uint32_t pack2(float lo, float hi) { uint32_t r; asm("cvt.rn.bf16x2.f32 %0, %1, %2;" : "=r"(r) : "f"(hi), "f"(lo)); return r; }
__device__ __forceinline__ float blo(uint32_t v) { return __uint_as_float(v << 16); }
__device__ __forceinline__ float bhi(uint32_t v) { return __uint_as_float(v & 0xffff0000u); }
__device__ __forceinline__ uint32_t hadd2(uint32_t a, uint32_t b) { uint32_t r; asm("add.rn.bf16x2 %0, %1, %2;" : "=r"(r) : "r"(a), "r"(b)); return r; }
__device__ __forceinline__ void str(uint32_t* p, uint32_t v) { asm volatile("st.relaxed.gpu.global.u32 [%0], %1;" ::"l"(p), "r"(v) : "memory"); }
__device__ __forceinline__ uint32_t tagf(float x, uint32_t tag) { return (__float_as_uint(x) & ~3u) | (tag & 3); }
template <int N> __device__ __forceinline__ float4 gather4(const uint32_t* p, int stride, uint32_t tag) {
  uint4 v[N];
  int it = 0;
  uint32_t bad;
  do {
#pragma unroll
    for (int i = 0; i < N; i++) v[i] = ldr4(p + i * stride);
    bad = 0;
#pragma unroll
    for (int i = 0; i < N; i++) bad |= (v[i].x ^ tag) | (v[i].y ^ tag) | (v[i].z ^ tag) | (v[i].w ^ tag);
  } while ((bad & 3) && ++it < 100000);
  float4 s = make_float4(__uint_as_float(v[0].x), __uint_as_float(v[0].y), __uint_as_float(v[0].z), __uint_as_float(v[0].w));
#pragma unroll
  for (int i = 1; i < N; i++) { s.x += __uint_as_float(v[i].x); s.y += __uint_as_float(v[i].y); s.z += __uint_as_float(v[i].z); s.w += __uint_as_float(v[i].w); }
  return s;
}
__device__ __forceinline__ float rbf(float x) { return blo(pack2(x, 0.f)); }
__device__ __forceinline__ uint64_t mkdesc(uint32_t addr, uint32_t lbo, uint32_t sbo, uint32_t swz) {
  return (uint64_t)((addr & 0x3FFFF) >> 4) | ((uint64_t)(lbo >> 4) << 16) | ((uint64_t)(sbo >> 4) << 32) | ((uint64_t)swz << 62);
}
template <int N> __device__ __forceinline__ void regfence(float* d) {
#pragma unroll
  for (int i = 0; i < N; i++) asm volatile("" : "+f"(d[i])::"memory");
}

__device__ __forceinline__ void wgmma_rs_32_0(float* d, uint32_t a0, uint32_t a1, uint32_t a2, uint32_t a3, uint64_t db, int sd) {
  asm volatile("{ .reg .pred p; setp.ne.b32 p, %21, 0; wgmma.mma_async.sync.aligned.m64n32k16.f32.bf16.bf16 {%0,%1,%2,%3,%4,%5,%6,%7,%8,%9,%10,%11,%12,%13,%14,%15}, {%16,%17,%18,%19}, %20, p, 1, 1, 0; }"
   : "+f"(d[0]), "+f"(d[1]), "+f"(d[2]), "+f"(d[3]), "+f"(d[4]), "+f"(d[5]), "+f"(d[6]), "+f"(d[7]), "+f"(d[8]), "+f"(d[9]), "+f"(d[10]), "+f"(d[11]), "+f"(d[12]), "+f"(d[13]), "+f"(d[14]), "+f"(d[15]) : "r"(a0), "r"(a1), "r"(a2), "r"(a3), "l"(db), "r"(sd));
}
__device__ __forceinline__ void wgmma_rs_64_1(float* d, uint32_t a0, uint32_t a1, uint32_t a2, uint32_t a3, uint64_t db, int sd) {
  asm volatile("{ .reg .pred p; setp.ne.b32 p, %37, 0; wgmma.mma_async.sync.aligned.m64n64k16.f32.bf16.bf16 {%0,%1,%2,%3,%4,%5,%6,%7,%8,%9,%10,%11,%12,%13,%14,%15,%16,%17,%18,%19,%20,%21,%22,%23,%24,%25,%26,%27,%28,%29,%30,%31}, {%32,%33,%34,%35}, %36, p, 1, 1, 1; }"
   : "+f"(d[0]), "+f"(d[1]), "+f"(d[2]), "+f"(d[3]), "+f"(d[4]), "+f"(d[5]), "+f"(d[6]), "+f"(d[7]), "+f"(d[8]), "+f"(d[9]), "+f"(d[10]), "+f"(d[11]), "+f"(d[12]), "+f"(d[13]), "+f"(d[14]), "+f"(d[15]), "+f"(d[16]), "+f"(d[17]), "+f"(d[18]), "+f"(d[19]), "+f"(d[20]), "+f"(d[21]), "+f"(d[22]), "+f"(d[23]), "+f"(d[24]), "+f"(d[25]), "+f"(d[26]), "+f"(d[27]), "+f"(d[28]), "+f"(d[29]), "+f"(d[30]), "+f"(d[31]) : "r"(a0), "r"(a1), "r"(a2), "r"(a3), "l"(db), "r"(sd));
}
__device__ __forceinline__ void wgmma_rs_192_0(float* d, uint32_t a0, uint32_t a1, uint32_t a2, uint32_t a3, uint64_t db, int sd) {
  asm volatile("{ .reg .pred p; setp.ne.b32 p, %101, 0; wgmma.mma_async.sync.aligned.m64n192k16.f32.bf16.bf16 {%0,%1,%2,%3,%4,%5,%6,%7,%8,%9,%10,%11,%12,%13,%14,%15,%16,%17,%18,%19,%20,%21,%22,%23,%24,%25,%26,%27,%28,%29,%30,%31,%32,%33,%34,%35,%36,%37,%38,%39,%40,%41,%42,%43,%44,%45,%46,%47,%48,%49,%50,%51,%52,%53,%54,%55,%56,%57,%58,%59,%60,%61,%62,%63,%64,%65,%66,%67,%68,%69,%70,%71,%72,%73,%74,%75,%76,%77,%78,%79,%80,%81,%82,%83,%84,%85,%86,%87,%88,%89,%90,%91,%92,%93,%94,%95}, {%96,%97,%98,%99}, %100, p, 1, 1, 0; }"
   : "+f"(d[0]), "+f"(d[1]), "+f"(d[2]), "+f"(d[3]), "+f"(d[4]), "+f"(d[5]), "+f"(d[6]), "+f"(d[7]), "+f"(d[8]), "+f"(d[9]), "+f"(d[10]), "+f"(d[11]), "+f"(d[12]), "+f"(d[13]), "+f"(d[14]), "+f"(d[15]), "+f"(d[16]), "+f"(d[17]), "+f"(d[18]), "+f"(d[19]), "+f"(d[20]), "+f"(d[21]), "+f"(d[22]), "+f"(d[23]), "+f"(d[24]), "+f"(d[25]), "+f"(d[26]), "+f"(d[27]), "+f"(d[28]), "+f"(d[29]), "+f"(d[30]), "+f"(d[31]), "+f"(d[32]), "+f"(d[33]), "+f"(d[34]), "+f"(d[35]), "+f"(d[36]), "+f"(d[37]), "+f"(d[38]), "+f"(d[39]), "+f"(d[40]), "+f"(d[41]), "+f"(d[42]), "+f"(d[43]), "+f"(d[44]), "+f"(d[45]), "+f"(d[46]), "+f"(d[47]), "+f"(d[48]), "+f"(d[49]), "+f"(d[50]), "+f"(d[51]), "+f"(d[52]), "+f"(d[53]), "+f"(d[54]), "+f"(d[55]), "+f"(d[56]), "+f"(d[57]), "+f"(d[58]), "+f"(d[59]), "+f"(d[60]), "+f"(d[61]), "+f"(d[62]), "+f"(d[63]), "+f"(d[64]), "+f"(d[65]), "+f"(d[66]), "+f"(d[67]), "+f"(d[68]), "+f"(d[69]), "+f"(d[70]), "+f"(d[71]), "+f"(d[72]), "+f"(d[73]), "+f"(d[74]), "+f"(d[75]), "+f"(d[76]), "+f"(d[77]), "+f"(d[78]), "+f"(d[79]), "+f"(d[80]), "+f"(d[81]), "+f"(d[82]), "+f"(d[83]), "+f"(d[84]), "+f"(d[85]), "+f"(d[86]), "+f"(d[87]), "+f"(d[88]), "+f"(d[89]), "+f"(d[90]), "+f"(d[91]), "+f"(d[92]), "+f"(d[93]), "+f"(d[94]), "+f"(d[95]) : "r"(a0), "r"(a1), "r"(a2), "r"(a3), "l"(db), "r"(sd));
}
__device__ __forceinline__ void wgmma_ss_8_10(float* d, uint64_t da, uint64_t db, int sd) {
  asm volatile("{ .reg .pred p; setp.ne.b32 p, %6, 0; wgmma.mma_async.sync.aligned.m64n8k16.f32.bf16.bf16 {%0,%1,%2,%3}, %4, %5, p, 1, 1, 1, 0; }"
   : "+f"(d[0]), "+f"(d[1]), "+f"(d[2]), "+f"(d[3]) : "l"(da), "l"(db), "r"(sd));
}
__device__ __forceinline__ void wgmma_ss_192_01(float* d, uint64_t da, uint64_t db, int sd) {
  asm volatile("{ .reg .pred p; setp.ne.b32 p, %98, 0; wgmma.mma_async.sync.aligned.m64n192k16.f32.bf16.bf16 {%0,%1,%2,%3,%4,%5,%6,%7,%8,%9,%10,%11,%12,%13,%14,%15,%16,%17,%18,%19,%20,%21,%22,%23,%24,%25,%26,%27,%28,%29,%30,%31,%32,%33,%34,%35,%36,%37,%38,%39,%40,%41,%42,%43,%44,%45,%46,%47,%48,%49,%50,%51,%52,%53,%54,%55,%56,%57,%58,%59,%60,%61,%62,%63,%64,%65,%66,%67,%68,%69,%70,%71,%72,%73,%74,%75,%76,%77,%78,%79,%80,%81,%82,%83,%84,%85,%86,%87,%88,%89,%90,%91,%92,%93,%94,%95}, %96, %97, p, 1, 1, 0, 1; }"
   : "+f"(d[0]), "+f"(d[1]), "+f"(d[2]), "+f"(d[3]), "+f"(d[4]), "+f"(d[5]), "+f"(d[6]), "+f"(d[7]), "+f"(d[8]), "+f"(d[9]), "+f"(d[10]), "+f"(d[11]), "+f"(d[12]), "+f"(d[13]), "+f"(d[14]), "+f"(d[15]), "+f"(d[16]), "+f"(d[17]), "+f"(d[18]), "+f"(d[19]), "+f"(d[20]), "+f"(d[21]), "+f"(d[22]), "+f"(d[23]), "+f"(d[24]), "+f"(d[25]), "+f"(d[26]), "+f"(d[27]), "+f"(d[28]), "+f"(d[29]), "+f"(d[30]), "+f"(d[31]), "+f"(d[32]), "+f"(d[33]), "+f"(d[34]), "+f"(d[35]), "+f"(d[36]), "+f"(d[37]), "+f"(d[38]), "+f"(d[39]), "+f"(d[40]), "+f"(d[41]), "+f"(d[42]), "+f"(d[43]), "+f"(d[44]), "+f"(d[45]), "+f"(d[46]), "+f"(d[47]), "+f"(d[48]), "+f"(d[49]), "+f"(d[50]), "+f"(d[51]), "+f"(d[52]), "+f"(d[53]), "+f"(d[54]), "+f"(d[55]), "+f"(d[56]), "+f"(d[57]), "+f"(d[58]), "+f"(d[59]), "+f"(d[60]), "+f"(d[61]), "+f"(d[62]), "+f"(d[63]), "+f"(d[64]), "+f"(d[65]), "+f"(d[66]), "+f"(d[67]), "+f"(d[68]), "+f"(d[69]), "+f"(d[70]), "+f"(d[71]), "+f"(d[72]), "+f"(d[73]), "+f"(d[74]), "+f"(d[75]), "+f"(d[76]), "+f"(d[77]), "+f"(d[78]), "+f"(d[79]), "+f"(d[80]), "+f"(d[81]), "+f"(d[82]), "+f"(d[83]), "+f"(d[84]), "+f"(d[85]), "+f"(d[86]), "+f"(d[87]), "+f"(d[88]), "+f"(d[89]), "+f"(d[90]), "+f"(d[91]), "+f"(d[92]), "+f"(d[93]), "+f"(d[94]), "+f"(d[95]) : "l"(da), "l"(db), "r"(sd));
}

#define HINT(x) x

__global__ void __cluster_dims__(2, 1, 1) __launch_bounds__(384, 1) fused_kernel(const uint8_t* __restrict__ pk, uint64_t dv,
    uint64_t dsh, const __nv_bfloat16* __restrict__ pssm, const __nv_bfloat16* __restrict__ pD, uint8_t* ps, const __grid_constant__ Params p) {
  extern __shared__ __align__(1024) uint8_t smem_raw[];
  const uint32_t t_start = clk();
  const uint32_t sb = smem_u32(smem_raw);
  const uint32_t bars = sb + O_BAR;
  const int tid = threadIdx.x, lane = tid & 31;
  const int warp = __shfl_sync(0xffffffffu, tid >> 5, 0);
  {
    const int b = blockIdx.x, w = (tid >> 5) & 3, r = lane >> 2, c = lane & 3, g = tid >> 7, t = (b >> 2) * 64 + r * 8;
    const uint32_t x = r * 64 + ((c ^ (r >> 1)) << 4), o = t * (D_ * 2) + (b & 3) * 64 + c * 16, mv = tid << 24 >> 31, ms = tid >= 352 ? -1 : 0;
    auto pick = [&](uint64_t d, uint32_t m) { return (uint64_t)((uint32_t)(d >> 32) & m) << 32 | (uint32_t)d & m; };
    const uint32_t d = sb + kreg(0) + x + w * 1024 + (2 >> g) * voff(0);
    const uint8_t* const a = pk + pick(dv, mv) + (o + w * (D_ * 4));
    cpa16(d, a, g ? 16 : 0);
    cpa16(d + 512, a + D_ * 2, g ? 16 : 0);
    cpa16(settag(d - w * 512, mv, sb + O_EP - 4096) + 4096,
          pk + (pick(dsh, ms) | pick((uint8_t*)(g_sync + Y_EP + b * 32) - pk, mv)) + (settag(max((int)o + (w - 3) * (D_ * 2), 0), ms, (b & 3) * 256 + x) & ~mv), g && (t | mv | ms) ? 16 : 0);
    if (tid == 256) TSTAMP(74);
  }
  const int b = blockIdx.x, kh = b & 1;
  const int part = b / 20, grp = part < NE0 ? 0 : part < NE ? 1 : 2;
  auto loadwm = [&]() {
    const int x = b % 20, col = part < 5 ? (x >> 2) * D_ + part * 128 + (x & 3) * 32 : 5 * D_ + x * 32;
    mbar_expect(bars + 8 * B_WM, 40960);
    tma3d(sb + O_WM, &p.m_wm, col, 0, 0, bars + 8 * B_WM);
  };
  auto BAR = [&](int i) { return bars + 8 * i; };
#define ROLE const int rb = b >> 3, fs = b & 7, vr = min(rb, 14) / 3, vt = min(rb, 14) % 3; \
  const uint32_t ord = VR == 3 ? (vr == 4 ? 0x34210 : 0x43210) : vr == 3 ? 0x42310 : vr == 4 ? 0x32410 : 0x43210; uint8_t* const misc = ps + rb * 4096; \
  (void)fs; (void)vt; (void)ord; (void)misc
  if (tid == 0) TSTAMP(63);
#define EPOCHU const uint32_t ep = __shfl_sync(0xffffffffu, lds32(sb + O_EP), 0) + 1

  if (warp < 4) {
    if (tid == 32) TSTAMP(118);
    asm volatile("setmaxnreg.dec.sync.aligned.u32 40;");
    if (tid == 32) TSTAMP(120);
    asm volatile("barrier.cluster.arrive.relaxed.aligned;" ::: "memory");
    const int hw = warp - 2;
    auto kvcheck = [&](int j, uint32_t ep) {
      const uint32_t a = sb + bnd(j) + U_KV + lane * 32;
      uint32_t x[4];
      mbar_wait(BAR(B_KV + j), 0);
#pragma unroll
      for (int i = 0; i < 4; i++) x[i] = lds32(a + i * 1024 + (lane & 28)) ^ ep;
      if (__any_sync(0xffffffffu, (x[0] | x[1] | x[2] | x[3]) & 1)) {
#pragma unroll 1
        for (int i = 0; i < 4096; i += 1024) refetch_all(ps + (page(G_KV + j, b) + lane * 32 + i), lane & 28, a + i, ep);
      }
      __syncwarp();
      if (lane == 0) mbar_arrive(BAR(B_OK + j));
    };
    if (warp == 0) {
      bar_sync(1, 384);
      EPOCHU;
      if (lane == 0) TSTAMP(0);
      __syncwarp();
      ROLE;
      {
        const uint32_t* f = g_sync + Y_KV + (min(lane, 4) * 4 + (b >> 5)) * 32;
        const uint32_t tw = lane != 5 ? T_W0 : b * D_WM + T_WM2 - 20 * NE * D_WM;
        uint32_t pend = (b < 120 && grp == 2 ? 127 : 95) - PK;
        int it = 0;
        do {
          uint32_t v = ep * 32;
          HINT(if (lane < 5 && (pend & 31)) v = ldr(f));
          uint32_t m = __ballot_sync(0xffffffffu, (lane < 5 ? (int)(v - ep * 32) >= 0 : clk() - t_start >= tw) || ++it > 100000) & pend;
          pend &= ~m;
          uint32_t ck = m & EV0;
          for (; m; m &= m - 1) {
            const int j = __ffs(m) - 1;
            if (elect()) {
              if (j < 5) {
                TSTAMP(2 + j);
                mbar_expect(BAR(B_KV + j), 4096);
                bulk_ld(sb + bnd(j) + U_KV, ps + page(G_KV + j, b), 4096, BAR(B_KV + j));
              } else if (j == 5) {
                loadwm();
                TSTAMP(109);
              } else {
                bulk_pf((kh ? p.wu : p.wg) + (b >> 1) * 2 * F_, 6144);
                TSTAMP(108);
              }
            }
          }
          for (; ck; ck &= ck - 1) kvcheck(__ffs(ck) - 1, ep);
        } while (pend);
      }
      {
        const int rl = (ord >> (min(lane, 19) & 28)) & 7;
        const uint32_t* const cnt = (const uint32_t*)(misc + M_X) + rl * 2 + ((min(lane, 19) >> 1) & 1);
        sts32(sb + O_XT + lane * 4, tile(rb, rl * 4 + (lane & 3)));
        __syncwarp();
        uint32_t known = 0;
        int slot = 4;
#pragma unroll 1
        for (int i = -AH; i < 20; i++) {
          const int s = i < 0 ? i + AH : i, rd = (ord >> (s & 28)) & 7;
          const uint32_t dst = sb + slot * SLOT, full = BAR(B_FULL + slot);
          const uint8_t* const xs = ps + (tile(rb, rd * 4 + (s & 3)) + kh * 16384);
          auto loadx = [&]() {
            asm volatile("{ .reg .pred p; elect.sync _|p, 0xffffffff;\n @p cp.async.bulk.shared::cluster.global.mbarrier::complete_tx::bytes.multicast::cluster [%0], [%1], 4096, [%2], %3; }"
                         ::"r"(dst + 24576 + kh * 4096), "l"(xs), "r"(full), "h"((uint16_t)3) : "memory");
          };
          auto loadw = [&]() {
            mbar_wait(full + 8 * (B_EMPTY - B_FULL), (0xc0fc0 >> s) & 1);
            asm volatile("{ .reg .pred p; elect.sync _|p, 0xffffffff;\n @p mbarrier.arrive.expect_tx.shared::cta.b64 _, [%2], 32768;\n"
                         " @p cp.async.bulk.tensor.4d.shared::cluster.global.mbarrier::complete_tx::bytes [%0], [%1, {0, %3, %4, 0}], [%2]; }"
                         ::"r"(dst), "l"(&p.m_w1), "r"(full), "r"(rd * 128 + (s & 3) * 32), "r"(fs * 3) : "memory");
          };
          uint32_t v = ep * 16 - 1;
          HINT(if (i >= 0 && (~known >> s) & PD) v = ldr(cnt));
          if (i >= AH && (known >> s) & 1) {
            loadw();
            loadx();
          } else {
            if ((uint32_t)i >= AH) loadw();
            if (lane == 0) TS3(2, s);
            if (i >= 0) {
              HINT(if (!((known >> s) & 1)) poll_lane(v, cnt, ep * 16, s));
              loadx();
            }
          }
          if (i >= 0 && lane == 0) TS3(3, s);
          if (((PFW | PF2) << AH >> (i + AH)) & 1) {
            const int k = __popc((PFW | PF2) << (31 - s));
            if (elect()) bulk_pf(k < 5 ? (kh ? p.wu : p.wg) + (k * 128 + (b >> 1) * 2) * F_ : p.w2 + b * 7680 + (k - 5) * 2560, k < 5 ? 6144 : 5120);
          }
          if (lane == 0 && i == -1) TSTAMP(10);
          if (lane == 0 && i == 0) TSTAMP(19);
          if (lane == 0 && i == 16) TSTAMP(1);
          slot = i == -1 ? 4 : slot == 5 ? 0 : slot + 1;
          known |= __ballot_sync(0xffffffffu, (int)(v - ep * 16) >= 0);
        }
      }
      __syncwarp();
      asm volatile("barrier.cluster.wait.aligned;" ::: "memory");
      if ((sb & 0xffffff) != SD) __trap();
#pragma unroll 1
      for (int s = 0; s < 10; s++) {
        const int e = s < 7 ? s : s - 7;
        const uint32_t d = sb + w2entry(e), st = e == 6 ? SLOT : 8192;
        const int k0 = (fs ^ (s < 4 ? s >> 1 : s & 1)) * 192, c0 = ocol(b, s < 4 ? s & 1 : s >> 1);
        mbar_wait(BAR(s >= 7 ? B_W2E + e : B_EMPTY + min(s, 5)), s < 4);
        if (elect()) {
          mbar_expect(BAR(B_W2F + e), 24576);
#pragma unroll
          for (int i = 0; i < 3; i++) tma2d(d + i * st, &p.m_w2, c0, k0 + i * 64, BAR(B_W2F + e));
        }
      }
    } else {
      uint32_t dd = 0;
      if (warp == 1) {
        mbar_init(BAR(B_SSM), 1);
        unrolled<NLD>([&](auto I) {
          constexpr uint32_t e = nth_load(I.v), n = e & 15, kind = (e >> 4) & 15;
          while (clk() - t_start < (e >> 8) + (n == 5 ? (b >> 2) * D_Q : 0)) {}
          if (elect()) {
            if constexpr (kind == 0) {
              const uint32_t d = sb + kreg(n), bar = BAR(B_K + n);
              const int ch = n * 128 + (b & 3) * 32, tg = (b >> 2) * 8;
              mbar_expect(bar, 9984);
              tma3d(d, &p.m_k, ch, tg, 0, bar);
              tma3d(d + voff(n), &p.m_v, ch, tg, 0, bar);
              tma3d(d + 4096, &p.m_kh, ch, tg - 1, 5, bar);
              bulk_ld(d + 5632, pk + dsh + ch * 8, 256, bar);
            } else if constexpr (kind == 2) {
              if (grp == n) loadwm();
            } else if constexpr (kind == 1 && n < 5) {
              mbar_expect(BAR(B_SSM + n), 4096);
              bulk_ld(sb + bnd(n) + U_RAW, pssm + (size_t)(n * 128 + b) * S_, 4096, BAR(B_SSM + n));
            } else {
              mbar_expect(BAR(B_QIN), 20480);
              tma3d(sb + O_REG, &p.m_q, 0, b * 16, 0, BAR(B_QIN));
            }
            TSTAMP(96 + I.v);
          }
          if constexpr (I.v == 0) {
            static_assert(e % 256 == 16, "first load");
#pragma unroll
            for (int i = B_SSM + 1; i < B_PL + 5; i++) mbar_init(BAR(i), i < B_PL ? 1 : 2);
            bar_arrive(1, 384);
            if (lane == 0) TSTAMP(112);
          }
        });
        mbar_wait(BAR(B_PL), 0);
        if (lane < 5) asm volatile("mbarrier.expect_tx.relaxed.cta.shared::cta.b64 [%0], 4096;" ::"r"(BAR(B_PR + lane)) : "memory");
      } else {
        uint32_t x[10];
        asm volatile("ld.global.nc.u16 %0, [%1];" : "=r"(dd) : "l"(pD + min(lane, 4) * 128 + b) : "memory");
#pragma unroll
        for (int i = 0; i < 10; i++) x[i] = ldr((const uint32_t*)p.c + lane + i * 32);
#pragma unroll
        for (int j = 0; j < 5; j++) {
          if (hw && lane < 19) sts128(sb + bnd(j) + (lane < 17 ? U_KV + 4096 + lane * 16 : lane == 17 ? U_RAW - 16 : U_ODD - 16), 0, 0, 0, 0);
        }
        if (tid == 96) TSTAMP(122);
        if (elect()) {
#pragma unroll
          for (int i = 0; i < 4; i++) asm volatile("prefetch.tensormap [%0];" ::"l"(&p.m_k + hw * 4 + i) : "memory");
        }
        bar_sync(1, 384);
        if (hw) {
#pragma unroll
          for (int i = 0; i < 10; i++)
            sts32(sb + O_SILU + i % 5 * 256 + (lane >> 2) * 32 + i / 5 * 16 + (lane & 3) * 4, pack2(__fdividef(blo(x[i]), 1.f + __expf(-blo(x[i]))), __fdividef(bhi(x[i]), 1.f + __expf(-bhi(x[i])))));
          fence_async_smem();
          __syncwarp();
          if (lane < 5) mbar_arrive(BAR(B_PL + lane));
        }
      }
      uint32_t xl = (lane ^ lane >> 3) * 16;
      auto rowsum = [&](int h, uint8_t* og) {
        float z[4] = {0.f, 0.f, 0.f, 0.f};
        auto acc = [&](uint32_t v) { const float f = blo(v), g = bhi(v); z[0] += f; z[1] = fmaf(f, f, z[1]); z[2] += g; z[3] = fmaf(g, g, z[3]); };
        uint32_t a = sb + O_REG + h * 512 + xl;
        uint4 x = lds128(a), y = lds128(a + 1024);
#pragma unroll 1
        for (int i = 0; i < 10; i++) {
          a += 2048;
          const uint4 u = lds128(a), v = lds128(a + 1024);
          if (og) { stg128(og, x.x, x.y, x.z, x.w); stg128(og + 64, y.x, y.y, y.z, y.w); og += 128; }
          acc(x.x); acc(x.y); acc(x.z); acc(x.w); acc(y.x); acc(y.y); acc(y.z); acc(y.w);
          x = u; y = v;
        }
        z[0] += z[2]; z[1] += z[3];
#pragma unroll
        for (int i = 1; i < 3; i++) { z[0] += __shfl_xor_sync(0xffffffffu, z[0], i); z[1] += __shfl_xor_sync(0xffffffffu, z[1], i); }
        z[0] *= 1.f / D_;
        return make_float2(z[0], fmaxf(z[1] * (1.f / D_) - z[0] * z[0], 0.f) + 1e-5f);
      };
      {
        EPOCHU;
#pragma unroll 1
        for (uint64_t ev = warp == 1 ? EV1 : hw ? EV3 : EV2; ev; ev >>= 8) {
          const int j = ev & 7;
          if (ev & 16) {
            const float dj = blo(__shfl_sync(0xffffffffu, dd, j));
            mbar_wait(BAR(B_SSM + j), 0);
            if (lane == 0 && j == 0) TSTAMP(77);
#pragma unroll 1
            for (int h = 0; h < 4096; h += 2048) {
              const uint32_t ra = sb + bnd(j) + U_RAW + h + lane * 16;
              uint4 w[4];
              uint32_t pv[4];
#pragma unroll
              for (int i = 0; i < 4; i++) { w[i] = lds128(ra + i * 512); pv[i] = lds32(ra + i * 512 - 4); }
              if (!(h | lane)) { w[0].x = prmt(pack2(blo(w[0].x) + dj, 0.f), w[0].x, 0x7610); sts32(ra, w[0].x); }
#pragma unroll
              for (int i = 0; i < 4; i++) sts128(ra + (U_ODD - U_RAW) + i * 512, prmt(pv[i], w[i].x, 0x5432), prmt(w[i].x, w[i].y, 0x5432), prmt(w[i].y, w[i].z, 0x5432), prmt(w[i].z, w[i].w, 0x5432));
            }
            __syncwarp();
            if (lane == 0) { mbar_arrive(BAR(B_PL + j)); TSTAMP(32 + j); }
          } else if (ev & 32) {
            kvcheck(j, ep);
          } else {
            mbar_wait(BAR(B_QIN), 0);
            if (lane == 0 && j == 0) TSTAMP(9);
            const float2 z = rowsum(j, nullptr);
            const float rs = rbf(rsqrtf(z.y));
            if (!(xl & 48)) sts32(sb + O_LN + j * 32 + (xl >> 4), pack2(rs, -z.x * rs));
            __syncwarp();
            if (lane < 2) mbar_arrive(BAR(B_LN));
            if (lane == 0) TSTAMP(59 + 2 * j);
          }
        }
      }
      if (warp == 1) {
        EPOCHU;
        ROLE;
        uint32_t known = 0;
        const uint32_t* const cnt = g_sync + Y_Y + min(lane, 10) * 32;
        const uint32_t target = ep * (lane < 5 ? 128 : 40);
        int ny = 0, nm = 0;
#pragma unroll 1
        for (int it = 0; ny < 5 || nm < 6; it++) {
          const int j = nm < 5 ? (ord >> (nm * 4)) & 7 : nm;
          uint32_t u = target;
          HINT(if (DM ? ~known & 31 : known != 2047) u = ldr(cnt));
          if (DM ? nm < 6 : (known >> (5 + j)) & 1) {
            uint4 v[5];
            uint32_t bad = 0, lo[5], hi[5];
#pragma unroll
            for (int k = 0; k < 5; k++) v[k] = ldr4(g_mod + j * D_ + k * 128 + lane * 4);
#pragma unroll
            for (int k = 0; k < 5; k++) {
              bad |= (v[k].x ^ ep) | (v[k].y ^ ep) | (v[k].z ^ ep) | (v[k].w ^ ep);
              lo[k] = pack2(__uint_as_float(v[k].x), __uint_as_float(v[k].y));
              hi[k] = pack2(__uint_as_float(v[k].z), __uint_as_float(v[k].w));
            }
            if (!__any_sync(0xffffffffu, bad & 3) || it > 200000) {
              if (nm < 5) {
                const uint32_t ma = sb + O_MA + nm * 768 + lane * 8, one = 0x3F803F80u, c0 = hadd2(lo[4], one), c1 = hadd2(hi[4], one);
                sts64(ma, hmul2(lo[2], hadd2(lo[1], one)), hmul2(hi[2], hadd2(hi[1], one)));
                sts64(ma + 256, hmul2(lo[2], lo[0]), hmul2(hi[2], hi[0]));
                sts64(ma + 512, c0, c1);
                __syncwarp();
                if (lane == 0) { mbar_arrive(BAR(B_PR + nm)); if (nm < 3) TSTAMP(nm < 2 ? 7 + nm : 79); }
                if (j == vr) {
                  sts64(sb + O_CS + (lane >> 1) * 32 + (lane & 1) * 8, c0, c1);
                  sts64(sb + O_CS + (lane >> 1) * 32 + (lane & 1) * 8 + 16, lo[3], hi[3]);
                  fence_async_smem();
                  __syncwarp();
                  if (lane == 0) mbar_arrive(BAR(B_CS));
                }
              } else {
#pragma unroll
                for (int k = 0; k < 5; k++) if ((k * 32 + lane >= 80) == kh) sts128(sb + O_GB + k * 512 + lane * 16 - kh * 1280, lo[k] << 16, lo[k] & 0xffff0000u, hi[k] << 16, hi[k] & 0xffff0000u);
              }
              nm++;
            }
          }
          known |= __ballot_sync(0xffffffffu, (int)(u - target) >= 0 || it > 100000) & 2047;
          if (ny < 5) {
            const int y = (ord >> (ny * 4)) & 7;
            if (nm > 5 && ny >= 2) mbar_wait(BAR(B_YE + (ny & 1)), ny >> 2);
            if (((known >> y) & 1) && (ny < 2 || mbar_test(BAR(B_YE + (ny & 1)), ny >> 2) || it > 200000)) {
              if (elect()) {
                if (ny < 2) TSTAMP(47 + ny);
                bulk_ld(sb + (ny & 1 ? O_BP : O_Y), ps + page(G_Y + y, b), 4096, BAR(B_PR + ny));
              }
              ny++;
            }
          }
        }
        __syncwarp();
        if (lane < 6) mbar_expect(BAR(B_HF + lane), 8192);
        if (lane == 0) { sts128(sb + O_BP + 6144, 0, 0, 0, 0); mbar_arrive(BAR(B_VV)); }
        mbar_wait(BAR(B_YE + 1), 1);
      } else {
        uint32_t ya = lane * 32 + (lane & 4) * 4, pl = (lane & 3) * 16;
        keep(ya); keep(xl); keep(pl);
        mbar_wait(BAR(B_LN), 0);
        ROLE;
        const uint32_t tt = (lds32(sb + O_EP) & 1) - 1, ln[2] = {lds32(sb + O_LN + (lane & 28)), lds32(sb + O_LN + 32 + (lane & 28))};
#pragma unroll 1
        for (int it = 0; it != 10;) {
          const int j = (ord >> (it * 2 & 28)) & 7, odd = (it >> 1) & 1, g = (it & 1) * 2 + hw;
          const uint32_t pm = sb + O_MA + (it & 14) * 384 + g * 64, yo = sb + (odd ? O_BP : O_Y) + g * 1024, qo = sb + O_REG + (j * 4 + g) * 1024;
          uint32_t y[8];
          if (!(it & 1)) mbar_wait(BAR(B_PR + ((it >> 1) & 7)), 0);
          if (!(xl | hw) && it < 6 && !(it & 1)) TSTAMP(it == 0 ? 49 : it == 2 ? 58 : 80);
          ldsm4t(addu(ya, yo), y[0], y[1], y[2], y[3]);
          ldsm4t(addu(ya, yo) ^ 16, y[4], y[5], y[6], y[7]);
          const uint4 q0 = lds128(addu(xl, qo)), a4 = lds128(addu(pl, pm)), b4 = lds128(addu(pl, pm) + 256), q1 = lds128(addu(xl, qo) + 512), c4 = lds128(addu(pl, pm) + 512);
          if ((__ballot_sync(0xffffffffu, ((y[0] ^ tt) | (y[1] ^ tt) | (y[2] ^ tt) | (y[3] ^ tt) | (y[4] ^ tt) | (y[5] ^ tt) | (y[6] ^ tt) | (y[7] ^ tt)) & 0x00010001u) & 15) && it < 16) {
#pragma unroll 1
            for (int hf = 0; hf < 32; hf += 16) refetch16(ps + (page(G_Y + j, b) + g * 1024 + (ya ^ hf)), (ya ^ hf) + yo, tt);
            __syncwarp();
            it += 16;
            continue;
          }
          const uint32_t ma[4] = {a4.x, a4.y, a4.z, a4.w}, mb[4] = {b4.x, b4.y, b4.z, b4.w};
          uint32_t q[8] = {q0.x, q0.y, q0.z, q0.w, q1.x, q1.y, q1.z, q1.w};
#pragma unroll
          for (int i = 0; i < 8; i++) q[i] = hfma2(hfma2(hfma2lh(q[i], ln[i >> 2]), ma[i & 3], mb[i & 3]), y[i], q[i]);
          uint8_t* const xg = ps + addu(xl, tile(rb, j * 4 + g) + (b & 4) * 4096 + (b & 3) * 1024);
          stg128(xg, tag0(hmul2(q[0], c4.x), tt), hmul2(q[1], c4.y), hmul2(q[2], c4.z), hmul2(q[3], c4.w));
          stg128(xg + 512, tag0(hmul2(q[4], c4.x), tt), hmul2(q[5], c4.y), hmul2(q[6], c4.z), hmul2(q[7], c4.w));
          asm volatile("{ .reg .pred p; elect.sync _|p, 0xffffffff; @p red.relaxed.gpu.global.add.u32 [%0], 1; @p mbarrier.arrive.shared::cta.b64 _, [%1]; }"
                       ::"l"(misc + M_X + j * 8 + (it & 1) * 4), "r"(BAR(B_YE + odd)) : "memory");
          sts128(addu(xl, qo), q[0], q[1], q[2], q[3]);
          sts128(addu(xl, qo) + 512, q[4], q[5], q[6], q[7]);
          if (!(xl | hw) && (it & 1)) TSTAMP(12 + ((it & 15) >> 1));
          if (!(xl | hw) && it == 0) TSTAMP(116);
          it = (it & 15) + 1;
        }
        const int lane = ya >> 5, t = hw * 32 + lane;
        EPOCHU;
        bar_sync(4, 64);
        const float2 z = rowsum(hw, p.out + ((t >> 2) * 1280 + pl + b * 20480));
        const uint32_t pa = pack2(-z.x, sqrtf(z.y));
        if (!(xl & 48))
          asm volatile("st.relaxed.gpu.global.v2.u32 [%0], {%1,%2};" ::"l"(misc + M_ST + fs * 128 + hw * 64 + (xl >> 3)), "r"(pa), "r"(tagf(__fdividef(1.f, bhi(pa) * bhi(pa)), ep)) : "memory");
        uint4 v;
        int it = 0;
        do v = ldr4((const uint32_t*)(misc + M_ST + t * 16)); while ((((v.y ^ ep) | (v.w ^ ep)) & 3) && ++it < 100000);
        sts128(sb + O_ST + t * 16, v.x, v.y, v.z, v.w);
        __syncwarp();
        if (lane == 0) mbar_arrive(BAR(B_ST + hw));
        if (t == 0) TSTAMP(52);
      }
      ROLE;
      EPOCHU;
      int lane;
      asm volatile("mov.u32 %0, %%laneid;" : "=r"(lane));
      {
        HINT(poll_ge(g_sync + Y_VV + fs * 32, ep * 128));
        uint32_t v[20], bad;
        int it = 0;
        const uint32_t* g = g_vv + fs * 1920 + (hw + 1) * 128 + lane;
        do {
          bad = 0;
#pragma unroll
          for (int k = 0; k < 20; k++) v[k] = ldr(g + ((k % 5) * 384 + (k / 5) * 32));
#pragma unroll
          for (int k = 0; k < 20; k++) bad |= v[k] ^ ep;
        } while (__any_sync(0xffffffffu, bad & 1) && ++it < 100000);
#pragma unroll
        for (int k = 0; k < 4; k++) sts128(sb + O_BP + ((hw + 1) * 128 + k * 32 + lane) * 16, v[5 * k], v[5 * k + 1], v[5 * k + 2], hadd2(v[5 * k + 3], v[5 * k + 4]));
        fence_async_smem();
        __syncwarp();
      }
      if (lane == 0) mbar_arrive(BAR(B_VV));
      if (warp == 1) {
        if (lane == 0) TSTAMP(37);
        uint32_t v;
        int it = 0;
        do asm volatile("ld.acquire.gpu.global.u32 %0, [%1];" : "=r"(v) : "l"(misc + M_O) : "memory"); while ((int)(v - ep * 16) < 0 && ++it < 100000);
        asm volatile("fence.proxy.async.global;" ::: "memory");
        if (lane == 0) { mbar_arrive(BAR(B_X1)); TSTAMP(30); }
      } else {
        asm volatile("fence.acq_rel.gpu;" ::: "memory");
        __syncwarp();
        if (lane == 0) hint_add((uint32_t*)(misc + M_O));
      }
      __syncwarp();
      asm volatile("barrier.cluster.wait.aligned;" ::: "memory");
    }
  } else {
    const int isE = warp >= 8 ? 1 : 0;
    const int w = warp & 3, r = lane >> 2, c = lane & 3;
    const bool lead = (tid & 127) == 0;
    const int tb = b >> 2;
    if (tid == 256) TSTAMP(75);
    asm volatile("setmaxnreg.inc.sync.aligned.u32 232;");
    const uint32_t sb = __shfl_sync(0xffffffffu, smem_u32(smem_raw), 0);
    auto BAR = [&](int i) { return sb + O_BAR + 8 * i; };
    uint32_t ep;
#pragma unroll
    for (int i = 0; i < 7; i++) mbar_init(BAR(warp - 4 + 8 * i), i == 0 ? 2 << isE : i == 1 ? 4 : 1);
    asm volatile("fence.mbarrier_init.release.cluster;" ::: "memory");
    asm volatile("barrier.cluster.arrive.relaxed.aligned;" ::: "memory");
    if (lead) TSTAMP(76);
    auto first = [&]() { asm volatile("cp.async.wait_all;" ::: "memory"); bar_sync(1, 384); };
    uint32_t A[64];
    auto release = [&](uint32_t m) { if (w == 3 && lane < 12 && ((m >> (lane >> 1)) & 1)) mbar_arrive_cl(mapa(BAR(B_EMPTY + (lane >> 1)), lane & 1)); __syncwarp(); };
    auto aload = [&](int j) {
      const uint32_t sa = sb + bnd(j) + ((r & 1) ? U_RAW : U_ODD) + 4 * (8 * w + (r >> 1) - 3 + c);
#pragma unroll
      for (int g = 0; g < 16; g++) { A[4 * g] = lds32(sa + g * 256); A[4 * g + 1] = lds32(sa + g * 256 + 128); A[4 * g + 2] = lds32(sa + g * 256 + 16); A[4 * g + 3] = lds32(sa + g * 256 + 144); }
      if (lead) TSTAMP(89 + j);
    };
    auto gemv = [&]() {
      float d[16];
      const uint64_t db = mkdesc(SD + O_SILU, 32, 128, 0), da = mkdesc(SD + O_WM, 20480, 512, 2);
      mbar_wait(BAR(B_PL), 0);
      mbar_wait(BAR(B_WM), 0);
      if (lead) TSTAMP(81 + grp);
      if (EM == 2 && w < 2 && lane == 0) hint_add(g_sync + Y_MOD + part * 32);
      wg_fence();
#pragma unroll
      for (int kk = 0; kk < 20; kk++) wgmma_ss_8_10(d + (kk & 3) * 4, da + kk * 64, db + kk * 4, kk >> 2);
      wg_commit();
      wg_wait<0>();
      regfence<16>(d);
#pragma unroll
      for (int i = 0; i < 4; i++) d[i] = (d[i] + d[4 + i]) + (d[8 + i] + d[12 + i]);
      if (EM == 1 && w < 2 && lane == 0) hint_add(g_sync + Y_MOD + part * 32);
      const uint32_t xa = sb + O_SILU + 2048 + (w & 1) * 64 + r * 8;
      if (c == 0 && w >= 2) sts64(xa, __float_as_uint(d[1]), __float_as_uint(d[3]));
      bar_sync(5 + isE, 128);
      if (w < 2) {
        const float2 e = lds64f(xa);
        if (c == 0) { str(g_mod + b * 32 + w * 16 + r, tagf(d[0] + e.x, ep)); str(g_mod + b * 32 + w * 16 + r + 8, tagf(d[2] + e.y, ep)); }
        __syncwarp();
        if (!DM && !EM && lane == 0) hint_add(g_sync + Y_MOD + part * 32);
      }
      if (lead) TSTAMP(grp == 2 ? 60 : 20 + grp);
    };
#pragma unroll 1
    for (int it = 0; it < 3; it++) {
      const int n = it ? it + 2 * isE : 0, tg = lane & 7;
      const bool real = it | isE;
      const uint32_t a = sb + kreg(n) + tg * 64 + ((w ^ (tg >> 1)) << 4) + (lane >> 3) * 4;
      if (it) mbar_wait(BAR(B_K + n), 0); else if (isE) first();
      if (lead && real) TSTAMP(69 + n);
      uint32_t kk[11], x[8];
      ep = lds32(sb + O_EP) + 1;
      const uint4 sw = lds128(sb + kreg(n) + 5632 + w * 64 + (lane & 24) * 2);
#pragma unroll
      for (int i = 0; i < 11; i++) kk[i] = lds32(a + (i < 3 ? 4096 + i * 512 : (i - 3) * 512));
#pragma unroll
      for (int i = 0; i < 8; i++) x[7 - i] = lds32(a + voff(n) + i * 512);
      const uint32_t w0 = prmt(sw.x, sw.z, 0x5410), w1 = prmt(sw.x, sw.z, 0x7632), w2 = prmt(sw.y, sw.w, 0x5410), w3 = prmt(sw.y, sw.w, 0x7632);
#pragma unroll
      for (int i = 0; i < 8; i++) x[7 - i] = hmul2(hfma2(kk[i + 3], w0, hfma2(kk[i + 2], w1, hfma2(kk[i + 1], w2, hmul2(kk[i], w3)))), x[7 - i]);
      hint_addp(!w && (PK ? it : real), g_sync + Y_KV + (n * 4 + (b & 3)) * 32);
      const int tw = (~tb & 7) ^ ((~lane & 1) << 2);
#pragma unroll
      for (int i = 0; i < 4; i++) x[2 * i] = settag(x[2 * i], tw == i ? 0x00010001u : 0u, -(ep & 1));
      const uint32_t o = page(G_KV + n, (b & 3) * 32 + w * 8 + (lane >> 3) * 2) + 4080 - tb * 128 - tg * 16;
      stg128p(real, ps + o, prmt(x[0], x[1], 0x5410), prmt(x[2], x[3], 0x5410), prmt(x[4], x[5], 0x5410), prmt(x[6], x[7], 0x5410));
      stg128p(real, ps + o + 4096, prmt(x[0], x[1], 0x7632), prmt(x[2], x[3], 0x7632), prmt(x[4], x[5], 0x7632), prmt(x[6], x[7], 0x7632));
      if (lead) TSTAMP(real ? 64 + n : 62);
      if (it == 0) {
        if (!isE) first();
        if (PK && isE) {
          const uint32_t o = (tid & 127) * 32 + (lane & 16);
          uint4 u, v;
          int k = 0;
          while (clk() - t_start < T_P) {}
          do { u = ldr4((const uint32_t*)(ps + (page(G_KV, b) + o))); v = ldr4((const uint32_t*)(ps + (page(G_KV, b) + (o ^ 16)))); }
          while (__any_sync(0xffffffffu, ((r & 2 ? r & 1 ? u.w : u.z : r & 1 ? u.y : u.x) ^ ep) & 1) && ++k < 100000);
          sts128(sb + bnd(0) + U_KV + o, u.x, u.y, u.z, u.w);
          sts128(sb + bnd(0) + U_KV + (o ^ 16), v.x, v.y, v.z, v.w);
          fence_async_smem();
          __syncwarp();
          if (lane == 0) mbar_arrive(BAR(B_OK));
          if (lead) TSTAMP(2);
        }
        asm volatile("barrier.cluster.wait.aligned;" ::: "memory");
        if (GE == 1 && isE > grp) gemv();
        mbar_wait(BAR(B_PL + isE), 0);
        aload(isE);
      }
      if (GE == 2 && it == 0 && isE > grp) gemv();
      if (!GE && it == 1 && !(isE | grp)) gemv();
    }
    if (MX && isE) bar_sync(8, 256);
#pragma unroll 1
    for (int j = isE; j < 5; j += 2) {
      const int u = tid & 127;
      const uint32_t pb = sb + (bnd(j) | 16384);
      float d[128];
      mbar_wait(BAR(B_OK + j), 0);
      if (lead) TSTAMP(53 + j);
      const uint64_t db = mkdesc(SD + U_KV, 16, 128, 0) | bnd(j) >> 4;
      wg_fence();
        wgmma_rs_32_0(d + 0, A[0], A[1], A[2], A[3], db + 0, 0);
        wgmma_rs_32_0(d + 16, A[0], A[1], A[2], A[3], db + 32, 0);
        wgmma_rs_32_0(d + 32, A[0], A[1], A[2], A[3], db + 64, 0);
        wgmma_rs_32_0(d + 48, A[0], A[1], A[2], A[3], db + 96, 0);
        wgmma_rs_32_0(d + 0, A[4], A[5], A[6], A[7], db + 16, 1);
        wgmma_rs_32_0(d + 16, A[4], A[5], A[6], A[7], db + 48, 1);
        wgmma_rs_32_0(d + 32, A[4], A[5], A[6], A[7], db + 80, 1);
        wgmma_rs_32_0(d + 48, A[4], A[5], A[6], A[7], db + 112, 1);
        wgmma_rs_32_0(d + 0, A[8], A[9], A[10], A[11], db + 32, 1);
        wgmma_rs_32_0(d + 16, A[8], A[9], A[10], A[11], db + 64, 1);
        wgmma_rs_32_0(d + 32, A[8], A[9], A[10], A[11], db + 96, 1);
        wgmma_rs_32_0(d + 64, A[0], A[1], A[2], A[3], db + 128, 0);
        wgmma_rs_32_0(d + 0, A[12], A[13], A[14], A[15], db + 48, 1);
        wgmma_rs_32_0(d + 16, A[12], A[13], A[14], A[15], db + 80, 1);
        wgmma_rs_32_0(d + 32, A[12], A[13], A[14], A[15], db + 112, 1);
        wgmma_rs_32_0(d + 48, A[8], A[9], A[10], A[11], db + 128, 1);
        wgmma_rs_32_0(d + 0, A[16], A[17], A[18], A[19], db + 64, 1);
        wgmma_rs_32_0(d + 16, A[16], A[17], A[18], A[19], db + 96, 1);
        wgmma_rs_32_0(d + 32, A[16], A[17], A[18], A[19], db + 128, 1);
        wgmma_rs_32_0(d + 64, A[4], A[5], A[6], A[7], db + 144, 1);
        wgmma_rs_32_0(d + 0, A[20], A[21], A[22], A[23], db + 80, 1);
        wgmma_rs_32_0(d + 16, A[20], A[21], A[22], A[23], db + 112, 1);
        wgmma_rs_32_0(d + 48, A[12], A[13], A[14], A[15], db + 144, 1);
        wgmma_rs_32_0(d + 32, A[20], A[21], A[22], A[23], db + 144, 1);
        wgmma_rs_32_0(d + 0, A[24], A[25], A[26], A[27], db + 96, 1);
        wgmma_rs_32_0(d + 16, A[24], A[25], A[26], A[27], db + 128, 1);
        wgmma_rs_32_0(d + 80, A[0], A[1], A[2], A[3], db + 160, 0);
        wgmma_rs_32_0(d + 64, A[8], A[9], A[10], A[11], db + 160, 1);
        wgmma_rs_32_0(d + 0, A[28], A[29], A[30], A[31], db + 112, 1);
        wgmma_rs_32_0(d + 16, A[28], A[29], A[30], A[31], db + 144, 1);
        wgmma_rs_32_0(d + 48, A[16], A[17], A[18], A[19], db + 160, 1);
        wgmma_rs_32_0(d + 32, A[24], A[25], A[26], A[27], db + 160, 1);
        wgmma_rs_32_0(d + 0, A[32], A[33], A[34], A[35], db + 128, 1);
        wgmma_rs_32_0(d + 16, A[32], A[33], A[34], A[35], db + 160, 1);
        wgmma_rs_32_0(d + 80, A[4], A[5], A[6], A[7], db + 176, 1);
        wgmma_rs_32_0(d + 64, A[12], A[13], A[14], A[15], db + 176, 1);
        wgmma_rs_32_0(d + 0, A[36], A[37], A[38], A[39], db + 144, 1);
        wgmma_rs_32_0(d + 48, A[20], A[21], A[22], A[23], db + 176, 1);
        wgmma_rs_32_0(d + 32, A[28], A[29], A[30], A[31], db + 176, 1);
        wgmma_rs_32_0(d + 16, A[36], A[37], A[38], A[39], db + 176, 1);
        wgmma_rs_32_0(d + 0, A[40], A[41], A[42], A[43], db + 160, 1);
        wgmma_rs_32_0(d + 96, A[0], A[1], A[2], A[3], db + 192, 0);
        wgmma_rs_32_0(d + 80, A[8], A[9], A[10], A[11], db + 192, 1);
        wgmma_rs_32_0(d + 64, A[16], A[17], A[18], A[19], db + 192, 1);
        wgmma_rs_32_0(d + 0, A[44], A[45], A[46], A[47], db + 176, 1);
        wgmma_rs_32_0(d + 48, A[24], A[25], A[26], A[27], db + 192, 1);
        wgmma_rs_32_0(d + 32, A[32], A[33], A[34], A[35], db + 192, 1);
        wgmma_rs_32_0(d + 16, A[40], A[41], A[42], A[43], db + 192, 1);
        wgmma_rs_32_0(d + 0, A[48], A[49], A[50], A[51], db + 192, 1);
        wgmma_rs_32_0(d + 96, A[4], A[5], A[6], A[7], db + 208, 1);
        wgmma_rs_32_0(d + 80, A[12], A[13], A[14], A[15], db + 208, 1);
        wgmma_rs_32_0(d + 64, A[20], A[21], A[22], A[23], db + 208, 1);
        wgmma_rs_32_0(d + 48, A[28], A[29], A[30], A[31], db + 208, 1);
        wgmma_rs_32_0(d + 32, A[36], A[37], A[38], A[39], db + 208, 1);
        wgmma_rs_32_0(d + 16, A[44], A[45], A[46], A[47], db + 208, 1);
        wgmma_rs_32_0(d + 0, A[52], A[53], A[54], A[55], db + 208, 1);
        wgmma_rs_32_0(d + 112, A[0], A[1], A[2], A[3], db + 224, 0);
        wgmma_rs_32_0(d + 96, A[8], A[9], A[10], A[11], db + 224, 1);
        wgmma_rs_32_0(d + 80, A[16], A[17], A[18], A[19], db + 224, 1);
        wgmma_rs_32_0(d + 64, A[24], A[25], A[26], A[27], db + 224, 1);
        wgmma_rs_32_0(d + 48, A[32], A[33], A[34], A[35], db + 224, 1);
        wgmma_rs_32_0(d + 32, A[40], A[41], A[42], A[43], db + 224, 1);
        wgmma_rs_32_0(d + 16, A[48], A[49], A[50], A[51], db + 224, 1);
        wgmma_rs_32_0(d + 0, A[56], A[57], A[58], A[59], db + 224, 1);
        wgmma_rs_32_0(d + 112, A[4], A[5], A[6], A[7], db + 240, 1);
        wgmma_rs_32_0(d + 96, A[12], A[13], A[14], A[15], db + 240, 1);
        wgmma_rs_32_0(d + 80, A[20], A[21], A[22], A[23], db + 240, 1);
        wgmma_rs_32_0(d + 64, A[28], A[29], A[30], A[31], db + 240, 1);
        wgmma_rs_32_0(d + 48, A[36], A[37], A[38], A[39], db + 240, 1);
        wgmma_rs_32_0(d + 32, A[44], A[45], A[46], A[47], db + 240, 1);
        wgmma_rs_32_0(d + 16, A[52], A[53], A[54], A[55], db + 240, 1);
        wgmma_rs_32_0(d + 0, A[60], A[61], A[62], A[63], db + 240, 1);
      wg_commit();
      bar_sync(5 + isE, 128);
      if (ER) release(0140242142 >> 6 * j);
      if (j < 3) mbar_wait(BAR(B_PL + 2 + j), 0);
      const uint32_t yoff = pb + w * 2048 + (127 + 2 * w - lane) * 16;
      const uint32_t yoff0 = yoff + (lane < 2 * w ? -2048 : 8192), yoff4 = yoff + (lane < 2 * w ? 6144 : 0);
      wg_wait<0>();
      regfence<128>(d);
      if (j == 4 || MX && j == 0) bar_arrive(8, 256);
      if (j == 4) bar_sync(5, 128);
      if (lead) TSTAMP(42 + j);
      if (EY == 2 && lead) hint_add(g_sync + Y_Y + j * 32);
#pragma unroll
      for (int z = 0; z < 8; z++) {
        uint32_t e[4];
#pragma unroll
        for (int i = 0; i < 4; i++) {
          const int x = 4 * z + i;
          e[i] = x < 31 ? pack2(d[4 * x] + d[4 * x + 6], d[4 * x + 1] + d[4 * x + 7]) : pack2(d[4 * x], d[4 * x + 1]);
        }
        if (z == 0 && c < w) e[0] = 0;
        stsm4t(z == 0 ? yoff0 : z == 4 ? yoff4 : z < 4 ? yoff + 8192 - 512 * z : yoff - 512 * (z - 4), e[0], e[1], e[2], e[3]);
      }
      uint8_t* g = ps + page(G_Y + j, u >> 1) + ((b & 97) | (b & 6) << 2 | (b & 24) >> 2) * 32 + ((u ^ (b >> 4)) & 1) * 16;
      if (EY & 1) hint_addp(!w && (EY == 1 || !j), g_sync + Y_Y + j * 32);
      bar_sync(5 + isE, 128);
      if (EY >= 4) hint_addp(!w && (EY == 4 || j), g_sync + Y_Y + j * 32);
#pragma unroll
      for (int i = 0; i < 2; i++) {
        const uint32_t pa = pb + u * 16 + i * 8192;
        const uint4 p0 = lds128(pa), p1 = lds128(pa + 2048), p2 = lds128(pa + 4096), p3 = lds128(pa + 6144);
        stg128(g + (i << 18), settag(hadd2(hadd2(p0.x, p1.x), hadd2(p2.x, p3.x)), 1, ep), hadd2(hadd2(p0.y, p1.y), hadd2(p2.y, p3.y)),
               hadd2(hadd2(p0.z, p1.z), hadd2(p2.z, p3.z)), hadd2(hadd2(p0.w, p1.w), hadd2(p2.w, p3.w)));
      }
      if (EY % 3 == 0) hint_addp(w == 3 && (!EY || j), g_sync + Y_Y + j * 32);
      if (lead) TSTAMP(84 + j);
      if (!ER) release(0140242142 >> 6 * j);
      if (j < 3) aload(j + 2);
      if (b < 120 && j == (GE == 3 ? max(2 * grp - 1, 0) : 2 * grp - 1)) gemv();
    }
    bar_sync(5 + isE, 128);
    release(isE ? 016 : 010);
    const int rh = isE;
    uint32_t hA[96];
    const uint32_t hb = sb + (isE ? O_REG : 24576) + w * 2048, hs = isE ? 8192 : SLOT;
    auto publish = [&](int kq) {
      asm volatile("st.async.weak.shared::cluster.mbarrier::complete_tx::bytes.v4.b32 [%0], {%1,%2,%3,%4}, [%5];" ::"r"(mapa(hb + lane * 16, kh ^ 1) + (kq >> 2) * hs + (kq & 3) * 512),
                   "r"(hA[4 * kq]), "r"(hA[4 * kq + 1]), "r"(hA[4 * kq + 2]), "r"(hA[4 * kq + 3]), "r"(mapa(BAR(B_HF + isE * 3), kh ^ 1) + (kq >> 2) * 8) : "memory");
      if (kq == 3 && tid == 256) TSTAMP(117);
    };
    {
      float ag[96], au[96], iv[2];
      int slot = 4, prev = 0, s = 0;
      int v0, vo;
      uint32_t vg;
      { ROLE; v0 = min(vr, VR) * 4; vo = (2 * vt + isE) * 256; vg = (fs * 5 + vr) * 384 + (2 * vt + isE) * 64 + 16 * w + r; }
      const uint32_t dbase = mkdesc(sb, 4096, 0, 0);
      uint32_t ck = sb + 24576 + rh * 4096 + w * 1024 + lane * 32 + (r & 1) * 16;
      keep(ck);
      const uint32_t emp = mapa(BAR(B_EMPTY), tid & 1);
      if (isE) bar_sync(8, 256);
      auto check = [&](uint32_t tag) {
        if ((tag ^ ep) & 1) refetch(ps + (lds32(sb + O_XT + s * 4) + rh * 16384 + (tid & 127) * 32), (r & 1) * 16, (ck + slot * SLOT) & ~31u, ep);
        __syncwarp();
        if (lead) TS3(isE, s);
        if (s && s < 20 && (s & 3) == 0 && tid == 128) TSTAMP(37 + (s >> 2));
        if (s == LH + LEAD * isE) { if (isE) bar_arrive(7, 256); else bar_sync(7, 256); }
      };
      auto stage = [&](float* vv) {
        const uint32_t dl = dbase + slot * (SLOT >> 4);
        const uint64_t dg = mkdesc(0, 0, 1024, 1) | dl, da = mkdesc(0, 0, 512, 2) | (dl + ((24576 + rh * 4096) >> 4));
        wg_wait<1>();
        wg_fence();
        if (vv) {
          wgmma_ss_8_10(vv, dg + vo, mkdesc(sb + O_CS, 32, 128, 0) + (s & 3) * 8, s & 3);
          wgmma_ss_8_10(vv, dg + vo + 128, mkdesc(sb + O_CS, 32, 128, 0) + (s & 3) * 8 + 4, 1);
          wg_commit();
        }
        const int sd = s, nx = s == 19 ? 5 : slot == 5 ? 0 : slot + 1;
        const uint32_t par = (0x1c0fc0 >> ++s) & 1;
        uint32_t in, tag;
        auto peek = [&]() { asm volatile("{ .reg .pred p; setp.ne.u32 p, %2, 0; @p ld.shared.u32 %0, [%1]; }" : "=r"(tag) : "r"(addu(ck, nx * SLOT)), "r"(in) : "memory"); };
        if (RP == 0) in = TW ? mbar_try(BAR(B_FULL + nx), par) : mbar_test(BAR(B_FULL + nx), par);
        wgmma_ss_192_01(ag, da, dg, sd);
        if (s > 2 && (tid & 126) == 0) mbar_arrive_cl(addu(emp, prev & 63));
        if (RP == 0) peek();
        if (RP == 1) in = TW ? mbar_try(BAR(B_FULL + nx), par) : mbar_test(BAR(B_FULL + nx), par);
        wgmma_ss_192_01(au, da, mkdesc(0, 0, 1024, 1) | (dl + 768), sd);
        if (RP == 1) peek();
        if (RP == 2) in = TW ? mbar_try(BAR(B_FULL + nx), par) : mbar_test(BAR(B_FULL + nx), par);
        wgmma_ss_192_01(ag, mkdesc(0, 0, 512, 2) | ((uint32_t)da + 2), mkdesc(0, 0, 1024, 1) | (dl + 128), 1);
        if (RP == 2) peek();
        wgmma_ss_192_01(au, mkdesc(0, 0, 512, 2) | ((uint32_t)da + 2), mkdesc(0, 0, 1024, 1) | (dl + 896), 1);
        wg_commit();
        prev = prev >> 8 | slot << 11;
        slot = nx;
        if (!in) { mbar_wait(BAR(B_FULL + nx), par); tag = lds32(addu(ck, nx * SLOT)); }
        check(tag);
      };
      mbar_wait(BAR(B_FULL + 4), 0);
      check(lds32(ck + 4 * SLOT));
      if (lead) TSTAMP(22 + isE);
#pragma unroll 1
      for (int end = v0, k = 0; k < 2; end = 20, k++) {
#pragma unroll 1
        while (s < end) stage(nullptr);
        if (k == 0) {
          float vv[4];
          mbar_wait(BAR(B_CS), 0);
          if (EVV) hint_addp(1, g_sync + Y_VV + vg / 1920 * 32);
#pragma unroll 1
          do stage(vv); while (s & 3);
          wg_wait<1>();
          regfence<4>(vv);
          if (c == 0) { str(g_vv + vg, settag(pack2(vv[0], vv[1]), 1, ep)); str(g_vv + vg + 8, settag(pack2(vv[2], vv[3]), 1, ep)); }
          __syncwarp();
          if (!EVV) hint_addp(1, g_sync + Y_VV + vg / 1920 * 32);
        }
      }
      {
        if (tid == 128) str(g_sync + Y_EP + b * 32, ep);
        wg_wait<1>();
        if ((tid & 126) == 0) mbar_arrive_cl(emp + 32);
        mbar_wait(BAR(B_ST + rh), 0);
        const float2 sa = lds64f(sb + O_ST + rh * 512 + w * 128 + r * 8), sc = lds64f(sb + O_ST + rh * 512 + w * 128 + r * 8 + 64);
        const uint32_t a0 = __float_as_uint(sa.x), a1 = __float_as_uint(sc.x);
        iv[0] = sa.y; iv[1] = sc.y;
        mbar_wait(BAR(B_VV), 0);
        const uint64_t dp = mkdesc(sb + O_BP, 16, 128, 0);
        wg_fence();
        wgmma_rs_192_0(ag, a0, a1, 0, 0, dp, 1);
        wgmma_rs_192_0(au, a0, a1, 0, 0, dp + 192, 1);
        wg_commit();
        wg_wait<1>();
        if ((tid & 126) == 0) mbar_arrive_cl(emp + 40);
        mbar_wait(BAR(isE ? B_ST : B_EMPTY + 2), !isE);
        wg_wait<0>();
      }
      regfence<96>(ag); regfence<96>(au);
      if (lead) TSTAMP(24 + isE);
#pragma unroll
      for (int kq = 0; kq < 12; kq++) {
#pragma unroll
        for (int i = 0; i < 4; i++) hA[4 * kq + i] = pack2(ag[8 * kq + 2 * i] * iv[i & 1] * au[8 * kq + 2 * i], ag[8 * kq + 2 * i + 1] * iv[i & 1] * au[8 * kq + 2 * i + 1]);
        if (kq < 4 * NPUB) publish(kq);
      }
      if (lead) TSTAMP(50 + isE);
    }
    float o[2][32];
    float2 gb[8];
    const uint32_t stg = hb + (lane & 15) * 128 + (((lane >> 4) ^ (lane & 7)) << 4);
    const int row = (b >> 3) * 128 + rh * 64 + 16 * w;
    auto ldgb = [&](int fin) {
#pragma unroll
      for (int u = 0; u < 8; u++) gb[u] = lds64f(sb + O_GB + (ocol(b & 6, fin) + 8 * u + 2 * c) * 4);
      if (fin >= 3) { if (elect()) bulk_wait_read<2>(); __syncwarp(); }
    };
    auto piece = [&](int fin, int u) {
      const float* x = o[fin & 1] + 8 * u;
      const float2 g0 = gb[2 * u], g1 = gb[2 * u + 1];
      stsm4((stg ^ u * 32) + fin % 3 * hs, pack2(x[0] * g0.x, x[1] * g0.y), pack2(x[2] * g0.x, x[3] * g0.y), pack2(x[4] * g1.x, x[5] * g1.y), pack2(x[6] * g1.x, x[7] * g1.y));
    };
    auto flush = [&](int fin) {
      fence_async_smem();
      __syncwarp();
      if (elect()) { tma2d_add(&p.m_out, hb + fin % 3 * hs, ocol(b, fin), row); bulk_commit(); }
    };
    unrolled<10>([&](auto I) {
      constexpr int s = I.v, e = s < 7 ? s : s - 7, src = s < 4 ? s >> 1 : s & 1, blk = s < 4 ? s & 1 : s >> 1;
      constexpr int fin = s == 3 ? 0 : blk - 1;
      const uint64_t dw = mkdesc(sb + w2entry(e), 1024 * s, 1024, 1);
      if (s == 3 || s >= 4 && !src) ldgb(fin);
      if (s == 4) mbar_wait(BAR(B_X1), 0);
      mbar_wait(BAR(B_W2F + e), s >= 7);
      if (s == 6 && tid == 256) TSTAMP(123);
      TS2(3 * s);
      unrolled<12>([&](auto J) {
        constexpr int kk = J.v, n = s < 4 ? kk : src * 12 + kk;
        if (s == 2 && !(kk & 3)) {
          mbar_wait_cluster(BAR(B_HF + isE * 3 + (kk >> 2)), 0);
          if (kk == 0 && lead) TSTAMP(26 + isE);
#pragma unroll
          for (int i = kk; i < kk + 4; i++) {
            const uint4 v = lds128(hb + lane * 16 + (i >> 2) * hs + (i & 3) * 512);
            hA[48 + 4 * i] = v.x; hA[49 + 4 * i] = v.y; hA[50 + 4 * i] = v.z; hA[51 + 4 * i] = v.w;
          }
        }
        if (kk == 0 || s == 2 && !(kk & 3)) wg_fence();
        const uint32_t* h = hA + src * 48 + 4 * kk;
        wgmma_rs_64_1(o[blk & 1], h[0], h[1], h[2], h[3], dw + (kk >> 2) * (e == 6 ? SLOT >> 4 : 512) + (kk & 3) * 128, (src | kk) ? 1 : 0);
        if (s < 2 && (s * 12 + kk) % PUBD == PUBD - 1 && 4 * NPUB + (s * 12 + kk) / PUBD < 12) publish(4 * NPUB + (s * 12 + kk) / PUBD);
        if (kk == QD - 1 && s >= 1 && (s < 4 || !src)) {
          wg_commit();
          wg_wait<1>();
          if (s < 4 && lead) mbar_arrive(BAR(B_W2E + s - 1));
          if (s >= 3) regfence<32>(o[fin & 1]);
          if (s == 4) flush(0);
          TS2(3 * s + 2);
        }
        if (s == 3 && kk >= QD - 1 && (kk - QD + 1) % 2 == 0 && (kk - QD + 1) / 2 < 4) piece(0, (kk - QD + 1) / 2);
        if (s >= 4 && n >= QD - 1 && (n - QD + 1) % 3 == 0 && (n - QD + 1) / 3 < 4) piece(fin, (n - QD + 1) / 3);
        if (s >= 4 && n == QD + 14) flush(fin);
      });
      wg_commit();
      TS2(3 * s + 1);
    });
    ldgb(4);
    mbar_wait(BAR(B_X1), 0);
    wg_wait<0>();
    regfence<32>(o[0]);
    if (lead) TSTAMP(28 + isE);
#pragma unroll
    for (int u = 0; u < 4; u++) piece(4, u);
    flush(4);
    if (tid == 128) TSTAMP(119);
    if (elect()) bulk_wait_read<0>();
    if (tid == 256) TSTAMP(121);
    if (!isE) {
      if (lead) TSTAMP(31);
    }
  }
}

#define L2PROMO CU_TENSOR_MAP_L2_PROMOTION_L2_128B
typedef CUresult (*EncodeFn)(CUtensorMap*, CUtensorMapDataType, cuuint32_t, void*, const cuuint64_t*, const cuuint64_t*, const cuuint32_t*,
                             const cuuint32_t*, CUtensorMapInterleave, CUtensorMapSwizzle, CUtensorMapL2promotion, CUtensorMapFloatOOBfill);

void make_map(EncodeFn enc, CUtensorMap* m, const void* ptr, uint64_t inner, uint64_t outer, uint32_t bi, uint32_t bo, CUtensorMapSwizzle sw) {
  cuuint64_t d[2] = {inner, outer};
  cuuint64_t s[1] = {inner * 2};
  cuuint32_t bx[2] = {bi, bo};
  cuuint32_t e[2] = {1, 1};
  enc(m, CU_TENSOR_MAP_DATA_TYPE_BFLOAT16, 2, const_cast<void*>(ptr), d, s, bx, e, CU_TENSOR_MAP_INTERLEAVE_NONE, sw, L2PROMO,
      CU_TENSOR_MAP_FLOAT_OOB_FILL_NONE);
}

void make_map3(EncodeFn enc, CUtensorMap* m, const void* ptr, uint64_t d0, uint64_t d1, uint64_t d2, uint64_t s1, uint64_t s2, uint32_t b0, uint32_t b1, uint32_t b2,
               CUtensorMapSwizzle sw, uint64_t s3 = 0) {
  cuuint64_t d[4] = {d0, d1, d2, 2};
  cuuint64_t s[3] = {s1, s2, s3};
  cuuint32_t bx[4] = {b0, b1, b2, 2};
  cuuint32_t e[4] = {1, 1, 1, 1};
  enc(m, CU_TENSOR_MAP_DATA_TYPE_BFLOAT16, s3 ? 4 : 3, const_cast<void*>(ptr), d, s, bx, e, CU_TENSOR_MAP_INTERLEAVE_NONE, sw, L2PROMO,
      CU_TENSOR_MAP_FLOAT_OOB_FILL_NONE);
}

}

extern "C" void kernel_launch(void* const* d_in, const int* in_sizes, int n_in, void* d_out, int out_size) {
  (void)in_sizes; (void)n_in; (void)out_size;
  void* f = nullptr;
  cudaDriverEntryPointQueryResult qr;
  cudaGetDriverEntryPoint("cuTensorMapEncodeTiled", &f, cudaEnableDefault, &qr);
  EncodeFn enc = (EncodeFn)f;
  void* s;
  cudaGetSymbolAddress(&s, g_s);
  Params p = {};
  uint8_t* ps = (uint8_t*)(((uintptr_t)s + (2 << 20) - 1) & ~(uintptr_t)((2 << 20) - 1));
  make_map3(enc, &p.m_k, d_in[1], D_, S_ / 8, 8, 8 * D_ * 2, D_ * 2, 32, 8, 8, CU_TENSOR_MAP_SWIZZLE_64B);
  make_map3(enc, &p.m_kh, d_in[1], D_, S_ / 8, 8, 8 * D_ * 2, D_ * 2, 32, 8, 3, CU_TENSOR_MAP_SWIZZLE_64B);
  make_map3(enc, &p.m_v, d_in[2], D_, S_ / 8, 8, 8 * D_ * 2, D_ * 2, 32, 8, 8, CU_TENSOR_MAP_SWIZZLE_64B);
  make_map3(enc, &p.m_q, d_in[0], 32, S_, D_ / 32, D_ * 2, 64, 32, 16, D_ / 32, CU_TENSOR_MAP_SWIZZLE_64B);
  make_map3(enc, &p.m_wm, d_in[11], 6 * D_, 160, 4, 12 * D_, 160 * 12 * D_, 32, 160, 4, CU_TENSOR_MAP_SWIZZLE_64B);
  const int lo = (uintptr_t)d_in[7] < (uintptr_t)d_in[8] ? 7 : 8;
  make_map3(enc, &p.m_w1, d_in[lo], 64, D_, F_ / 64, F_ * 2, 128, 64, 32, 3, CU_TENSOR_MAP_SWIZZLE_128B, (uintptr_t)d_in[15 - lo] - (uintptr_t)d_in[lo]);
  make_map(enc, &p.m_w2, d_in[9], D_, F_, 64, 64, CU_TENSOR_MAP_SWIZZLE_128B);
  make_map(enc, &p.m_out, d_out, D_, S_, 64, 16, CU_TENSOR_MAP_SWIZZLE_128B);
  p.c = (const __nv_bfloat16*)d_in[10];
  p.wg = (const __nv_bfloat16*)d_in[7];
  p.wu = (const __nv_bfloat16*)d_in[8];
  p.w2 = (const __nv_bfloat16*)d_in[9];
  p.out = (uint8_t*)d_out;
  cudaFuncSetAttribute(fused_kernel, cudaFuncAttributeMaxDynamicSharedMemorySize, SMEM_BYTES);
  fused_kernel<<<128, 384, SMEM_BYTES, cudaStreamPerThread>>>((const uint8_t*)d_in[1], (uintptr_t)d_in[2] - (uintptr_t)d_in[1], (uintptr_t)d_in[3] - (uintptr_t)d_in[1],
                                                              (const __nv_bfloat16*)d_in[4], (const __nv_bfloat16*)d_in[5], ps, p);
}
```

```cpp
#include <cuda_runtime.h>
#include <cuda.h>
#include <cuda_bf16.h>
#include <cstdint>

namespace {

constexpr int S_ = 2048, D_ = 640, F_ = 1536;

__device__ __align__(1024) uint8_t g_s[10 << 20];
#define g_sync ((uint32_t*)(ps + (1 << 16)))
#define g_mod ((uint32_t*)(ps + (2 << 16)))
#define g_vv ((uint32_t*)(ps + (3 << 16)))
#define TIMOFF (4 << 16)
enum { Y_KV = 0, Y_Y = 20 * 32, Y_MOD = 25 * 32, Y_VV = 31 * 32, Y_EP = 4 };
enum { G_KV = 1, G_Y = 6, G_X = 11 };
enum { M_X = 0, M_O = 96, M_ST = 512 };
#define TSTAMP(i) do { } while (0)
#define TS3(k, i) do { } while (0)
#define TS2(i) do { } while (0)
#define TS 7
#define SCH 1
#define T0 1000
#define TR 100
#define O7 4
#define T_K1 T0
#define T_K2 (T0 + 7 * TR)
#define T_S1 (T0 + 14 * TR)
#define T_K3 (T0 + 175 * TR / 10)
#define T_WM0 (T0 + (O7 & 1 ? 280 : 245) * TR / 10)
#define T_S2 (T0 + (O7 & 1 ? 245 : 300) * TR / 10)
#define T_Q (T0 + (O7 & 16 ? 370 : O7 & 8 ? 475 : O7 & 4 ? 440 : O7 & 2 ? 405 : 335) * TR / 10)
#define T_K4 (T0 + (O7 & 16 ? 545 : O7 & 6 ? 335 : 510) * TR / 10)
#define T_S3 (T0 + (O7 & 16 ? 335 : O7 & 4 ? 405 : 580) * TR / 10)
#define T_S4 (T0 + (O7 & 8 ? 440 : 615) * TR / 10)
#define T_WM1 (T0 + 65 * TR)
#define T_W0 (T0 + 71 * TR)
#define T_WM2 (T0 + 76 * TR)
#define T_S0 600
#define D_Q 54
#define D_WM 27
#define NE0 1
#define NE 2
#define STEP(kv, gv, cv, fa) ((kv + 1) | (gv + 1) << 3 | (cv + 1) << 5 | (fa + 1) << 8)
#define EV 8
#define EV0 31
#define EV1 0ull
#define EV2 0x14401210ull
#define EV3 0x411311ull
#define LJ 9
#define LU 0
#define LT 0
#define XG 3
#define WI 3
#define GA 2
#define T_W3 8000
#define D_W3 20
#define B5 80
#define T_P1 5500
#define FR 1
#define PS 3
#define FD 6
#define PA 8
#define FA 0
#define XW 0
#define KP 0
#define YW 0
#define YF 0
#define T_M 0
#define LB 0
#define KO 1
#define NH 5
#define SCHED_E STEP(0, -1, -1, 1), STEP(2, -1, -1, -1), STEP(4, -1, 1, 3), STEP(-1, 1, 3, -1), STEP(-1, 2, -1, -1)
#define SCHED_L STEP(-1, -1, -1, 0), STEP(1, 0, -1, -1), STEP(3, -1, 0, 2), STEP(-1, -1, 2, 4), STEP(-1, -1, 4, -1)
#define PFW 0x71u
#define PF2 0xc80u
#define AH 1
#define PD 3
#define ROT 1
#define QD 5
#define PUBD 2
#define NPUB 1
#define LH 17
#define MX 0
#define WARM 1
#define RS 2
#define GE 6
#define ER 1
#define VR 3
#define EVV 1
#define DM 1
#define PK 1
#define GO 1
#define PW 1
#define XQ 1
#define T_P 3800
#define EK 1
#define EY 4
#define EM 0
#define RP 2
#define TW 0
#define LEAD 2

struct Params {
  CUtensorMap m_k, m_kh, m_v, m_q, m_wm, m_w1, m_w2, m_out;
  const __nv_bfloat16 *c, *wg, *wu, *w2;
  uint8_t* out;
};
constexpr int NLD = 12;
__host__ __device__ constexpr uint32_t nth_load(int n) {
  const uint32_t when[NLD] = {T_K1 << 8 | 1, T_K2 << 8 | 2, T_K3 << 8 | 3, T_K4 << 8 | 4, T_S0 << 8 | 16, T_S1 << 8 | 17, T_S2 << 8 | 18, T_S3 << 8 | 19, T_S4 << 8 | 20,
                              T_Q << 8 | 21, T_WM0 << 8 | 32, T_WM1 << 8 | 33};
  for (int i = 0; i < NLD; i++) {
    int rank = 0;
    for (int k = 0; k < NLD; k++) rank += when[k] < when[i];
    if (rank == n) return when[i];
  }
  return 0;
}
__host__ __device__ constexpr uint64_t sched(int g) {
  const uint32_t t[2][5] = {{SCHED_L}, {SCHED_E}};
  uint64_t r = 0;
  for (int i = 0; i < 5; i++) r |= (uint64_t)t[g][i] << 12 * i;
  return r;
}
template <int I> struct IC { static constexpr int v = I; };
template <int N, class F> __device__ __forceinline__ void unrolled(F f) {
  if constexpr (N > 0) { unrolled<N - 1>(f); f(IC<N - 1>()); }
}

constexpr uint32_t SLOT = 32768;
constexpr uint32_t SD = 1024;
constexpr uint32_t U_RAW = 16, U_ODD = U_RAW + 4160, U_KV = 8448;
constexpr uint32_t O_WM = 2 * SLOT;
constexpr uint32_t O_SILU = O_WM + 40960;
constexpr uint32_t O_REG = 6 * SLOT;
constexpr uint32_t O_Y = O_REG + 20480;
constexpr uint32_t O_BP = O_Y + 4096;
constexpr uint32_t O_MA = O_BP + 4096;
constexpr uint32_t O_ST = O_BP + 7040;
constexpr uint32_t O_CS = O_ST + 1024;
constexpr uint32_t O_GB = O_CS + 640;
constexpr uint32_t O_LN = O_GB + 1280;
constexpr uint32_t O_EP = O_GB + 1280 + 64;
constexpr uint32_t O_BAR = O_EP + 192;
constexpr uint32_t O_XT = O_EP + 64;
constexpr uint32_t SMEM_BYTES = O_BAR + 1024;
static_assert(SMEM_BYTES <= 232448, "smem");
enum { B_W2E = 0, B_EMPTY = 4, B_LN = 10, B_VV = 11, B_YE = 12, B_OK = 16 - PK, B_FULL = 21, B_W2F = 27, B_HF = 34, B_KV = 40,
       B_CS = 45, B_X1 = 46, B_ST = 47, B_SSM = 56, B_QIN = 61, B_WM = 62, B_K = 62, B_PL = 67, B_PR = XQ ? 72 : 49 };
__device__ __forceinline__ uint32_t kreg(int n) { return n != 2 ? (0x1309b >> 4 * n & 15) << 14 : 4 * SLOT + 26624; }
__device__ __forceinline__ uint32_t voff(int n) { return n != 2 ? 6144 : -4 * SLOT; }
__device__ __forceinline__ uint32_t w2entry(int e) { return e == 6 ? 3 * SLOT + 24576 : e * SLOT; }
__device__ __forceinline__ int ocol(int ro, int i) { i += ROT * ((ro >> 1) & 3); return (ro & 1) * 320 + (i < 5 ? i : i - 5) * 64; }
__device__ __forceinline__ uint32_t bnd(int j) { return (0x720a8 >> 4 * j & 15) << 14; }
__device__ __forceinline__ uint32_t page(int g, int p) { return g << 19 | p << 12; }
__device__ __forceinline__ uint32_t tile(int rb, int x) { return page(G_X + (x >> 2), rb * 8 + (x & 3)); }

__device__ __forceinline__ uint32_t smem_u32(const void* p) { return (uint32_t)__cvta_generic_to_shared(p); }
__device__ __forceinline__ void mbar_init(uint32_t bar, uint32_t cnt) { asm volatile("mbarrier.init.shared::cta.b64 [%0], %1;" ::"r"(bar), "r"(cnt) : "memory"); }
__device__ __forceinline__ void mbar_expect(uint32_t bar, uint32_t bytes) { asm volatile("mbarrier.arrive.expect_tx.shared::cta.b64 _, [%0], %1;" ::"r"(bar), "r"(bytes) : "memory"); }
__device__ __forceinline__ void mbar_arrive(uint32_t bar) { asm volatile("mbarrier.arrive.shared::cta.b64 _, [%0];" ::"r"(bar) : "memory"); }
__device__ __forceinline__ void mbar_wait(uint32_t bar, uint32_t parity) {
  asm volatile("{\n .reg .pred p;\n .reg .u32 c;\n mov.u32 c, 0;\n LOOP:\n mbarrier.try_wait.parity.shared::cta.b64 p, [%0], %1;\n @p bra DONE;\n add.u32 c, c, 1;\n setp.lt.u32 p, c, 200000;\n @p bra LOOP;\n DONE:\n }" ::"r"(bar), "r"(parity) : "memory");
}
__device__ __forceinline__ void mbar_wait_cluster(uint32_t bar, uint32_t parity) {
  asm volatile("{\n .reg .pred p;\n .reg .u32 c;\n mov.u32 c, 0;\n LOOP:\n mbarrier.try_wait.parity.acquire.cluster.shared::cta.b64 p, [%0], %1;\n @p bra DONE;\n add.u32 c, c, 1;\n setp.lt.u32 p, c, 200000;\n @p bra LOOP;\n DONE:\n }" ::"r"(bar), "r"(parity) : "memory");
}
__device__ __forceinline__ bool mbar_test(uint32_t bar, uint32_t parity) {
  uint32_t r;
  asm volatile("{ .reg .pred p; mbarrier.test_wait.parity.shared::cta.b64 p, [%1], %2; selp.u32 %0, 1, 0, p; }" : "=r"(r) : "r"(bar), "r"(parity) : "memory");
  return r;
}
__device__ __forceinline__ bool mbar_try(uint32_t bar, uint32_t parity) {
  uint32_t r;
  asm volatile("{ .reg .pred p; mbarrier.try_wait.parity.shared::cta.b64 p, [%1], %2; selp.u32 %0, 1, 0, p; }" : "=r"(r) : "r"(bar), "r"(parity) : "memory");
  return r;
}
__device__ __forceinline__ uint32_t mapa(uint32_t a, uint32_t cta) { uint32_t r; asm("mapa.shared::cluster.u32 %0, %1, %2;" : "=r"(r) : "r"(a), "r"(cta)); return r; }
__device__ __forceinline__ void mbar_arrive_cl(uint32_t bar) { asm volatile("mbarrier.arrive.shared::cluster.b64 _, [%0];" ::"r"(bar) : "memory"); }
__device__ __forceinline__ void edge(uint32_t x) { asm volatile("{ .reg .pred p; .reg .u32 c; mov.u32 c, %0;\n L: setp.lt.u32 p, c, 99;\n @p bra.uni D;\n mov.u32 c, %%clock;\n bra.uni L;\n D: }" ::"r"(x) : "memory"); }
__device__ __forceinline__ bool elect() { uint32_t p; asm volatile("{ .reg .pred q; elect.sync _|q, 0xffffffff; selp.u32 %0, 1, 0, q; }" : "=r"(p)); return p; }
__device__ __forceinline__ uint32_t clk() { uint32_t c; asm volatile("mov.u32 %0, %%clock;" : "=r"(c)); return c; }
__device__ __forceinline__ uint32_t ldr(const uint32_t* p) { uint32_t v; asm volatile("ld.relaxed.gpu.global.u32 %0, [%1];" : "=r"(v) : "l"(p) : "memory"); return v; }
__device__ __forceinline__ uint4 ldr4(const uint32_t* p) {
  uint4 v; asm volatile("ld.relaxed.gpu.global.v4.u32 {%0,%1,%2,%3}, [%4];" : "=r"(v.x), "=r"(v.y), "=r"(v.z), "=r"(v.w) : "l"(p) : "memory"); return v;
}
__device__ __forceinline__ void poll_ge(const uint32_t* p, uint32_t target) {
  asm volatile("{\n .reg .pred p;\n .reg .u32 c, v;\n mov.u32 c, 0;\n LOOP:\n ld.relaxed.gpu.global.u32 v, [%0];\n sub.u32 v, v, %1;\n setp.ge.s32 p, v, 0;\n @p bra DONE;\n add.u32 c, c, 1;\n setp.lt.u32 p, c, 100000;\n @p bra LOOP;\n DONE:\n }" ::"l"(p), "r"(target) : "memory");
}
__device__ __forceinline__ void poll_lane(uint32_t& v, const void* p, uint32_t target, int l) {
  for (int it = 0; !((__ballot_sync(0xffffffffu, (int)(v - target) >= 0) >> l) & 1) && it < 100000; it++) v = ldr((const uint32_t*)p);
}
__device__ __forceinline__ void hint_add(uint32_t* p) { asm volatile("red.relaxed.gpu.global.add.u32 [%0], 1;" ::"l"(p) : "memory"); }
__device__ __forceinline__ void refetch(const void* g, uint32_t off, uint32_t a, uint32_t tag) {
  asm volatile("{\n .reg .pred p;\n .reg .u32 c, v, x, y, z;\n .reg .u64 q;\n mov.u32 c, 0;\n cvt.u64.u32 q, %1;\n add.u64 q, q, %0;\n"
               " LOOP:\n ld.relaxed.gpu.global.u32 v, [q];\n xor.b32 v, v, %3;\n and.b32 v, v, 1;\n setp.eq.u32 p, v, 0;\n @p bra DONE;\n add.u32 c, c, 1;\n setp.lt.u32 p, c, 100000;\n @p bra LOOP;\n"
               " DONE:\n ld.relaxed.gpu.global.v4.u32 {v, x, y, z}, [%0];\n st.shared.v4.u32 [%2], {v, x, y, z};\n ld.relaxed.gpu.global.v4.u32 {v, x, y, z}, [%0+16];\n xor.b32 c, %2, 16;\n"
               " st.shared.v4.u32 [c], {v, x, y, z};\n fence.proxy.async.shared::cta;\n }" ::"l"(g), "r"(off), "r"(a), "r"(tag) : "memory");
}
__device__ __forceinline__ void refetch_all(const void* g, uint32_t off, uint32_t a, uint32_t tag) {
  asm volatile("{\n .reg .pred p;\n .reg .u32 c, v, x, y, z;\n .reg .u64 q;\n mov.u32 c, 0;\n cvt.u64.u32 q, %1;\n add.u64 q, q, %0;\n"
               " LOOP:\n ld.relaxed.gpu.global.u32 v, [q];\n xor.b32 v, v, %3;\n and.b32 v, v, 1;\n setp.eq.u32 p, v, 0;\n vote.sync.all.pred p, p, 0xffffffff;\n @p bra DONE;\n add.u32 c, c, 1;\n setp.lt.u32 p, c, 100000;\n @p bra LOOP;\n"
               " DONE:\n ld.relaxed.gpu.global.v4.u32 {v, x, y, z}, [%0];\n st.shared.v4.u32 [%2], {v, x, y, z};\n ld.relaxed.gpu.global.v4.u32 {v, x, y, z}, [%0+16];\n xor.b32 c, %2, 16;\n"
               " st.shared.v4.u32 [c], {v, x, y, z};\n fence.proxy.async.shared::cta;\n }" ::"l"(g), "r"(off), "r"(a), "r"(tag) : "memory");
}
__device__ __forceinline__ void refetch16(const void* g, uint32_t a, uint32_t tag) {
  asm volatile("{\n .reg .pred p;\n .reg .u32 c, t, v, x, y, z;\n mov.u32 c, 0;\n"
               " LOOP:\n ld.relaxed.gpu.global.v4.u32 {v, x, y, z}, [%0];\n xor.b32 t, v, %2;\n and.b32 t, t, 1;\n setp.eq.u32 p, t, 0;\n vote.sync.all.pred p, p, 0xffffffff;\n @p bra DONE;\n add.u32 c, c, 1;\n setp.lt.u32 p, c, 100000;\n @p bra LOOP;\n"
               " DONE:\n st.shared.v4.u32 [%1], {v, x, y, z};\n }" ::"l"(g), "r"(a), "r"(tag) : "memory");
}
__device__ __forceinline__ uint2 ldr2(const uint32_t* p) {
  uint2 v; asm volatile("ld.relaxed.gpu.global.v2.u32 {%0,%1}, [%2];" : "=r"(v.x), "=r"(v.y) : "l"(p) : "memory"); return v;
}
__device__ __forceinline__ uint32_t settag(uint32_t x, uint32_t m, uint32_t t) { return (x & ~m) | (t & m); }
__device__ __forceinline__ void stg128(void* p, uint32_t x, uint32_t y, uint32_t z, uint32_t w) {
  asm volatile("st.global.v4.u32 [%0], {%1,%2,%3,%4};" ::"l"(p), "r"(x), "r"(y), "r"(z), "r"(w) : "memory");
}
__device__ __forceinline__ void stg128p(uint32_t on, void* p, uint32_t x, uint32_t y, uint32_t z, uint32_t w) {
  asm volatile("{ .reg .pred q; setp.ne.u32 q, %5, 0; @q st.global.v4.u32 [%0], {%1,%2,%3,%4}; }" ::"l"(p), "r"(x), "r"(y), "r"(z), "r"(w), "r"(on) : "memory");
}
__device__ __forceinline__ void hint_addp(uint32_t on, uint32_t* p) { asm volatile("{ .reg .pred p, q; elect.sync _|p, 0xffffffff; setp.ne.and.u32 q, %1, 0, p; @q red.relaxed.gpu.global.add.u32 [%0], 1; }" ::"l"(p), "r"(on) : "memory"); }
__device__ __forceinline__ void cpa16(uint32_t dst, const void* src, uint32_t n) { asm volatile("cp.async.cg.shared.global [%0], [%1], 16, %2;" ::"r"(dst), "l"(src), "r"(n) : "memory"); }
__device__ __forceinline__ void tma3d(uint32_t dst, const CUtensorMap* m, int x, int y, int z, uint32_t bar) {
  asm volatile("cp.async.bulk.tensor.3d.shared::cluster.global.mbarrier::complete_tx::bytes [%0], [%1, {%3, %4, %5}], [%2];" ::"r"(dst), "l"(m), "r"(bar), "r"(x), "r"(y), "r"(z) : "memory");
}
__device__ __forceinline__ void tma4d(uint32_t dst, const CUtensorMap* m, int x, int y, int z, int u, uint32_t bar) {
  asm volatile("cp.async.bulk.tensor.4d.shared::cluster.global.mbarrier::complete_tx::bytes [%0], [%1, {%3, %4, %5, %6}], [%2];" ::"r"(dst), "l"(m), "r"(bar), "r"(x), "r"(y), "r"(z), "r"(u) : "memory");
}
__device__ __forceinline__ void bulk_st(void* dst, uint32_t src, uint32_t bytes) {
  asm volatile("cp.async.bulk.global.shared::cta.bulk_group [%0], [%1], %2;" ::"l"(dst), "r"(src), "r"(bytes) : "memory");
}
__device__ __forceinline__ void bulk_pf(const void* src, uint32_t bytes) { asm volatile("cp.async.bulk.prefetch.L2.global [%0], %1;" ::"l"(src), "r"(bytes) : "memory"); }
__device__ __forceinline__ void tma2d(uint32_t dst, const CUtensorMap* m, int x, int y, uint32_t bar) {
  asm volatile("cp.async.bulk.tensor.2d.shared::cluster.global.mbarrier::complete_tx::bytes [%0], [%1, {%3, %4}], [%2];" ::"r"(dst), "l"(m), "r"(bar), "r"(x), "r"(y) : "memory");
}
__device__ __forceinline__ void tma2d_add(const CUtensorMap* m, uint32_t src, int x, int y) {
  asm volatile("cp.reduce.async.bulk.tensor.2d.global.shared::cta.add.tile.bulk_group [%0, {%2, %3}], [%1];" ::"l"(m), "r"(src), "r"(x), "r"(y) : "memory");
}
__device__ __forceinline__ void bulk_ld(uint32_t dst, const void* src, uint32_t bytes, uint32_t bar) {
  asm volatile("cp.async.bulk.shared::cluster.global.mbarrier::complete_tx::bytes [%0], [%1], %2, [%3];" ::"r"(dst), "l"(src), "r"(bytes), "r"(bar) : "memory");
}
__device__ __forceinline__ void bulk_commit() { asm volatile("cp.async.bulk.commit_group;" ::: "memory"); }
template <int N> __device__ __forceinline__ void bulk_wait() { asm volatile("cp.async.bulk.wait_group %0;" ::"n"(N) : "memory"); }
template <int N> __device__ __forceinline__ void bulk_wait_read() { asm volatile("cp.async.bulk.wait_group.read %0;" ::"n"(N) : "memory"); }
__device__ __forceinline__ void fence_async_smem() { asm volatile("fence.proxy.async.shared::cta;" ::: "memory"); }
__device__ __forceinline__ void bar_sync(int id, int n) { asm volatile("bar.sync %0, %1;" ::"r"(id), "r"(n) : "memory"); }
__device__ __forceinline__ void bar_arrive(int id, int n) { asm volatile("bar.arrive %0, %1;" ::"r"(id), "r"(n) : "memory"); }
__device__ __forceinline__ void wg_fence() { asm volatile("wgmma.fence.sync.aligned;" ::: "memory"); }
__device__ __forceinline__ void wg_commit() { asm volatile("wgmma.commit_group.sync.aligned;" ::: "memory"); }
template <int N> __device__ __forceinline__ void wg_wait() { asm volatile("wgmma.wait_group.sync.aligned %0;" ::"n"(N) : "memory"); }
__device__ __forceinline__ void ldsm4(uint32_t a, uint32_t& r0, uint32_t& r1, uint32_t& r2, uint32_t& r3) {
  asm volatile("ldmatrix.sync.aligned.m8n8.x4.shared.b16 {%0,%1,%2,%3}, [%4];" : "=r"(r0), "=r"(r1), "=r"(r2), "=r"(r3) : "r"(a) : "memory");
}
__device__ __forceinline__ void ldsm4t(uint32_t a, uint32_t& r0, uint32_t& r1, uint32_t& r2, uint32_t& r3) {
  asm volatile("ldmatrix.sync.aligned.m8n8.x4.trans.shared.b16 {%0,%1,%2,%3}, [%4];" : "=r"(r0), "=r"(r1), "=r"(r2), "=r"(r3) : "r"(a) : "memory");
}
__device__ __forceinline__ void stsm4t(uint32_t a, uint32_t r0, uint32_t r1, uint32_t r2, uint32_t r3) {
  asm volatile("stmatrix.sync.aligned.m8n8.x4.trans.shared.b16 [%0], {%1,%2,%3,%4};" ::"r"(a), "r"(r0), "r"(r1), "r"(r2), "r"(r3) : "memory");
}
__device__ __forceinline__ void stsm4(uint32_t a, uint32_t r0, uint32_t r1, uint32_t r2, uint32_t r3) {
  asm volatile("stmatrix.sync.aligned.m8n8.x4.shared.b16 [%0], {%1,%2,%3,%4};" ::"r"(a), "r"(r0), "r"(r1), "r"(r2), "r"(r3) : "memory");
}
__device__ __forceinline__ uint32_t lds32(uint32_t a) { uint32_t v; asm volatile("ld.shared.u32 %0, [%1];" : "=r"(v) : "r"(a) : "memory"); return v; }
__device__ __forceinline__ uint4 lds128(uint32_t a) { uint4 v; asm volatile("ld.shared.v4.u32 {%0,%1,%2,%3}, [%4];" : "=r"(v.x), "=r"(v.y), "=r"(v.z), "=r"(v.w) : "r"(a) : "memory"); return v; }
__device__ __forceinline__ float4 lds128f(uint32_t a) { float4 v; asm volatile("ld.shared.v4.f32 {%0,%1,%2,%3}, [%4];" : "=f"(v.x), "=f"(v.y), "=f"(v.z), "=f"(v.w) : "r"(a) : "memory"); return v; }
__device__ __forceinline__ float2 lds64f(uint32_t a) { float2 v; asm volatile("ld.shared.v2.f32 {%0,%1}, [%2];" : "=f"(v.x), "=f"(v.y) : "r"(a) : "memory"); return v; }
__device__ __forceinline__ void sts32(uint32_t a, uint32_t v) { asm volatile("st.shared.u32 [%0], %1;" ::"r"(a), "r"(v) : "memory"); }
__device__ __forceinline__ void sts64(uint32_t a, uint32_t x, uint32_t y) { asm volatile("st.shared.v2.u32 [%0], {%1,%2};" ::"r"(a), "r"(x), "r"(y) : "memory"); }
__device__ __forceinline__ void sts128(uint32_t a, uint32_t x, uint32_t y, uint32_t z, uint32_t w) { asm volatile("st.shared.v4.u32 [%0], {%1,%2,%3,%4};" ::"r"(a), "r"(x), "r"(y), "r"(z), "r"(w) : "memory"); }
__device__ __forceinline__ void sts16(uint32_t a, uint16_t v) { asm volatile("st.shared.u16 [%0], %1;" ::"r"(a), "h"(v) : "memory"); }
__device__ __forceinline__ uint32_t prmt(uint32_t a, uint32_t b, uint32_t s) { uint32_t r; asm("prmt.b32 %0, %1, %2, %3;" : "=r"(r) : "r"(a), "r"(b), "r"(s)); return r; }
__device__ __forceinline__ uint32_t hfma2(uint32_t a, uint32_t b, uint32_t c) { uint32_t r; asm("fma.rn.bf16x2 %0, %1, %2, %3;" : "=r"(r) : "r"(a), "r"(b), "r"(c)); return r; }
__device__ __forceinline__ uint32_t hfma2lh(uint32_t a, uint32_t l) {
  uint32_t r;
  asm("{ .reg .b16 x, y; .reg .b32 u, v; mov.b32 {x, y}, %2; mov.b32 u, {x, x}; mov.b32 v, {y, y}; fma.rn.bf16x2 %0, %1, u, v; }" : "=r"(r) : "r"(a), "r"(l));
  return r;
}
__device__ __forceinline__ uint32_t addu(uint32_t a, uint32_t u) { uint32_t r; asm("add.u32 %0, %1, %2;" : "=r"(r) : "r"(a), "r"(u)); return r; }
__device__ __forceinline__ uint32_t tag0(uint32_t x, uint32_t t) { uint32_t r; asm("lop3.b32 %0, %1, 1, %2, 0xb8;" : "=r"(r) : "r"(x), "r"(t)); return r; }
__device__ __forceinline__ void keep(uint32_t& x) { x = __shfl_xor_sync(0xffffffffu, x, 0); }
__device__ __forceinline__ uint32_t hmul2(uint32_t a, uint32_t b) { uint32_t r; asm("mul.rn.bf16x2 %0, %1, %2;" : "=r"(r) : "r"(a), "r"(b)); return r; }
__device__ __forceinline__ uint32_t pack2(float lo, float hi) { uint32_t r; asm("cvt.rn.bf16x2.f32 %0, %1, %2;" : "=r"(r) : "f"(hi), "f"(lo)); return r; }
__device__ __forceinline__ float blo(uint32_t v) { return __uint_as_float(v << 16); }
__device__ __forceinline__ float bhi(uint32_t v) { return __uint_as_float(v & 0xffff0000u); }
__device__ __forceinline__ uint32_t hadd2(uint32_t a, uint32_t b) { uint32_t r; asm("add.rn.bf16x2 %0, %1, %2;" : "=r"(r) : "r"(a), "r"(b)); return r; }
__device__ __forceinline__ void str(uint32_t* p, uint32_t v) { asm volatile("st.relaxed.gpu.global.u32 [%0], %1;" ::"l"(p), "r"(v) : "memory"); }
__device__ __forceinline__ uint32_t tagf(float x, uint32_t tag) { return (__float_as_uint(x) & ~3u) | (tag & 3); }
template <int N> __device__ __forceinline__ float4 gather4(const uint32_t* p, int stride, uint32_t tag) {
  uint4 v[N];
  int it = 0;
  uint32_t bad;
  do {
#pragma unroll
    for (int i = 0; i < N; i++) v[i] = ldr4(p + i * stride);
    bad = 0;
#pragma unroll
    for (int i = 0; i < N; i++) bad |= (v[i].x ^ tag) | (v[i].y ^ tag) | (v[i].z ^ tag) | (v[i].w ^ tag);
  } while ((bad & 3) && ++it < 100000);
  float4 s = make_float4(__uint_as_float(v[0].x), __uint_as_float(v[0].y), __uint_as_float(v[0].z), __uint_as_float(v[0].w));
#pragma unroll
  for (int i = 1; i < N; i++) { s.x += __uint_as_float(v[i].x); s.y += __uint_as_float(v[i].y); s.z += __uint_as_float(v[i].z); s.w += __uint_as_float(v[i].w); }
  return s;
}
__device__ __forceinline__ float rbf(float x) { return blo(pack2(x, 0.f)); }
__device__ __forceinline__ uint64_t mkdesc(uint32_t addr, uint32_t lbo, uint32_t sbo, uint32_t swz) {
  return (uint64_t)((addr & 0x3FFFF) >> 4) | ((uint64_t)(lbo >> 4) << 16) | ((uint64_t)(sbo >> 4) << 32) | ((uint64_t)swz << 62);
}
template <int N> __device__ __forceinline__ void regfence(float* d) {
#pragma unroll
  for (int i = 0; i < N; i++) asm volatile("" : "+f"(d[i])::"memory");
}

__device__ __forceinline__ void wgmma_rs_32_0(float* d, uint32_t a0, uint32_t a1, uint32_t a2, uint32_t a3, uint64_t db, int sd) {
  asm volatile("{ .reg .pred p; setp.ne.b32 p, %21, 0; wgmma.mma_async.sync.aligned.m64n32k16.f32.bf16.bf16 {%0,%1,%2,%3,%4,%5,%6,%7,%8,%9,%10,%11,%12,%13,%14,%15}, {%16,%17,%18,%19}, %20, p, 1, 1, 0; }"
   : "+f"(d[0]), "+f"(d[1]), "+f"(d[2]), "+f"(d[3]), "+f"(d[4]), "+f"(d[5]), "+f"(d[6]), "+f"(d[7]), "+f"(d[8]), "+f"(d[9]), "+f"(d[10]), "+f"(d[11]), "+f"(d[12]), "+f"(d[13]), "+f"(d[14]), "+f"(d[15]) : "r"(a0), "r"(a1), "r"(a2), "r"(a3), "l"(db), "r"(sd));
}
__device__ __forceinline__ void wgmma_rs_64_1(float* d, uint32_t a0, uint32_t a1, uint32_t a2, uint32_t a3, uint64_t db, int sd) {
  asm volatile("{ .reg .pred p; setp.ne.b32 p, %37, 0; wgmma.mma_async.sync.aligned.m64n64k16.f32.bf16.bf16 {%0,%1,%2,%3,%4,%5,%6,%7,%8,%9,%10,%11,%12,%13,%14,%15,%16,%17,%18,%19,%20,%21,%22,%23,%24,%25,%26,%27,%28,%29,%30,%31}, {%32,%33,%34,%35}, %36, p, 1, 1, 1; }"
   : "+f"(d[0]), "+f"(d[1]), "+f"(d[2]), "+f"(d[3]), "+f"(d[4]), "+f"(d[5]), "+f"(d[6]), "+f"(d[7]), "+f"(d[8]), "+f"(d[9]), "+f"(d[10]), "+f"(d[11]), "+f"(d[12]), "+f"(d[13]), "+f"(d[14]), "+f"(d[15]), "+f"(d[16]), "+f"(d[17]), "+f"(d[18]), "+f"(d[19]), "+f"(d[20]), "+f"(d[21]), "+f"(d[22]), "+f"(d[23]), "+f"(d[24]), "+f"(d[25]), "+f"(d[26]), "+f"(d[27]), "+f"(d[28]), "+f"(d[29]), "+f"(d[30]), "+f"(d[31]) : "r"(a0), "r"(a1), "r"(a2), "r"(a3), "l"(db), "r"(sd));
}
__device__ __forceinline__ void wgmma_rs_192_0(float* d, uint32_t a0, uint32_t a1, uint32_t a2, uint32_t a3, uint64_t db, int sd) {
  asm volatile("{ .reg .pred p; setp.ne.b32 p, %101, 0; wgmma.mma_async.sync.aligned.m64n192k16.f32.bf16.bf16 {%0,%1,%2,%3,%4,%5,%6,%7,%8,%9,%10,%11,%12,%13,%14,%15,%16,%17,%18,%19,%20,%21,%22,%23,%24,%25,%26,%27,%28,%29,%30,%31,%32,%33,%34,%35,%36,%37,%38,%39,%40,%41,%42,%43,%44,%45,%46,%47,%48,%49,%50,%51,%52,%53,%54,%55,%56,%57,%58,%59,%60,%61,%62,%63,%64,%65,%66,%67,%68,%69,%70,%71,%72,%73,%74,%75,%76,%77,%78,%79,%80,%81,%82,%83,%84,%85,%86,%87,%88,%89,%90,%91,%92,%93,%94,%95}, {%96,%97,%98,%99}, %100, p, 1, 1, 0; }"
   : "+f"(d[0]), "+f"(d[1]), "+f"(d[2]), "+f"(d[3]), "+f"(d[4]), "+f"(d[5]), "+f"(d[6]), "+f"(d[7]), "+f"(d[8]), "+f"(d[9]), "+f"(d[10]), "+f"(d[11]), "+f"(d[12]), "+f"(d[13]), "+f"(d[14]), "+f"(d[15]), "+f"(d[16]), "+f"(d[17]), "+f"(d[18]), "+f"(d[19]), "+f"(d[20]), "+f"(d[21]), "+f"(d[22]), "+f"(d[23]), "+f"(d[24]), "+f"(d[25]), "+f"(d[26]), "+f"(d[27]), "+f"(d[28]), "+f"(d[29]), "+f"(d[30]), "+f"(d[31]), "+f"(d[32]), "+f"(d[33]), "+f"(d[34]), "+f"(d[35]), "+f"(d[36]), "+f"(d[37]), "+f"(d[38]), "+f"(d[39]), "+f"(d[40]), "+f"(d[41]), "+f"(d[42]), "+f"(d[43]), "+f"(d[44]), "+f"(d[45]), "+f"(d[46]), "+f"(d[47]), "+f"(d[48]), "+f"(d[49]), "+f"(d[50]), "+f"(d[51]), "+f"(d[52]), "+f"(d[53]), "+f"(d[54]), "+f"(d[55]), "+f"(d[56]), "+f"(d[57]), "+f"(d[58]), "+f"(d[59]), "+f"(d[60]), "+f"(d[61]), "+f"(d[62]), "+f"(d[63]), "+f"(d[64]), "+f"(d[65]), "+f"(d[66]), "+f"(d[67]), "+f"(d[68]), "+f"(d[69]), "+f"(d[70]), "+f"(d[71]), "+f"(d[72]), "+f"(d[73]), "+f"(d[74]), "+f"(d[75]), "+f"(d[76]), "+f"(d[77]), "+f"(d[78]), "+f"(d[79]), "+f"(d[80]), "+f"(d[81]), "+f"(d[82]), "+f"(d[83]), "+f"(d[84]), "+f"(d[85]), "+f"(d[86]), "+f"(d[87]), "+f"(d[88]), "+f"(d[89]), "+f"(d[90]), "+f"(d[91]), "+f"(d[92]), "+f"(d[93]), "+f"(d[94]), "+f"(d[95]) : "r"(a0), "r"(a1), "r"(a2), "r"(a3), "l"(db), "r"(sd));
}
__device__ __forceinline__ void wgmma_ss_8_00(float* d, uint64_t da, uint64_t db, int sd) {
  asm volatile("{ .reg .pred p; setp.ne.b32 p, %6, 0; wgmma.mma_async.sync.aligned.m64n8k16.f32.bf16.bf16 {%0,%1,%2,%3}, %4, %5, p, 1, 1, 0, 0; }"
   : "+f"(d[0]), "+f"(d[1]), "+f"(d[2]), "+f"(d[3]) : "l"(da), "l"(db), "r"(sd));
}
__device__ __forceinline__ void wgmma_ss_8_10(float* d, uint64_t da, uint64_t db, int sd) {
  asm volatile("{ .reg .pred p; setp.ne.b32 p, %6, 0; wgmma.mma_async.sync.aligned.m64n8k16.f32.bf16.bf16 {%0,%1,%2,%3}, %4, %5, p, 1, 1, 1, 0; }"
   : "+f"(d[0]), "+f"(d[1]), "+f"(d[2]), "+f"(d[3]) : "l"(da), "l"(db), "r"(sd));
}
__device__ __forceinline__ void wgmma_ss_64_00(float* d, uint64_t da, uint64_t db, int sd) {
  asm volatile("{ .reg .pred p; setp.ne.b32 p, %34, 0; wgmma.mma_async.sync.aligned.m64n64k16.f32.bf16.bf16 {%0,%1,%2,%3,%4,%5,%6,%7,%8,%9,%10,%11,%12,%13,%14,%15,%16,%17,%18,%19,%20,%21,%22,%23,%24,%25,%26,%27,%28,%29,%30,%31}, %32, %33, p, 1, 1, 0, 0; }"
   : "+f"(d[0]), "+f"(d[1]), "+f"(d[2]), "+f"(d[3]), "+f"(d[4]), "+f"(d[5]), "+f"(d[6]), "+f"(d[7]), "+f"(d[8]), "+f"(d[9]), "+f"(d[10]), "+f"(d[11]), "+f"(d[12]), "+f"(d[13]), "+f"(d[14]), "+f"(d[15]), "+f"(d[16]), "+f"(d[17]), "+f"(d[18]), "+f"(d[19]), "+f"(d[20]), "+f"(d[21]), "+f"(d[22]), "+f"(d[23]), "+f"(d[24]), "+f"(d[25]), "+f"(d[26]), "+f"(d[27]), "+f"(d[28]), "+f"(d[29]), "+f"(d[30]), "+f"(d[31]) : "l"(da), "l"(db), "r"(sd));
}
__device__ __forceinline__ void wgmma_ss_192_01(float* d, uint64_t da, uint64_t db, int sd) {
  asm volatile("{ .reg .pred p; setp.ne.b32 p, %98, 0; wgmma.mma_async.sync.aligned.m64n192k16.f32.bf16.bf16 {%0,%1,%2,%3,%4,%5,%6,%7,%8,%9,%10,%11,%12,%13,%14,%15,%16,%17,%18,%19,%20,%21,%22,%23,%24,%25,%26,%27,%28,%29,%30,%31,%32,%33,%34,%35,%36,%37,%38,%39,%40,%41,%42,%43,%44,%45,%46,%47,%48,%49,%50,%51,%52,%53,%54,%55,%56,%57,%58,%59,%60,%61,%62,%63,%64,%65,%66,%67,%68,%69,%70,%71,%72,%73,%74,%75,%76,%77,%78,%79,%80,%81,%82,%83,%84,%85,%86,%87,%88,%89,%90,%91,%92,%93,%94,%95}, %96, %97, p, 1, 1, 0, 1; }"
   : "+f"(d[0]), "+f"(d[1]), "+f"(d[2]), "+f"(d[3]), "+f"(d[4]), "+f"(d[5]), "+f"(d[6]), "+f"(d[7]), "+f"(d[8]), "+f"(d[9]), "+f"(d[10]), "+f"(d[11]), "+f"(d[12]), "+f"(d[13]), "+f"(d[14]), "+f"(d[15]), "+f"(d[16]), "+f"(d[17]), "+f"(d[18]), "+f"(d[19]), "+f"(d[20]), "+f"(d[21]), "+f"(d[22]), "+f"(d[23]), "+f"(d[24]), "+f"(d[25]), "+f"(d[26]), "+f"(d[27]), "+f"(d[28]), "+f"(d[29]), "+f"(d[30]), "+f"(d[31]), "+f"(d[32]), "+f"(d[33]), "+f"(d[34]), "+f"(d[35]), "+f"(d[36]), "+f"(d[37]), "+f"(d[38]), "+f"(d[39]), "+f"(d[40]), "+f"(d[41]), "+f"(d[42]), "+f"(d[43]), "+f"(d[44]), "+f"(d[45]), "+f"(d[46]), "+f"(d[47]), "+f"(d[48]), "+f"(d[49]), "+f"(d[50]), "+f"(d[51]), "+f"(d[52]), "+f"(d[53]), "+f"(d[54]), "+f"(d[55]), "+f"(d[56]), "+f"(d[57]), "+f"(d[58]), "+f"(d[59]), "+f"(d[60]), "+f"(d[61]), "+f"(d[62]), "+f"(d[63]), "+f"(d[64]), "+f"(d[65]), "+f"(d[66]), "+f"(d[67]), "+f"(d[68]), "+f"(d[69]), "+f"(d[70]), "+f"(d[71]), "+f"(d[72]), "+f"(d[73]), "+f"(d[74]), "+f"(d[75]), "+f"(d[76]), "+f"(d[77]), "+f"(d[78]), "+f"(d[79]), "+f"(d[80]), "+f"(d[81]), "+f"(d[82]), "+f"(d[83]), "+f"(d[84]), "+f"(d[85]), "+f"(d[86]), "+f"(d[87]), "+f"(d[88]), "+f"(d[89]), "+f"(d[90]), "+f"(d[91]), "+f"(d[92]), "+f"(d[93]), "+f"(d[94]), "+f"(d[95]) : "l"(da), "l"(db), "r"(sd));
}

#define HINT(x) x

__global__ void __cluster_dims__(2, 1, 1) __launch_bounds__(384, 1) fused_kernel(const uint8_t* __restrict__ pk, uint64_t dv,
    uint64_t dsh, const __nv_bfloat16* __restrict__ pssm, const __nv_bfloat16* __restrict__ pD, uint8_t* ps, const __grid_constant__ Params p) {
  extern __shared__ __align__(1024) uint8_t smem_raw[];
  const uint32_t t_start = clk();
  const uint32_t sb = smem_u32(smem_raw);
  const uint32_t bars = sb + O_BAR;
  const int tid = threadIdx.x, lane = tid & 31;
  const int warp = __shfl_sync(0xffffffffu, tid >> 5, 0);
  {
    const int b = blockIdx.x, w = (tid >> 5) & 3, r = lane >> 2, c = lane & 3, g = tid >> 7, t = (b >> 2) * 64 + r * 8;
    const uint32_t x = r * 64 + ((c ^ (r >> 1)) << 4), o = t * (D_ * 2) + (b & 3) * 64 + c * 16, mv = tid << 24 >> 31, ms = tid >= 352 ? -1 : 0;
    auto pick = [&](uint64_t d, uint32_t m) { return (uint64_t)((uint32_t)(d >> 32) & m) << 32 | (uint32_t)d & m; };
    const uint32_t d = sb + kreg(0) + x + w * 1024 + (2 >> g) * voff(0);
    const uint8_t* const a = pk + pick(dv, mv) + (o + w * (D_ * 4));
    cpa16(d, a, g ? 16 : 0);
    cpa16(d + 512, a + D_ * 2, g ? 16 : 0);
    cpa16(settag(d - w * 512, mv, sb + O_EP - 4096) + 4096,
          pk + (pick(dsh, ms) | pick((uint8_t*)(g_sync + Y_EP + b * 32) - pk, mv)) + (settag(max((int)o + (w - 3) * (D_ * 2), 0), ms, (b & 3) * 256 + x) & ~mv), g && (t | mv | ms) ? 16 : 0);
    if (tid == 256) TSTAMP(74);
  }
  const int b = blockIdx.x, kh = b & 1;
  const int part = b / 20, grp = part < NE0 ? 0 : part < NE ? 1 : 2;
  auto loadwm = [&]() {
    const int x = b % 20, col = part < 5 ? (x >> 2) * D_ + part * 128 + (x & 3) * 32 : 5 * D_ + x * 32;
    mbar_expect(bars + 8 * B_WM, 40960);
    tma3d(sb + O_WM, &p.m_wm, col, 0, 0, bars + 8 * B_WM);
  };
  auto BAR = [&](int i) { return bars + 8 * i; };
#define ROLE const int rb = b >> 3, fs = b & 7, vr = min(rb, 14) / 3, vt = min(rb, 14) % 3; \
  const uint32_t ord = VR == 3 ? (vr == 4 ? 0x34210 : 0x43210) : vr == 3 ? 0x42310 : vr == 4 ? 0x32410 : 0x43210; uint8_t* const misc = ps + rb * 4096; \
  (void)fs; (void)vt; (void)ord; (void)misc
  if (tid == 0) TSTAMP(63);
#define EPOCHU const uint32_t ep = __shfl_sync(0xffffffffu, lds32(sb + O_EP), 0) + 1

  if (warp < 4) {
    if (tid == 32) TSTAMP(118);
    asm volatile("setmaxnreg.dec.sync.aligned.u32 40;");
    if (tid == 32) TSTAMP(120);
    asm volatile("barrier.cluster.arrive.relaxed.aligned;" ::: "memory");
    const int hw = warp - 2;
    auto kvcheck = [&](int j, uint32_t ep) {
      const uint32_t a = sb + bnd(j) + U_KV + lane * 32;
      uint32_t x[4];
      mbar_wait(BAR(B_KV + j), 0);
#pragma unroll
      for (int i = 0; i < 4; i++) x[i] = lds32(a + i * 1024 + (lane & 28)) ^ ep;
      if (__any_sync(0xffffffffu, (x[0] | x[1] | x[2] | x[3]) & 1)) {
#pragma unroll 1
        for (int i = 0; i < 4096; i += 1024) refetch_all(ps + (page(G_KV + j, b) + lane * 32 + i), lane & 28, a + i, ep);
      }
      __syncwarp();
      if (lane == 0) mbar_arrive(BAR(B_OK + j));
    };
    if (warp == 0) {
      bar_sync(1, 384);
      EPOCHU;
      if (lane == 0) TSTAMP(0);
      __syncwarp();
      ROLE;
      {
        const bool pol = lane < 5 || YW && lane == 7;
        const uint32_t* f = g_sync + (lane < 5 ? Y_KV + (lane * 4 + (b >> 5)) * 32 : Y_Y);
        const uint32_t tg = ep * (lane < 5 ? 32 : 128);
        const uint32_t tw = lane != 5 ? T_W0 : b * D_WM + T_WM2 - 20 * NE * D_WM;
        uint32_t pend = (!WI && b < 120 && grp == 2 ? 127 : 95) - (1 << PK) + 1 + YW * 128;
        int it = 0;
        uint32_t ck = 0;
        do {
          uint32_t v = tg;
          HINT(if (pol && (pend & 159)) v = ldr(f));
          if (KP) for (; ck; ck &= ck - 1) kvcheck(__ffs(ck) - 1, ep);
          uint32_t m = __ballot_sync(0xffffffffu, (pol ? (int)(v - tg) >= 0 : clk() - t_start >= tw) || ++it > 100000) & pend;
          pend &= ~m;
          ck = m & EV0;
          for (; m; m &= m - 1) {
            const int j = __ffs(m) - 1;
            if (elect()) {
              if (j < 5) {
                TSTAMP(2 + j);
                mbar_expect(BAR(B_KV + j), 4096);
                bulk_ld(sb + bnd(j) + U_KV, ps + page(G_KV + j, b), 4096, BAR(B_KV + j));
              } else if (!WI && j == 5) {
                loadwm();
                TSTAMP(109);
              } else if (YW && j == 7) {
                TSTAMP(47);
                bulk_ld(sb + O_Y, ps + page(G_Y, b), 4096, BAR(B_PR));
              } else {
                bulk_pf((kh ? p.wu : p.wg) + (b >> 1) * 2 * F_, 6144);
                TSTAMP(108);
              }
            }
          }
          if (!KP) for (; ck; ck &= ck - 1) kvcheck(__ffs(ck) - 1, ep);
        } while (pend | ck);
      }
      {
        const int rl = (ord >> (min(lane, 19) & 28)) & 7;
        const uint32_t* const cnt = (const uint32_t*)(misc + M_X) + (XG & 2 ? rl * 4 + (lane & 3) : rl * 2 + ((min(lane, 19) >> 1) & 1));
        const uint32_t xt = ep * (XG & 2 ? 8 : 16);
        sts32(sb + O_XT + lane * 4, tile(rb, rl * 4 + (lane & 3)));
        __syncwarp();
        uint32_t known = 0;
        int slot = 4;
#pragma unroll 1
        for (int i = -AH; i < 20; i++) {
          const int s = i < 0 ? i + AH : i, rd = (ord >> (s & 28)) & 7;
          const uint32_t dst = sb + slot * SLOT, full = BAR(B_FULL + slot);
          const uint8_t* const xs = ps + (tile(rb, rd * 4 + (s & 3)) + kh * 16384);
          auto loadx = [&]() {
            asm volatile("{ .reg .pred p; elect.sync _|p, 0xffffffff;\n @p cp.async.bulk.shared::cluster.global.mbarrier::complete_tx::bytes.multicast::cluster [%0], [%1], 4096, [%2], %3; }"
                         ::"r"(dst + 24576 + kh * 4096), "l"(xs), "r"(full), "h"((uint16_t)3) : "memory");
          };
          auto loadw = [&]() {
            mbar_wait(full + 8 * (B_EMPTY - B_FULL), (0xc0fc0 >> s) & 1);
            asm volatile("{ .reg .pred p; elect.sync _|p, 0xffffffff;\n @p mbarrier.arrive.expect_tx.shared::cta.b64 _, [%2], 32768;\n"
                         " @p cp.async.bulk.tensor.4d.shared::cluster.global.mbarrier::complete_tx::bytes [%0], [%1, {0, %3, %4, 0}], [%2]; }"
                         ::"r"(dst), "l"(&p.m_w1), "r"(full), "r"(rd * 128 + (s & 3) * 32), "r"(fs * 3) : "memory");
          };
          uint32_t v = xt - 1;
          HINT(if (i >= 0 && (~known >> s) & PD) v = ldr(cnt));
          if (i >= AH && (known >> s) & 1) {
            loadw();
            loadx();
          } else {
            if ((uint32_t)i >= AH) loadw();
            if (lane == 0) TS3(2, s);
            if (i >= 0) {
              HINT(if (!((known >> s) & 1)) poll_lane(v, cnt, xt, s));
              loadx();
            }
          }
          if (i >= 0 && lane == 0) TS3(3, s);
          if (((PFW | PF2) << AH >> (i + AH)) & 1) {
            const int k = __popc((PFW | PF2) << (31 - s));
            if (elect()) bulk_pf(k < 5 ? (kh ? p.wu : p.wg) + (k * 128 + (b >> 1) * 2) * F_ : p.w2 + b * 7680 + (k - 5) * 2560, k < 5 ? 6144 : 5120);
          }
          if (lane == 0 && i == -1) TSTAMP(10);
          if (lane == 0 && i == 0) TSTAMP(19);
          if (lane == 0 && i == 16) TSTAMP(1);
          slot = i == -1 ? 4 : slot == 5 ? 0 : slot + 1;
          known |= __ballot_sync(0xffffffffu, (int)(v - xt) >= 0);
        }
      }
      __syncwarp();
      asm volatile("barrier.cluster.wait.aligned;" ::: "memory");
      if ((sb & 0xffffff) != SD) __trap();
#pragma unroll 1
      for (int s = 0; s < 10; s++) {
        const int e = s < 7 ? s : s - 7;
        const uint32_t d = sb + w2entry(e), st = e == 6 ? SLOT : 8192;
        const int k0 = (fs ^ (s < 4 ? s >> 1 : s & 1)) * 192, c0 = ocol(b, s < 4 ? s & 1 : s >> 1);
        mbar_wait(BAR(s >= 7 ? B_W2E + e : B_EMPTY + min(s, 5)), s < 4);
        if (elect()) {
          mbar_expect(BAR(B_W2F + e), 24576);
#pragma unroll
          for (int i = 0; i < 3; i++) tma2d(d + i * st, &p.m_w2, c0, k0 + i * 64, BAR(B_W2F + e));
        }
      }
    } else {
      uint32_t dd = 0;
      if (warp == 1) {
        mbar_init(BAR(B_SSM), 1);
        unrolled<NLD>([&](auto I) {
          constexpr uint32_t e = nth_load(I.v), n = e & 15, kind = (e >> 4) & 15;
          while (clk() - t_start < (e >> 8) + (n == 5 ? (b >> 2) * D_Q : 0)) {}
          if (elect()) {
            if constexpr (kind == 0) {
              const uint32_t d = sb + kreg(n), bar = BAR(B_K + n);
              const int ch = n * 128 + (b & 3) * 32, tg = (b >> 2) * 8;
              mbar_expect(bar, 9984);
              tma3d(d, &p.m_k, ch, tg, 0, bar);
              tma3d(d + voff(n), &p.m_v, ch, tg, 0, bar);
              tma3d(d + 4096, &p.m_kh, ch, tg - 1, 5, bar);
              bulk_ld(d + 5632, pk + dsh + ch * 8, 256, bar);
            } else if constexpr (kind == 2) {
              if (grp == n) loadwm();
            } else if constexpr (kind == 1 && n < 5) {
              mbar_expect(BAR(B_SSM + n), 4096);
              bulk_ld(sb + bnd(n) + U_RAW, pssm + (size_t)(n * 128 + b) * S_, 4096, BAR(B_SSM + n));
            } else {
              mbar_expect(BAR(B_QIN), 20480);
              tma3d(sb + O_REG, &p.m_q, 0, b * 16, 0, BAR(B_QIN));
            }
            TSTAMP(96 + I.v);
          }
          if constexpr (I.v == 0) {
            static_assert(e % 256 == 16, "first load");
#pragma unroll
            for (int i = B_SSM + 1; i < B_PL + (XQ ? 10 : 5); i++) mbar_init(BAR(i), i < B_PL || i > B_PL + 5 ? 1 : i < B_PL + 5 ? 2 : LJ < 5 ? 5 : 3);
            bar_arrive(1, 384);
            if (lane == 0) TSTAMP(112);
            if (EV1) asm volatile("ld.global.nc.u16 %0, [%1];" : "=r"(dd) : "l"(pD + min(lane, 4) * 128 + b) : "memory");
          }
        });
        if ((WI == 3 || WI == 5) && b < (WI == 5 ? B5 : 120) && grp == 2) {
          while (clk() - t_start < T_W3 + (b - 20 * NE) * D_W3) {}
          if (elect()) { loadwm(); TSTAMP(109); }
        }
        mbar_wait(BAR(B_PL), 0);
        if (lane < 5) asm volatile("mbarrier.expect_tx.relaxed.cta.shared::cta.b64 [%0], 4096;" ::"r"(BAR(B_PR + lane)) : "memory");
      } else {
        uint32_t x[10];
        asm volatile("ld.global.nc.u16 %0, [%1];" : "=r"(dd) : "l"(pD + min(lane, 4) * 128 + b) : "memory");
#pragma unroll
        for (int i = 0; i < 10; i++) x[i] = ldr((const uint32_t*)p.c + lane + i * 32);
#pragma unroll
        for (int j = 0; j < 5; j++) {
          if (hw && lane < 19) sts128(sb + bnd(j) + (lane < 17 ? U_KV + 4096 + lane * 16 : lane == 17 ? U_RAW - 16 : U_ODD - 16), 0, 0, 0, 0);
        }
        if (tid == 96) TSTAMP(122);
        if (elect()) {
#pragma unroll
          for (int i = 0; i < 4; i++) asm volatile("prefetch.tensormap [%0];" ::"l"(&p.m_k + hw * 4 + i) : "memory");
        }
        bar_sync(1, 384);
        if (hw) {
#pragma unroll
          for (int i = 0; i < 10; i++)
            sts32(sb + O_SILU + i % 5 * 256 + (lane >> 2) * 32 + i / 5 * 16 + (lane & 3) * 4, pack2(__fdividef(blo(x[i]), 1.f + __expf(-blo(x[i]))), __fdividef(bhi(x[i]), 1.f + __expf(-bhi(x[i])))));
          if (LT && lane < 4) sts32(sb + O_LN + lane * 4, 0x3F803F80u);
          fence_async_smem();
          __syncwarp();
          if (lane < NH) mbar_arrive(BAR(B_PL + lane));
        }
      }
      uint32_t xl = (lane ^ lane >> 3) * 16;
      auto rowsum = [&](int h, uint8_t* og) {
        float z[4] = {0.f, 0.f, 0.f, 0.f};
        auto acc = [&](uint32_t v) { const float f = blo(v), g = bhi(v); z[0] += f; z[1] = fmaf(f, f, z[1]); z[2] += g; z[3] = fmaf(g, g, z[3]); };
        uint32_t a = sb + O_REG + h * 512 + xl;
        uint4 x = lds128(a), y = lds128(a + 1024);
#pragma unroll 1
        for (int i = 0; i < 10; i++) {
          a += 2048;
          const uint4 u = lds128(a), v = lds128(a + 1024);
          if (og) { stg128(og, x.x, x.y, x.z, x.w); stg128(og + 64, y.x, y.y, y.z, y.w); og += 128; }
          acc(x.x); acc(x.y); acc(x.z); acc(x.w); acc(y.x); acc(y.y); acc(y.z); acc(y.w);
          x = u; y = v;
        }
        z[0] += z[2]; z[1] += z[3];
#pragma unroll
        for (int i = 1; i < 3; i++) { z[0] += __shfl_xor_sync(0xffffffffu, z[0], i); z[1] += __shfl_xor_sync(0xffffffffu, z[1], i); }
        z[0] *= 1.f / D_;
        return make_float2(z[0], fmaxf(z[1] * (1.f / D_) - z[0] * z[0], 0.f) + 1e-5f);
      };
      {
        EPOCHU;
#pragma unroll 1
        for (uint64_t ev = warp == 1 ? EV1 : hw ? EV3 : EV2; ev; ev >>= 8) {
          const int j = ev & 7;
          if (EV0 == 31 && LJ < 5 || ev & 16) {
            const float dj = blo(__shfl_sync(0xffffffffu, dd, j));
            mbar_wait(BAR(B_SSM + j), 0);
            if (lane == 0 && j == 0) TSTAMP(77);
#pragma unroll 1
            for (int h = NH < 5 && ev & 8 ? hw * 2048 : 0; h < 4096; h += NH < 5 ? 2048 + (ev & 8) * 256 : 2048) {
              const uint32_t ra = sb + bnd(j) + U_RAW + h + lane * 16;
              uint4 w[4];
              uint32_t pv[4];
#pragma unroll
              for (int i = 0; i < 4; i++) { w[i] = lds128(ra + i * 512); pv[i] = lds32(ra + i * 512 - 4); }
              if (!(h | lane)) { w[0].x = prmt(pack2(blo(w[0].x) + dj, 0.f), w[0].x, 0x7610); sts32(ra, w[0].x); }
#pragma unroll
              for (int i = 0; i < 4; i++) sts128(ra + (U_ODD - U_RAW) + i * 512, prmt(pv[i], w[i].x, 0x5432), prmt(w[i].x, w[i].y, 0x5432), prmt(w[i].y, w[i].z, 0x5432), prmt(w[i].z, w[i].w, 0x5432));
            }
            __syncwarp();
            if (lane == 0) { mbar_arrive(BAR(B_PL + j)); TSTAMP(32 + j); }
          } else if (EV0 != 31 && ev & 32) {
            kvcheck(j, ep);
          } else if (LJ > 4) {
            mbar_wait(BAR(B_QIN), 0);
            if (lane == 0 && j == 0) TSTAMP(9);
            if (WI == 1 && j && b < 120 && grp == 2 && elect()) { loadwm(); TSTAMP(109); }
            const float2 z = rowsum(j, nullptr);
            const float rs = rbf(rsqrtf(z.y));
            if (!(xl & 48)) sts32(sb + O_LN + j * 32 + (xl >> 4), pack2(rs, -z.x * rs));
            __syncwarp();
            if (lane < (XQ ? 1 : 2)) mbar_arrive(BAR(XQ ? B_PR : B_LN));
            if (lane == 0) TSTAMP(59 + 2 * j);
          }
        }
      }
      if (warp == 1) {
        EPOCHU;
        ROLE;
        uint32_t known = 0;
        const uint32_t* const cnt = g_sync + Y_Y + min(lane, 10) * 32;
        const uint32_t target = ep * (lane < 5 ? 128 : 40);
        int ny = YW, nm = 0;
        if (T_M) while (clk() - t_start < T_M) {}
        if (WI == 4 && b < 120 && grp == 2) {
          while (clk() - t_start < T_W3 + (b - 20 * NE) * D_W3) {}
          if (elect()) { loadwm(); TSTAMP(109); }
        }
#pragma unroll 1
        for (int it = 0; ny < 5 || nm < 6; it++) {
          const int j = nm < 5 ? (ord >> (nm * 4)) & 7 : nm;
          if (lane == 0 && it == 0) TSTAMP(124);
          uint32_t u = target;
          HINT(if (DM ? ~known & 31 : known != 2047) u = ldr(cnt));
          auto ycopy = [&]() {
          known |= __ballot_sync(0xffffffffu, (int)(u - target) >= 0 || it > 100000) & 2047;
          if (ny < 5) {
            const int y = (ord >> (ny * 4)) & 7;
            if (nm > 5 && ny >= 2) mbar_wait(BAR(B_YE + (ny & 1)), ny >> 2);
            if (((known >> y) & 1) && (ny < 2 || mbar_test(BAR(B_YE + (ny & 1)), ny >> 2) || it > 200000)) {
              if (elect()) {
                if (ny < 2) TSTAMP(47 + ny);
                bulk_ld(sb + (ny & 1 ? O_BP : O_Y), ps + page(G_Y + y, b), 4096, BAR(B_PR + ny));
              }
              ny++;
            }
          }
          };
          const bool gm = (DM ? nm < 6 : (known >> (5 + j)) & 1) && (!LT || nm < 5 || ny > 2);
          uint4 v[5];
          if (YF) {
#pragma unroll
            for (int k = 0; k < 5; k++)
              asm volatile("{ .reg .pred p; setp.ne.u32 p, %5, 0; @p ld.relaxed.gpu.global.v4.u32 {%0,%1,%2,%3}, [%4]; }"
                           : "=r"(v[k].x), "=r"(v[k].y), "=r"(v[k].z), "=r"(v[k].w) : "l"(g_mod + j * D_ + k * 128 + lane * 4), "r"((uint32_t)gm) : "memory");
            ycopy();
          }
          if (gm) {
            uint32_t bad = 0, lo[5], hi[5];
#pragma unroll
            for (int k = 0; k < 5; k++) if (!YF) v[k] = ldr4(g_mod + j * D_ + k * 128 + lane * 4);
#pragma unroll
            for (int k = 0; k < 5; k++) {
              bad |= (v[k].x ^ ep) | (v[k].y ^ ep) | (v[k].z ^ ep) | (v[k].w ^ ep);
              lo[k] = pack2(__uint_as_float(v[k].x), __uint_as_float(v[k].y));
              hi[k] = pack2(__uint_as_float(v[k].z), __uint_as_float(v[k].w));
            }
            if (lane == 0 && it == 0 && bad != 12345) TSTAMP(125);
            if (!__any_sync(0xffffffffu, bad & 3) || it > 200000) {
              if (nm < 5) {
                const uint32_t ma = sb + O_MA + nm * 768 + lane * 8, one = 0x3F803F80u, c0 = hadd2(lo[4], one), c1 = hadd2(hi[4], one);
                sts64(ma, hmul2(lo[2], hadd2(lo[1], one)), hmul2(hi[2], hadd2(hi[1], one)));
                sts64(ma + 256, hmul2(lo[2], lo[0]), hmul2(hi[2], hi[0]));
                sts64(ma + 512, c0, c1);
                __syncwarp();
                if (lane == 0) { mbar_arrive(BAR(B_PR + nm)); if (nm < 3) TSTAMP(nm < 2 ? 7 + nm : 79); }
                if (j == vr) {
                  sts64(sb + O_CS + (lane >> 1) * 32 + (lane & 1) * 8, c0, c1);
                  sts64(sb + O_CS + (lane >> 1) * 32 + (lane & 1) * 8 + 16, lo[3], hi[3]);
                  fence_async_smem();
                  __syncwarp();
                  if (lane == 0) mbar_arrive(BAR(B_CS));
                }
              } else {
#pragma unroll
                for (int k = 0; k < 5; k++) if ((k * 32 + lane >= 80) == kh) sts128(sb + O_GB + k * 512 + lane * 16 - kh * 1280, lo[k] << 16, lo[k] & 0xffff0000u, hi[k] << 16, hi[k] & 0xffff0000u);
              }
              nm++;
            }
          }
          if (!YF) ycopy();
          if (WI == 5 && it == 0 && (uint32_t)(b - B5) < 120 - B5 && elect()) { loadwm(); TSTAMP(109); }
        }
        __syncwarp();
        if (lane < 6) mbar_expect(BAR(B_HF + lane), 8192);
        if (lane == 0) { sts128(sb + O_BP + 6144, 0, 0, 0, 0); mbar_arrive(BAR(B_VV)); }
        mbar_wait(BAR(B_YE + 1), 1);
      } else {
        uint32_t ya = lane * 32 + (lane & 4) * 4, pl = (lane & 3) * 16;
        const uint32_t e0 = lds32(sb + O_EP);
        keep(ya); keep(xl); keep(pl);
        mbar_wait(BAR(XQ ? B_PR : B_LN), 0);
        if (!xl && hw) TSTAMP(114);
        ROLE;
        const uint32_t tt = (e0 & 1) - 1;
        uint32_t ln[2];
        if (LT) {
          const float4 v = lds128f(sb + O_GB + lane * 16);
          float z[4] = {v.x, v.y, v.z, v.w};
#pragma unroll
          for (int i = 0; i < 8; i++) z[i & 3] += __shfl_xor_sync(0xffffffffu, z[i & 3], 1 + (i >> 2));
#pragma unroll
          for (int i = 0; i < 2; i++) {
            const float m = z[i] * (1.f / D_), rs = rbf(rsqrtf(fmaxf(z[2 + i] * (1.f / D_) - m * m, 0.f) + 1e-5f));
            ln[i] = pack2(rs, -m * rs);
          }
        } else { ln[0] = lds32(sb + O_LN + (lane & 28)); ln[1] = lds32(sb + O_LN + 32 + (lane & 28)); }
#pragma unroll 1
        for (int it = 0; it != 10;) {
          const int j = (ord >> (it * 2 & 28)) & 7, odd = (it >> 1) & 1, g = XG & 1 ? (it & 1) + 2 - 2 * hw : (it & 1) * 2 + hw;
          const uint32_t pm = sb + O_MA + (it & 14) * 384 + g * 64, yo = sb + (odd ? O_BP : O_Y) + g * 1024, qo = sb + O_REG + (j * 4 + g) * 1024;
          uint32_t y[8];
          if (XQ ? 0x154 >> it & 1 : !(it & 1)) mbar_wait(BAR(B_PR + ((it >> 1) & 7)), 0);
          if (!(xl | hw) && it < 6 && !(it & 1)) TSTAMP(it == 0 ? 49 : it == 2 ? 58 : 80);
          ldsm4t(addu(ya, yo), y[0], y[1], y[2], y[3]);
          ldsm4t(addu(ya, yo) ^ 16, y[4], y[5], y[6], y[7]);
          const uint4 q0 = lds128(addu(xl, qo)), a4 = lds128(addu(pl, pm)), b4 = lds128(addu(pl, pm) + 256), q1 = lds128(addu(xl, qo) + 512), c4 = lds128(addu(pl, pm) + 512);
          if (XQ) edge(it);
          if ((__ballot_sync(0xffffffffu, ((y[0] ^ tt) | (y[1] ^ tt) | (y[2] ^ tt) | (y[3] ^ tt) | (y[4] ^ tt) | (y[5] ^ tt) | (y[6] ^ tt) | (y[7] ^ tt)) & 0x00010001u) & 15) && it < 16) {
#pragma unroll 1
            for (int hf = 0; hf < 32; hf += 16) refetch16(ps + (page(G_Y + j, b) + g * 1024 + (ya ^ hf)), (ya ^ hf) + yo, tt);
            __syncwarp();
            it += 16;
            continue;
          }
          const uint32_t ma[4] = {a4.x, a4.y, a4.z, a4.w}, mb[4] = {b4.x, b4.y, b4.z, b4.w};
          uint32_t q[8] = {q0.x, q0.y, q0.z, q0.w, q1.x, q1.y, q1.z, q1.w};
#pragma unroll
          for (int i = 0; i < 8; i++) q[i] = hfma2(hfma2(hfma2lh(q[i], ln[i >> 2]), ma[i & 3], mb[i & 3]), y[i], q[i]);
          uint8_t* const xg = ps + addu(xl, tile(rb, j * 4 + g) + (b & 4) * 4096 + (b & 3) * 1024);
          const uint32_t mc[4] = {c4.x, c4.y, c4.z, c4.w};
          uint8_t* const xh = misc + (M_X + (XG & 2 ? j * 16 + g * 4 : j * 8 + (g & 2) * 2) + (xl >> 9));
          const uint32_t one = 1 + (xl >> 9);
#pragma unroll
          for (int i = 0; i < 8; i++) { y[i] = hmul2(q[i], mc[i & 3]); if (XQ == 2) q[i] |= it >> 5; }
          y[0] = tag0(y[0], tt); y[4] = tag0(y[4], tt);
          edge(it);
          stg128(xg, y[0], y[1], y[2], y[3]);
          stg128(xg + 512, y[4], y[5], y[6], y[7]);
          asm volatile("{ .reg .pred p; elect.sync _|p, 0xffffffff; @p red.relaxed.gpu.global.add.u32 [%0], %2; @p mbarrier.arrive.shared::cta.b64 _, [%1]; }"
                       ::"l"(xh), "r"(BAR(B_YE + odd)), "r"(one) : "memory");
          sts128(addu(xl, qo), q[0], q[1], q[2], q[3]);
          sts128(addu(xl, qo) + 512, q[4], q[5], q[6], q[7]);
          if (!(xl | hw) && (it & 1)) TSTAMP(12 + ((it & 15) >> 1));
          if (!xl && hw == (XG & 1) && it < 2) TSTAMP(113 + it * 3);
          it = (it & 15) + 1;
        }
        const int lane = ya >> 5, t = hw * 32 + lane;
        EPOCHU;
        bar_sync(4, 64);
        const float2 z = rowsum(hw, p.out + ((t >> 2) * 1280 + pl + b * 20480));
        const uint32_t pa = pack2(-z.x, sqrtf(z.y));
        if (!(xl & 48))
          asm volatile("st.relaxed.gpu.global.v2.u32 [%0], {%1,%2};" ::"l"(misc + M_ST + fs * 128 + hw * 64 + (xl >> 3)), "r"(pa), "r"(tagf(__fdividef(1.f, bhi(pa) * bhi(pa)), ep)) : "memory");
        uint4 v;
        int it = 0;
        do v = ldr4((const uint32_t*)(misc + M_ST + t * 16)); while ((((v.y ^ ep) | (v.w ^ ep)) & 3) && ++it < 100000);
        sts128(sb + O_ST + t * 16, v.x, v.y, v.z, v.w);
        __syncwarp();
        if (lane == 0) mbar_arrive(BAR(B_ST + hw));
        if (t == 0) TSTAMP(52);
      }
      ROLE;
      EPOCHU;
      int lane;
      asm volatile("mov.u32 %0, %%laneid;" : "=r"(lane));
      {
        HINT(poll_ge(g_sync + Y_VV + fs * 32, ep * 128));
        uint32_t v[20], bad;
        int it = 0;
        const uint32_t* g = g_vv + fs * 1920 + (hw + 1) * 128 + lane;
        do {
          bad = 0;
#pragma unroll
          for (int k = 0; k < 20; k++) v[k] = ldr(g + ((k % 5) * 384 + (k / 5) * 32));
#pragma unroll
          for (int k = 0; k < 20; k++) bad |= v[k] ^ ep;
        } while (__any_sync(0xffffffffu, bad & 1) && ++it < 100000);
#pragma unroll
        for (int k = 0; k < 4; k++) sts128(sb + O_BP + ((hw + 1) * 128 + k * 32 + lane) * 16, v[5 * k], v[5 * k + 1], v[5 * k + 2], hadd2(v[5 * k + 3], v[5 * k + 4]));
        fence_async_smem();
        __syncwarp();
      }
      if (lane == 0) mbar_arrive(BAR(B_VV));
      if (warp == 1) {
        if (lane == 0) TSTAMP(37);
        uint32_t v;
        int it = 0;
        do asm volatile("ld.acquire.gpu.global.u32 %0, [%1];" : "=r"(v) : "l"(misc + M_O) : "memory"); while ((int)(v - ep * 16) < 0 && ++it < 100000);
        asm volatile("fence.proxy.async.global;" ::: "memory");
        if (lane == 0) { mbar_arrive(BAR(B_X1)); TSTAMP(30); }
      } else {
        asm volatile("fence.acq_rel.gpu;" ::: "memory");
        __syncwarp();
        if (lane == 0) hint_add((uint32_t*)(misc + M_O));
      }
      __syncwarp();
      asm volatile("barrier.cluster.wait.aligned;" ::: "memory");
    }
  } else {
    const int isE = warp >= 8 ? 1 : 0;
    const int w = warp & 3, r = lane >> 2, c = lane & 3;
    const bool lead = (tid & 127) == 0;
    const int tb = b >> 2;
    if (tid == 256) TSTAMP(75);
    asm volatile("setmaxnreg.inc.sync.aligned.u32 232;");
    const uint32_t sb = __shfl_sync(0xffffffffu, smem_u32(smem_raw), 0);
    auto BAR = [&](int i) { return sb + O_BAR + 8 * i; };
    uint32_t ep;
#pragma unroll
    for (int i = 0; i < 7; i++) mbar_init(BAR(warp - 4 + 8 * i), i == 0 ? 2 << isE : i == 1 ? 4 : 1);
    asm volatile("fence.mbarrier_init.release.cluster;" ::: "memory");
    asm volatile("barrier.cluster.arrive.relaxed.aligned;" ::: "memory");
    if (lead) TSTAMP(76);
    auto first = [&]() { asm volatile("cp.async.wait_all;" ::: "memory"); bar_sync(1, 384); };
    uint32_t A[64];
    auto release = [&](uint32_t m) { if (w == 3 && lane < 12 && ((m >> (lane >> 1)) & 1)) mbar_arrive_cl(mapa(BAR(B_EMPTY + (lane >> 1)), lane & 1)); __syncwarp(); };
    auto aload = [&](int j) {
      const uint32_t sa = sb + bnd(j) + ((r & 1) ? U_RAW : U_ODD) + 4 * (8 * w + (r >> 1) - 3 + c);
#pragma unroll
      for (int g = 0; g < 16; g++) { A[4 * g] = lds32(sa + g * 256); A[4 * g + 1] = lds32(sa + g * 256 + 128); A[4 * g + 2] = lds32(sa + g * 256 + 16); A[4 * g + 3] = lds32(sa + g * 256 + 144); }
      if (lead) TSTAMP(89 + j);
    };
    auto gemv = [&]() {
      float d[16];
      const uint64_t db = mkdesc(SD + O_SILU, 32, 128, 0), da = mkdesc(SD + O_WM, 20480, 512, 2);
      mbar_wait(BAR(B_PL), 0);
      mbar_wait(BAR(B_WM), 0);
      if (lead) TSTAMP(81 + grp);
      if (EM == 2 && w < 2 && lane == 0) hint_add(g_sync + Y_MOD + part * 32);
      wg_fence();
#pragma unroll
      for (int kk = 0; kk < 20; kk++) wgmma_ss_8_10(d + (kk & 3) * 4, da + kk * 64, db + kk * 4, kk >> 2);
      wg_commit();
      wg_wait<0>();
      regfence<16>(d);
#pragma unroll
      for (int i = 0; i < 4; i++) d[i] = (d[i] + d[4 + i]) + (d[8 + i] + d[12 + i]);
      if (EM == 1 && w < 2 && lane == 0) hint_add(g_sync + Y_MOD + part * 32);
      const uint32_t xa = sb + O_SILU + 2048 + (w & 1) * 64 + r * 8;
      if (c == 0 && w >= 2) sts64(xa, __float_as_uint(d[1]), __float_as_uint(d[3]));
      bar_sync(5 + isE, 128);
      if (w < 2) {
        const float2 e = lds64f(xa);
        if (c == 0) { str(g_mod + b * 32 + w * 16 + r, tagf(d[0] + e.x, ep)); str(g_mod + b * 32 + w * 16 + r + 8, tagf(d[2] + e.y, ep)); }
        __syncwarp();
        if (!DM && !EM && lane == 0) hint_add(g_sync + Y_MOD + part * 32);
      }
      if (lead) TSTAMP(grp == 2 ? 60 : 20 + grp);
    };
    float qq[36];
    auto lnt0 = [&]() {
      const uint64_t dq = mkdesc(SD + O_REG, 0, 512, 2);
      mbar_wait(BAR(B_QIN), 0);
      if (lead) TSTAMP(9);
      wg_fence();
#pragma unroll
      for (int i = 0; i < 10; i++) {
        wgmma_ss_64_00(qq, dq + (i >> 1) * 256 + (i & 1) * 2, dq + (i >> 1) * 256 + (i & 1) * 2, i | LB == 4);
        wgmma_ss_8_00(qq + 32, dq + (i >> 1) * 256 + (i & 1) * 2, mkdesc(SD + O_LN, 0, 128, 0), i | LB == 4);
      }
      wg_commit();
    };
    auto lnt1 = [&]() {
      if (LB != 4) { wg_wait<0>(); regfence<36>(qq); }
      float z[2];
#pragma unroll
      for (int i = 0; i < 2; i++) {
        float t[4];
#pragma unroll
        for (int k = 0; k < 4; k++) t[k] = r & 1 ? qq[8 * k + 6 * i + 1] : qq[8 * k + 6 * i];
        z[i] = w & 2 ? w & 1 ? t[3] : t[2] : w & 1 ? t[1] : t[0];
      }
      const uint32_t a = sb + O_GB + r * 64 + w * 16;
      if (c == 0) sts64(a, __float_as_uint(qq[32]), __float_as_uint(qq[34]));
      if (c == r >> 1) sts64(a + 8, __float_as_uint(z[0]), __float_as_uint(z[1]));
      __syncwarp();
      if (lane == 0) mbar_arrive(BAR(B_PR));
      if (lead) TSTAMP(59);
    };
    auto ln1 = [&]() {
        if (LT) { lnt0(); lnt1(); return; }
        float z[4] = {0.f, 0.f, 0.f, 0.f};
        auto acc = [&](uint32_t v) { const float f = blo(v), g = bhi(v); z[0] += f; z[1] = fmaf(f, f, z[1]); z[2] += g; z[3] = fmaf(g, g, z[3]); };
        uint32_t a = sb + O_REG + w * 256 + (lane & 15) * 16 + (lane & 16) * 64;
        mbar_wait(BAR(B_QIN), 0);
        if (lead) TSTAMP(9);
        uint4 x = lds128(a), y = lds128(a + 2048);
#pragma unroll 1
        for (int i = 0; i < 5; i++) {
          a += 4096;
          acc(x.x); acc(x.y); acc(x.z); acc(x.w);
          x = lds128(a);
          edge(i);
          acc(y.x); acc(y.y); acc(y.z); acc(y.w);
          y = lds128(a + 2048);
        }
        z[0] += z[2]; z[1] += z[3];
#pragma unroll
        for (int i = 0; i < 3; i++) { z[0] += __shfl_xor_sync(0xffffffffu, z[0], 1 << i * i); z[1] += __shfl_xor_sync(0xffffffffu, z[1], 1 << i * i); }
        z[0] *= 1.f / D_;
        const float rs = rbf(rsqrtf(fmaxf(z[1] * (1.f / D_) - z[0] * z[0], 0.f) + 1e-5f));
        sts32(sb + O_LN + w * 16 + (lane & 12), pack2(rs, -z[0] * rs));
        __syncwarp();
        if (lane == 0) mbar_arrive(BAR(B_PR));
        if (lead) TSTAMP(59);
    };
#pragma unroll 1
    for (int it = 0; GA || it < 5 - KO * isE; it++) {
      const int n = (isE ? KO ? 0x7730 : 0x77430 : KO ? 0x74210 : 0x77210) >> 4 * it & 7, j = (isE ? KO ? 0x7317 : 0x73177 : 0x42077) >> 4 * it & 7;
      if (n < 5) {
      const int tg = lane & 7;
      const bool real = it | isE;
      const uint32_t a = sb + kreg(n) + tg * 64 + ((w ^ (tg >> 1)) << 4) + (lane >> 3) * 4;
      if (LB == 3 && n == 4) { lnt0(); lnt1(); }
      if (it) mbar_wait(BAR(B_K + n), 0); else if (isE) first();
      if (lead && real) TSTAMP(69 + n);
      uint32_t kk[11], x[8];
      ep = lds32(sb + O_EP) + 1;
      const uint4 sw = lds128(sb + kreg(n) + 5632 + w * 64 + (lane & 24) * 2);
#pragma unroll
      for (int i = 0; i < 11; i++) kk[i] = lds32(a + (i < 3 ? 4096 + i * 512 : (i - 3) * 512));
#pragma unroll
      for (int i = 0; i < 8; i++) x[7 - i] = lds32(a + voff(n) + i * 512);
      const uint32_t w0 = prmt(sw.x, sw.z, 0x5410), w1 = prmt(sw.x, sw.z, 0x7632), w2 = prmt(sw.y, sw.w, 0x5410), w3 = prmt(sw.y, sw.w, 0x7632);
#pragma unroll
      for (int i = 0; i < 8; i++) x[7 - i] = hmul2(hfma2(kk[i + 3], w0, hfma2(kk[i + 2], w1, hfma2(kk[i + 1], w2, hmul2(kk[i], w3)))), x[7 - i]);
      hint_addp(!w && (PK ? it : real), g_sync + Y_KV + (n * 4 + (b & 3)) * 32);
      const int tw = (~tb & 7) ^ ((~lane & 1) << 2);
#pragma unroll
      for (int i = 0; i < 4; i++) x[2 * i] = settag(x[2 * i], tw == i ? 0x00010001u : 0u, -(ep & 1));
      const uint32_t o = page(G_KV + n, (b & 3) * 32 + w * 8 + (lane >> 3) * 2) + 4080 - tb * 128 - tg * 16;
      stg128p(real, ps + o, prmt(x[0], x[1], 0x5410), prmt(x[2], x[3], 0x5410), prmt(x[4], x[5], 0x5410), prmt(x[6], x[7], 0x5410));
      stg128p(real, ps + o + 4096, prmt(x[0], x[1], 0x7632), prmt(x[2], x[3], 0x7632), prmt(x[4], x[5], 0x7632), prmt(x[6], x[7], 0x7632));
      if (lead) TSTAMP(real ? 64 + n : 62);
      if (it == 0) {
        if (!isE) first();
        if (PK && isE) {
          const uint32_t o = (tid & 127) * 32 + (lane & 16);
          uint4 u, v;
          int k = 0;
          while (clk() - t_start < T_P) {}
          do { u = ldr4((const uint32_t*)(ps + (page(G_KV, b) + o))); v = ldr4((const uint32_t*)(ps + (page(G_KV, b) + (o ^ 16)))); }
          while (__any_sync(0xffffffffu, ((r & 2 ? r & 1 ? u.w : u.z : r & 1 ? u.y : u.x) ^ ep) & 1) && ++k < 100000);
          sts128(sb + bnd(0) + U_KV + o, u.x, u.y, u.z, u.w);
          sts128(sb + bnd(0) + U_KV + (o ^ 16), v.x, v.y, v.z, v.w);
          fence_async_smem();
          __syncwarp();
          if (lane == 0) mbar_arrive(BAR(B_OK));
          if (lead) TSTAMP(2);
        }
        asm volatile("barrier.cluster.wait.aligned;" ::: "memory");
        mbar_wait(BAR(B_PL + isE), 0);
        aload(isE);
      }
      }
      if (LJ == 1 && LB == 1 && j == 3) ln1();
      if (b < (GA ? 20 * NE : 120) && it == (isE ? grp || GE != 3 ? grp + 2 - KO : 9 : grp || GE != 3 ? 9 : 3)) gemv();
      if (LJ == 1 && LB == 2 && j == 3) ln1();
      if (j < 5) {
      const int u = tid & 127;
      const uint32_t pb = sb + (bnd(j) | 16384);
      float d[128];
      mbar_wait(BAR(B_OK + j), 0);
      if (lead) TSTAMP(53 + j);
      const uint64_t db = mkdesc(SD + U_KV, 16, 128, 0) | bnd(j) >> 4;
      wg_fence();
        wgmma_rs_32_0(d + 0, A[0], A[1], A[2], A[3], db + 0, 0);
        wgmma_rs_32_0(d + 16, A[0], A[1], A[2], A[3], db + 32, 0);
        wgmma_rs_32_0(d + 32, A[0], A[1], A[2], A[3], db + 64, 0);
        wgmma_rs_32_0(d + 48, A[0], A[1], A[2], A[3], db + 96, 0);
        wgmma_rs_32_0(d + 0, A[4], A[5], A[6], A[7], db + 16, 1);
        wgmma_rs_32_0(d + 16, A[4], A[5], A[6], A[7], db + 48, 1);
        wgmma_rs_32_0(d + 32, A[4], A[5], A[6], A[7], db + 80, 1);
        wgmma_rs_32_0(d + 48, A[4], A[5], A[6], A[7], db + 112, 1);
        wgmma_rs_32_0(d + 0, A[8], A[9], A[10], A[11], db + 32, 1);
        wgmma_rs_32_0(d + 16, A[8], A[9], A[10], A[11], db + 64, 1);
        wgmma_rs_32_0(d + 32, A[8], A[9], A[10], A[11], db + 96, 1);
        wgmma_rs_32_0(d + 64, A[0], A[1], A[2], A[3], db + 128, 0);
        wgmma_rs_32_0(d + 0, A[12], A[13], A[14], A[15], db + 48, 1);
        wgmma_rs_32_0(d + 16, A[12], A[13], A[14], A[15], db + 80, 1);
        wgmma_rs_32_0(d + 32, A[12], A[13], A[14], A[15], db + 112, 1);
        wgmma_rs_32_0(d + 48, A[8], A[9], A[10], A[11], db + 128, 1);
        wgmma_rs_32_0(d + 0, A[16], A[17], A[18], A[19], db + 64, 1);
        wgmma_rs_32_0(d + 16, A[16], A[17], A[18], A[19], db + 96, 1);
        wgmma_rs_32_0(d + 32, A[16], A[17], A[18], A[19], db + 128, 1);
        wgmma_rs_32_0(d + 64, A[4], A[5], A[6], A[7], db + 144, 1);
        wgmma_rs_32_0(d + 0, A[20], A[21], A[22], A[23], db + 80, 1);
        wgmma_rs_32_0(d + 16, A[20], A[21], A[22], A[23], db + 112, 1);
        wgmma_rs_32_0(d + 48, A[12], A[13], A[14], A[15], db + 144, 1);
        wgmma_rs_32_0(d + 32, A[20], A[21], A[22], A[23], db + 144, 1);
        wgmma_rs_32_0(d + 0, A[24], A[25], A[26], A[27], db + 96, 1);
        wgmma_rs_32_0(d + 16, A[24], A[25], A[26], A[27], db + 128, 1);
        wgmma_rs_32_0(d + 80, A[0], A[1], A[2], A[3], db + 160, 0);
        wgmma_rs_32_0(d + 64, A[8], A[9], A[10], A[11], db + 160, 1);
        wgmma_rs_32_0(d + 0, A[28], A[29], A[30], A[31], db + 112, 1);
        wgmma_rs_32_0(d + 16, A[28], A[29], A[30], A[31], db + 144, 1);
        wgmma_rs_32_0(d + 48, A[16], A[17], A[18], A[19], db + 160, 1);
        wgmma_rs_32_0(d + 32, A[24], A[25], A[26], A[27], db + 160, 1);
        wgmma_rs_32_0(d + 0, A[32], A[33], A[34], A[35], db + 128, 1);
        wgmma_rs_32_0(d + 16, A[32], A[33], A[34], A[35], db + 160, 1);
        wgmma_rs_32_0(d + 80, A[4], A[5], A[6], A[7], db + 176, 1);
        wgmma_rs_32_0(d + 64, A[12], A[13], A[14], A[15], db + 176, 1);
        wgmma_rs_32_0(d + 0, A[36], A[37], A[38], A[39], db + 144, 1);
        wgmma_rs_32_0(d + 48, A[20], A[21], A[22], A[23], db + 176, 1);
        wgmma_rs_32_0(d + 32, A[28], A[29], A[30], A[31], db + 176, 1);
        wgmma_rs_32_0(d + 16, A[36], A[37], A[38], A[39], db + 176, 1);
        wgmma_rs_32_0(d + 0, A[40], A[41], A[42], A[43], db + 160, 1);
        wgmma_rs_32_0(d + 96, A[0], A[1], A[2], A[3], db + 192, 0);
        wgmma_rs_32_0(d + 80, A[8], A[9], A[10], A[11], db + 192, 1);
        wgmma_rs_32_0(d + 64, A[16], A[17], A[18], A[19], db + 192, 1);
        wgmma_rs_32_0(d + 0, A[44], A[45], A[46], A[47], db + 176, 1);
        wgmma_rs_32_0(d + 48, A[24], A[25], A[26], A[27], db + 192, 1);
        wgmma_rs_32_0(d + 32, A[32], A[33], A[34], A[35], db + 192, 1);
        wgmma_rs_32_0(d + 16, A[40], A[41], A[42], A[43], db + 192, 1);
        wgmma_rs_32_0(d + 0, A[48], A[49], A[50], A[51], db + 192, 1);
        wgmma_rs_32_0(d + 96, A[4], A[5], A[6], A[7], db + 208, 1);
        wgmma_rs_32_0(d + 80, A[12], A[13], A[14], A[15], db + 208, 1);
        wgmma_rs_32_0(d + 64, A[20], A[21], A[22], A[23], db + 208, 1);
        wgmma_rs_32_0(d + 48, A[28], A[29], A[30], A[31], db + 208, 1);
        wgmma_rs_32_0(d + 32, A[36], A[37], A[38], A[39], db + 208, 1);
        wgmma_rs_32_0(d + 16, A[44], A[45], A[46], A[47], db + 208, 1);
        wgmma_rs_32_0(d + 0, A[52], A[53], A[54], A[55], db + 208, 1);
        wgmma_rs_32_0(d + 112, A[0], A[1], A[2], A[3], db + 224, 0);
        wgmma_rs_32_0(d + 96, A[8], A[9], A[10], A[11], db + 224, 1);
        wgmma_rs_32_0(d + 80, A[16], A[17], A[18], A[19], db + 224, 1);
        wgmma_rs_32_0(d + 64, A[24], A[25], A[26], A[27], db + 224, 1);
        wgmma_rs_32_0(d + 48, A[32], A[33], A[34], A[35], db + 224, 1);
        wgmma_rs_32_0(d + 32, A[40], A[41], A[42], A[43], db + 224, 1);
        wgmma_rs_32_0(d + 16, A[48], A[49], A[50], A[51], db + 224, 1);
        wgmma_rs_32_0(d + 0, A[56], A[57], A[58], A[59], db + 224, 1);
        wgmma_rs_32_0(d + 112, A[4], A[5], A[6], A[7], db + 240, 1);
        wgmma_rs_32_0(d + 96, A[12], A[13], A[14], A[15], db + 240, 1);
        wgmma_rs_32_0(d + 80, A[20], A[21], A[22], A[23], db + 240, 1);
        wgmma_rs_32_0(d + 64, A[28], A[29], A[30], A[31], db + 240, 1);
        wgmma_rs_32_0(d + 48, A[36], A[37], A[38], A[39], db + 240, 1);
        wgmma_rs_32_0(d + 32, A[44], A[45], A[46], A[47], db + 240, 1);
        wgmma_rs_32_0(d + 16, A[52], A[53], A[54], A[55], db + 240, 1);
        wgmma_rs_32_0(d + 0, A[60], A[61], A[62], A[63], db + 240, 1);
      wg_commit();
      bar_sync(5 + isE, 128);
      if (WI == 2 && j == 1 && w == 1 && (uint32_t)(b - 40) < 40 && elect()) { loadwm(); TSTAMP(109); }
      if (ER) release(0140242142 >> 6 * j);
      if (!PW && j < 3) mbar_wait(BAR(B_PL + 2 + j), 0);
      const uint32_t yoff = pb + w * 2048 + (127 + 2 * w - lane) * 16;
      const uint32_t yoff0 = yoff + (lane < 2 * w ? -2048 : 8192), yoff4 = yoff + (lane < 2 * w ? 6144 : 0);
      wg_wait<0>();
      regfence<128>(d);
      if (j == 4) bar_arrive(8, 256);
      if (j == 4) bar_sync(5, 128);
      if (lead) TSTAMP(42 + j);
      if (GA == 1 && j == 3 && b < 120 && grp == 2) gemv();
      if (EY == 2 && lead) hint_add(g_sync + Y_Y + j * 32);
#pragma unroll
      for (int z = 0; z < 8; z++) {
        uint32_t e[4];
#pragma unroll
        for (int i = 0; i < 4; i++) {
          const int x = 4 * z + i;
          e[i] = x < 31 ? pack2(d[4 * x] + d[4 * x + 6], d[4 * x + 1] + d[4 * x + 7]) : pack2(d[4 * x], d[4 * x + 1]);
        }
        if (z == 0 && c < w) e[0] = 0;
        stsm4t(z == 0 ? yoff0 : z == 4 ? yoff4 : z < 4 ? yoff + 8192 - 512 * z : yoff - 512 * (z - 4), e[0], e[1], e[2], e[3]);
      }
      uint8_t* g = ps + page(G_Y + j, u >> 1) + ((b & 97) | (b & 6) << 2 | (b & 24) >> 2) * 32 + ((u ^ (b >> 4)) & 1) * 16;
      if (GA == 2 && j == 3 && b < 120 && grp == 2) gemv();
      if (EY & 1) hint_addp(!w && (EY == 1 || !j), g_sync + Y_Y + j * 32);
      bar_sync(5 + isE, 128);
      if (EY >= 4) hint_addp(!w && (EY == 4 || j), g_sync + Y_Y + j * 32);
#pragma unroll
      for (int i = 0; i < 2; i++) {
        const uint32_t pa = pb + u * 16 + i * 8192;
        const uint4 p0 = lds128(pa), p1 = lds128(pa + 2048), p2 = lds128(pa + 4096), p3 = lds128(pa + 6144);
        stg128(g + (i << 18), settag(hadd2(hadd2(p0.x, p1.x), hadd2(p2.x, p3.x)), 1, ep), hadd2(hadd2(p0.y, p1.y), hadd2(p2.y, p3.y)),
               hadd2(hadd2(p0.z, p1.z), hadd2(p2.z, p3.z)), hadd2(hadd2(p0.w, p1.w), hadd2(p2.w, p3.w)));
      }
      if (WI == 2 && j == 1 && w == 1 && (uint32_t)(b - 80) < 40 && elect()) { loadwm(); TSTAMP(109); }
      if (EY % 3 == 0) hint_addp(w == 3 && (!EY || j), g_sync + Y_Y + j * 32);
      if (lead) TSTAMP(84 + j);
      if (!ER) release(0140242142 >> 6 * j);
      if (!LB && j == LJ) ln1();
      if (LB == 4) {
#pragma unroll
        for (int i = 0; i < 36; i++) qq[i] = 0.f;
        if (j == LJ) lnt0();
      }
      if (GA && j >= 3) break;
      if (PW && j < 3) mbar_wait(BAR(B_PL + 2 + j), 0);
      if (LB == 5 && j == LJ) { lnt0(); aload(LJ + 2); lnt1(); } else
      if (j < 3) aload(j + 2);
      if (LB == 4) { wg_wait<0>(); regfence<36>(qq); }
      if (LB == 4 && j == LJ) lnt1();
      }
    }
    bar_sync(5 + isE, 128);
    release(isE ? 016 : 010);
    const int rh = isE;
    uint32_t hA[96];
    const uint32_t hb = sb + (isE ? O_REG : 24576) + w * 2048, hs = isE ? 8192 : SLOT;
    auto publish = [&](int kq) {
      asm volatile("st.async.weak.shared::cluster.mbarrier::complete_tx::bytes.v4.b32 [%0], {%1,%2,%3,%4}, [%5];" ::"r"(mapa(hb + lane * 16, kh ^ 1) + (kq >> 2) * hs + (kq & 3) * 512),
                   "r"(hA[4 * kq]), "r"(hA[4 * kq + 1]), "r"(hA[4 * kq + 2]), "r"(hA[4 * kq + 3]), "r"(mapa(BAR(B_HF + isE * 3), kh ^ 1) + (kq >> 2) * 8) : "memory");
      if (kq == 3 && tid == 256) TSTAMP(117);
    };
    {
      float ag[96], au[96], iv[2];
      int slot = 4, prev = 0, s = 0;
      int v0, vo;
      uint32_t vg;
      { ROLE; v0 = min(vr, VR) * 4; vo = (2 * vt + isE) * 256; vg = (fs * 5 + vr) * 384 + (2 * vt + isE) * 64 + 16 * w + r; }
      const uint32_t dbase = mkdesc(sb, 4096, 0, 0);
      uint32_t ck = sb + 24576 + rh * 4096 + w * 1024 + lane * 32 + (r & 1) * 16;
      keep(ck);
      const uint32_t emp = mapa(BAR(B_EMPTY), tid & 1);
      if (isE) bar_sync(8, 256);
      auto check = [&](uint32_t tag) {
        if ((tag ^ ep) & 1) refetch(ps + (lds32(sb + O_XT + s * 4) + rh * 16384 + (tid & 127) * 32), (r & 1) * 16, (ck + slot * SLOT) & ~31u, ep);
        __syncwarp();
        if (lead) TS3(isE, s);
        if (s && s < 20 && (s & 3) == 0 && tid == 128) TSTAMP(37 + (s >> 2));
        if (s == LH + LEAD * isE) { if (isE) bar_arrive(7, 256); else bar_sync(7, 256); }
      };
      auto stage = [&](float* vv) {
        const uint32_t dl = dbase + slot * (SLOT >> 4);
        const uint64_t dg = mkdesc(0, 0, 1024, 1) | dl, da = mkdesc(0, 0, 512, 2) | (dl + ((24576 + rh * 4096) >> 4));
        wg_wait<1>();
        wg_fence();
        if (vv) {
          wgmma_ss_8_10(vv, dg + vo, mkdesc(sb + O_CS, 32, 128, 0) + (s & 3) * 8, s & 3);
          wgmma_ss_8_10(vv, dg + vo + 128, mkdesc(sb + O_CS, 32, 128, 0) + (s & 3) * 8 + 4, 1);
          wg_commit();
        }
        const int sd = s, nx = s == 19 ? 5 : slot == 5 ? 0 : slot + 1;
        const uint32_t par = (0x1c0fc0 >> ++s) & 1;
        uint32_t in, tag;
        auto peek = [&]() { asm volatile("{ .reg .pred p; setp.ne.u32 p, %2, 0; @p ld.shared.u32 %0, [%1]; }" : "=r"(tag) : "r"(addu(ck, nx * SLOT)), "r"(in) : "memory"); };
        if (RP == 0) in = TW ? mbar_try(BAR(B_FULL + nx), par) : mbar_test(BAR(B_FULL + nx), par);
        wgmma_ss_192_01(ag, da, dg, sd);
        if (s > 2 && (tid & 126) == 0) mbar_arrive_cl(addu(emp, prev & 63));
        if (RP == 0) peek();
        if (RP == 1) in = TW ? mbar_try(BAR(B_FULL + nx), par) : mbar_test(BAR(B_FULL + nx), par);
        wgmma_ss_192_01(au, da, mkdesc(0, 0, 1024, 1) | (dl + 768), sd);
        if (RP == 1) peek();
        if (RP == 2) in = TW ? mbar_try(BAR(B_FULL + nx), par) : mbar_test(BAR(B_FULL + nx), par);
        wgmma_ss_192_01(ag, mkdesc(0, 0, 512, 2) | ((uint32_t)da + 2), mkdesc(0, 0, 1024, 1) | (dl + 128), 1);
        if (RP == 2) peek();
        wgmma_ss_192_01(au, mkdesc(0, 0, 512, 2) | ((uint32_t)da + 2), mkdesc(0, 0, 1024, 1) | (dl + 896), 1);
        wg_commit();
        prev = prev >> 8 | slot << 11;
        slot = nx;
        if (!in) { mbar_wait(BAR(B_FULL + nx), par); tag = lds32(addu(ck, nx * SLOT)); }
        check(tag);
      };
      mbar_wait(BAR(B_FULL + 4), 0);
      check(lds32(ck + 4 * SLOT));
      if (lead) TSTAMP(22 + isE);
#pragma unroll 1
      for (int end = v0, k = 0; k < 2; end = 20, k++) {
#pragma unroll 1
        while (s < end) stage(nullptr);
        if (k == 0) {
          float vv[4];
          mbar_wait(BAR(B_CS), 0);
          if (EVV) hint_addp(1, g_sync + Y_VV + vg / 1920 * 32);
#pragma unroll 1
          do stage(vv); while (s & 3);
          wg_wait<1>();
          regfence<4>(vv);
          if (c == 0) { str(g_vv + vg, settag(pack2(vv[0], vv[1]), 1, ep)); str(g_vv + vg + 8, settag(pack2(vv[2], vv[3]), 1, ep)); }
          __syncwarp();
          if (!EVV) hint_addp(1, g_sync + Y_VV + vg / 1920 * 32);
        }
      }
      {
        if (tid == 128) str(g_sync + Y_EP + b * 32, ep);
        wg_wait<1>();
        if ((tid & 126) == 0) mbar_arrive_cl(emp + 32);
        mbar_wait(BAR(B_ST + rh), 0);
        const float2 sa = lds64f(sb + O_ST + rh * 512 + w * 128 + r * 8), sc = lds64f(sb + O_ST + rh * 512 + w * 128 + r * 8 + 64);
        const uint32_t a0 = __float_as_uint(sa.x), a1 = __float_as_uint(sc.x);
        iv[0] = sa.y; iv[1] = sc.y;
        mbar_wait(BAR(B_VV), 0);
        const uint64_t dp = mkdesc(sb + O_BP, 16, 128, 0);
        wg_fence();
        wgmma_rs_192_0(ag, a0, a1, 0, 0, dp, 1);
        wgmma_rs_192_0(au, a0, a1, 0, 0, dp + 192, 1);
        wg_commit();
        wg_wait<1>();
        if ((tid & 126) == 0) mbar_arrive_cl(emp + 40);
        mbar_wait(BAR(isE ? B_ST : B_EMPTY + 2), !isE);
        wg_wait<0>();
      }
      regfence<96>(ag); regfence<96>(au);
      if (lead) TSTAMP(24 + isE);
#pragma unroll
      for (int kq = 0; kq < 12; kq++) {
#pragma unroll
        for (int i = 0; i < 4; i++) hA[4 * kq + i] = pack2(ag[8 * kq + 2 * i] * iv[i & 1] * au[8 * kq + 2 * i], ag[8 * kq + 2 * i + 1] * iv[i & 1] * au[8 * kq + 2 * i + 1]);
        if (kq < 4 * NPUB) publish(kq);
      }
      if (lead) TSTAMP(50 + isE);
    }
    float o[2][32];
    float2 gb[8];
    const uint32_t stg = hb + (lane & 15) * 128 + (((lane >> 4) ^ (lane & 7)) << 4);
    const int row = (b >> 3) * 128 + rh * 64 + 16 * w;
    auto ldgb = [&](int fin) {
#pragma unroll
      for (int u = 0; u < 8; u++) gb[u] = lds64f(sb + O_GB + (ocol(b & 6, fin) + 8 * u + 2 * c) * 4);
      if (fin >= 3 && !FA) { if (elect()) bulk_wait_read<2>(); __syncwarp(); }
    };
    auto piece = [&](int fin, int u) {
      const float* x = o[fin & 1] + 8 * u;
      const float2 g0 = gb[2 * u], g1 = gb[2 * u + 1];
      stsm4((stg ^ u * 32) + fin % 3 * hs, pack2(x[0] * g0.x, x[1] * g0.y), pack2(x[2] * g0.x, x[3] * g0.y), pack2(x[4] * g1.x, x[5] * g1.y), pack2(x[6] * g1.x, x[7] * g1.y));
    };
    auto flush = [&](int fin) {
      fence_async_smem();
      __syncwarp();
      if (elect()) { tma2d_add(&p.m_out, hb + fin % 3 * hs, ocol(b, fin), row); bulk_commit(); }
    };
    uint32_t fo, fa;
    uint4 fv[4];
    if (FA) {
      fo = (row + (lane >> 3)) * (D_ * 2) + (lane & 7) * 16;
      fa = hb + (lane >> 3) * 128 + ((lane ^ lane >> 3) & 7) * 16;
      keep(fo); keep(fa);
    }
    auto fetch = [&](int fin) {
      __syncwarp();
#pragma unroll
      for (int i = 0; i < 4; i++) fv[i] = lds128((fa ^ (i & 1) * 64) + i * 512 + (FA ? fin % 3 * hs : 0));
    };
    auto add = [&](int fin) {
      const uint8_t* const g = p.out + (FA ? addu(fo, ocol(b, fin) * 2) : fo);
#pragma unroll
      for (int i = 0; i < 4; i++)
        asm volatile("red.relaxed.gpu.global.add.noftz.v4.bf16x2 [%0], {%1,%2,%3,%4};" ::"l"(g + i * (D_ * 8)), "r"(fv[i].x), "r"(fv[i].y), "r"(fv[i].z), "r"(fv[i].w) : "memory");
    };
    auto last = [&]() {
      ldgb(4);
      if (FA) return;
      fo = (row + (lane >> 3)) * (D_ * 2) + ocol(b, 4) * 2 + (lane & 7) * 16;
      fa = hb + hs + (lane >> 3) * 128 + ((lane ^ lane >> 3) & 7) * 16;
      if (FR) { keep(fo); keep(fa); }
    };
    unrolled<10>([&](auto I) {
      constexpr int s = I.v, e = s < 7 ? s : s - 7, src = s < 4 ? s >> 1 : s & 1, blk = s < 4 ? s & 1 : s >> 1;
      constexpr int fin = s == 3 ? 0 : blk - 1;
      const uint64_t dw = mkdesc(sb + w2entry(e), 1024 * s, 1024, 1);
      if (s == 3 || s >= 4 && !src) ldgb(fin);
      if (s == 4) { if (FA) fetch(0); mbar_wait(BAR(B_X1), 0); }
      mbar_wait(BAR(B_W2F + e), s >= 7);
      if (s == 6 && tid == 256) TSTAMP(123);
      TS2(3 * s);
      unrolled<12>([&](auto J) {
        constexpr int kk = J.v, n = s < 4 ? kk : src * 12 + kk;
        if (s == 2 && !(kk & 3)) {
          mbar_wait_cluster(BAR(B_HF + isE * 3 + (kk >> 2)), 0);
          if (kk == 0 && lead) TSTAMP(26 + isE);
#pragma unroll
          for (int i = kk; i < kk + 4; i++) {
            const uint4 v = lds128(hb + lane * 16 + (i >> 2) * hs + (i & 3) * 512);
            hA[48 + 4 * i] = v.x; hA[49 + 4 * i] = v.y; hA[50 + 4 * i] = v.z; hA[51 + 4 * i] = v.w;
          }
        }
        if (kk == 0 || s == 2 && !(kk & 3)) wg_fence();
        const uint32_t* h = hA + src * 48 + 4 * kk;
        wgmma_rs_64_1(o[blk & 1], h[0], h[1], h[2], h[3], dw + (kk >> 2) * (e == 6 ? SLOT >> 4 : 512) + (kk & 3) * 128, (src | kk) ? 1 : 0);
        if (s < 2 && (s * 12 + kk) % PUBD == PUBD - 1 && 4 * NPUB + (s * 12 + kk) / PUBD < 12) publish(4 * NPUB + (s * 12 + kk) / PUBD);
        if (kk == QD - 1 && s >= 1 && (s < 4 || !src)) {
          wg_commit();
          wg_wait<1>();
          if (s < 4 && lead) mbar_arrive(BAR(B_W2E + s - 1));
          if (s >= 3) regfence<32>(o[fin & 1]);
          if (s == 4) { if (FA) add(0); else flush(0); }
          TS2(3 * s + 2);
        }
        if (s == 3 && kk >= QD - 1 && (kk - QD + 1) % 2 == 0 && (kk - QD + 1) / 2 < 4) piece(0, (kk - QD + 1) / 2);
        constexpr int ps_ = s >= PA ? PS : 3, nf = QD - 1 + 3 * ps_ + (s >= PA ? FD : 6);
        if (s >= 4 && n >= QD - 1 && (n - QD + 1) % ps_ == 0 && (n - QD + 1) / ps_ < 4) piece(fin, (n - QD + 1) / ps_);
        if (FA && s >= 4 && n == nf - FA) fetch(fin);
        if (s >= 4 && n == nf) { if (FA) add(fin); else flush(fin); }
        if (FR >= 2 && s >= 8 && n == nf + FR - 1) { last(); edge(0); }
      });
      wg_commit();
      TS2(3 * s + 1);
    });
    if (FR < 2) { last(); mbar_wait(BAR(B_X1), 0); }
    wg_wait<0>();
    regfence<32>(o[0]);
    if (lead) TSTAMP(28 + isE);
#pragma unroll
    for (int u = 0; u < 4; u++) piece(4, u);
    if (FR) {
      fetch(4);
      add(4);
    } else flush(4);
    if (tid == 128) TSTAMP(119);
    if (!FA && elect()) bulk_wait_read<0>();
    if (tid == 256) TSTAMP(121);
    if (!isE) {
      if (lead) TSTAMP(31);
    }
  }
}

#define L2PROMO CU_TENSOR_MAP_L2_PROMOTION_L2_128B
typedef CUresult (*EncodeFn)(CUtensorMap*, CUtensorMapDataType, cuuint32_t, void*, const cuuint64_t*, const cuuint64_t*, const cuuint32_t*,
                             const cuuint32_t*, CUtensorMapInterleave, CUtensorMapSwizzle, CUtensorMapL2promotion, CUtensorMapFloatOOBfill);

void make_map(EncodeFn enc, CUtensorMap* m, const void* ptr, uint64_t inner, uint64_t outer, uint32_t bi, uint32_t bo, CUtensorMapSwizzle sw) {
  cuuint64_t d[2] = {inner, outer};
  cuuint64_t s[1] = {inner * 2};
  cuuint32_t bx[2] = {bi, bo};
  cuuint32_t e[2] = {1, 1};
  enc(m, CU_TENSOR_MAP_DATA_TYPE_BFLOAT16, 2, const_cast<void*>(ptr), d, s, bx, e, CU_TENSOR_MAP_INTERLEAVE_NONE, sw, L2PROMO,
      CU_TENSOR_MAP_FLOAT_OOB_FILL_NONE);
}

void make_map3(EncodeFn enc, CUtensorMap* m, const void* ptr, uint64_t d0, uint64_t d1, uint64_t d2, uint64_t s1, uint64_t s2, uint32_t b0, uint32_t b1, uint32_t b2,
               CUtensorMapSwizzle sw, uint64_t s3 = 0) {
  cuuint64_t d[4] = {d0, d1, d2, 2};
  cuuint64_t s[3] = {s1, s2, s3};
  cuuint32_t bx[4] = {b0, b1, b2, 2};
  cuuint32_t e[4] = {1, 1, 1, 1};
  enc(m, CU_TENSOR_MAP_DATA_TYPE_BFLOAT16, s3 ? 4 : 3, const_cast<void*>(ptr), d, s, bx, e, CU_TENSOR_MAP_INTERLEAVE_NONE, sw, L2PROMO,
      CU_TENSOR_MAP_FLOAT_OOB_FILL_NONE);
}

}

extern "C" void kernel_launch(void* const* d_in, const int* in_sizes, int n_in, void* d_out, int out_size) {
  (void)in_sizes; (void)n_in; (void)out_size;
  void* f = nullptr;
  cudaDriverEntryPointQueryResult qr;
  cudaGetDriverEntryPoint("cuTensorMapEncodeTiled", &f, cudaEnableDefault, &qr);
  EncodeFn enc = (EncodeFn)f;
  void* s;
  cudaGetSymbolAddress(&s, g_s);
  Params p = {};
  uint8_t* ps = (uint8_t*)(((uintptr_t)s + (2 << 20) - 1) & ~(uintptr_t)((2 << 20) - 1));
  make_map3(enc, &p.m_k, d_in[1], D_, S_ / 8, 8, 8 * D_ * 2, D_ * 2, 32, 8, 8, CU_TENSOR_MAP_SWIZZLE_64B);
  make_map3(enc, &p.m_kh, d_in[1], D_, S_ / 8, 8, 8 * D_ * 2, D_ * 2, 32, 8, 3, CU_TENSOR_MAP_SWIZZLE_64B);
  make_map3(enc, &p.m_v, d_in[2], D_, S_ / 8, 8, 8 * D_ * 2, D_ * 2, 32, 8, 8, CU_TENSOR_MAP_SWIZZLE_64B);
  make_map3(enc, &p.m_q, d_in[0], 32, S_, D_ / 32, D_ * 2, 64, 32, 16, D_ / 32, CU_TENSOR_MAP_SWIZZLE_64B);
  make_map3(enc, &p.m_wm, d_in[11], 6 * D_, 160, 4, 12 * D_, 160 * 12 * D_, 32, 160, 4, CU_TENSOR_MAP_SWIZZLE_64B);
  const int lo = (uintptr_t)d_in[7] < (uintptr_t)d_in[8] ? 7 : 8;
  make_map3(enc, &p.m_w1, d_in[lo], 64, D_, F_ / 64, F_ * 2, 128, 64, 32, 3, CU_TENSOR_MAP_SWIZZLE_128B, (uintptr_t)d_in[15 - lo] - (uintptr_t)d_in[lo]);
  make_map(enc, &p.m_w2, d_in[9], D_, F_, 64, 64, CU_TENSOR_MAP_SWIZZLE_128B);
  make_map(enc, &p.m_out, d_out, D_, S_, 64, 16, CU_TENSOR_MAP_SWIZZLE_128B);
  p.c = (const __nv_bfloat16*)d_in[10];
  p.wg = (const __nv_bfloat16*)d_in[7];
  p.wu = (const __nv_bfloat16*)d_in[8];
  p.w2 = (const __nv_bfloat16*)d_in[9];
  p.out = (uint8_t*)d_out;
  cudaFuncSetAttribute(fused_kernel, cudaFuncAttributeMaxDynamicSharedMemorySize, SMEM_BYTES);
  fused_kernel<<<128, 384, SMEM_BYTES, cudaStreamPerThread>>>((const uint8_t*)d_in[1], (uintptr_t)d_in[2] - (uintptr_t)d_in[1], (uintptr_t)d_in[3] - (uintptr_t)d_in[1],
                                                              (const __nv_bfloat16*)d_in[4], (const __nv_bfloat16*)d_in[5], ps, p);
}
```
